```python
import torch

def _softmax(x, axis=-1):
    return torch.softmax(x, dim=axis)
def _gelu(x):
    return torch.nn.functional.gelu(x, approximate="tanh")
def _silu(x):
    return torch.nn.functional.silu(x)
def _sigmoid(x):
    return torch.sigmoid(x)
def _layernorm(x, axis=-1, eps=1e-5):
    m = x.mean(dim=axis, keepdim=True)
    v = x.var(dim=axis, keepdim=True, unbiased=False)
    return (x - m) / torch.sqrt(v + eps)
def _scatter_add(tgt, idx, src, axis=0):
    return tgt.clone().index_add_(axis, idx, src)
def _segment_sum(src, seg, n):
    out = torch.zeros((n,) + src.shape[1:], dtype=src.dtype)
    return out.index_add_(0, seg, src)
def _pad(x, pw):
    flat = tuple(v for pair in reversed(pw) for v in pair)
    return torch.nn.functional.pad(x, flat)

kernel_name = 'recurrent_scan__gqa_block_cached__moe_arch_mod__prompt'

def setup_inputs():

    _w = (lambda a: (lambda t: t.to(torch.bfloat16) if t.is_floating_point() else t)(torch.as_tensor(a)))
    def _A_setup():
        B, Sq, D = 1, 2048, 576
        Hq, Hkv, Sk, Dh = 32, 16, 2048, 128
        assert Hq % Hkv == 0, (Hq, Hkv)
        return {
            "x": _w((lambda *s: torch.randn(*s, dtype=torch.bfloat16) * 0.05)(B, Sq, D)),
            "k_cache": _w((lambda *s: torch.randn(*s, dtype=torch.bfloat16) * 0.8)(B, Hkv, Sk, Dh)),
            "v_cache": _w((lambda *s: torch.randn(*s, dtype=torch.bfloat16) * 0.2)(B, Hkv, Sk, Dh)),
            "wq": _w((lambda *s: torch.randn(*s, dtype=torch.bfloat16) * 0.8)(D, Hq * Dh) * (D ** -0.5)),
            "wo": _w((lambda *s: torch.randn(*s, dtype=torch.bfloat16) * 0.2)(Hq * Dh, D) * ((Hq * Dh) ** -0.5)),
        }
    _A_in = _A_setup()

    def _B_setup():
        B, S, D, F, C = 1, 2048, 576, 4608, 8
        return {
            "x": _w((lambda *s: torch.randn(*s, dtype=torch.bfloat16) * 0.05)(B, S, D)),
            "w_r": _w((lambda *s: torch.randn(*s, dtype=torch.bfloat16) * 0.2)(D)),
            "w_gate": _w((lambda *s: torch.randn(*s, dtype=torch.bfloat16) * 0.1)(D, F)),
            "w_up": _w((lambda *s: torch.randn(*s, dtype=torch.bfloat16) * 0.1)(D, F)),
            "w_down": _w((lambda *s: torch.randn(*s, dtype=torch.bfloat16) * 0.1)(F, D)),
        }
    _B_in = _B_setup()

    return {
        "A_x": _A_in["x"],
        "A_k_cache": _A_in["k_cache"],
        "A_v_cache": _A_in["v_cache"],
        "A_wq": _A_in["wq"],
        "A_wo": _A_in["wo"],
        "B_x": _B_in["x"],
        "B_w_r": _B_in["w_r"],
        "B_w_gate": _B_in["w_gate"],
        "B_w_up": _B_in["w_up"],
        "B_w_down": _B_in["w_down"],
    }

def reference(A_x, A_k_cache, A_v_cache, A_wq, A_wo, B_x, B_w_r, B_w_gate, B_w_up, B_w_down):
    def _A_ref(x, k_cache, v_cache, wq, wo):
        B, Sq, D = x.shape
        Hq, Dh = 32, 128
        Hkv = k_cache.shape[1]
        rep = Hq // Hkv
        q = (lambda x, *d: x.permute(*d))((x @ wq).reshape(B, Sq, Hq, Dh), 0, 2, 1, 3)
        k = (lambda x, n, axis: torch.repeat_interleave(x, n, dim=axis))(k_cache, rep, axis=1)
        v = (lambda x, n, axis: torch.repeat_interleave(x, n, dim=axis))(v_cache, rep, axis=1)
        scores = torch.einsum("bhqd,bhkd->bhqk", q, k) * (Dh ** -0.5)
        p = _softmax(scores, axis=-1)
        o = torch.einsum("bhqk,bhkd->bhqd", p, v)
        return (lambda x, *d: x.permute(*d))(o, 0, 2, 1, 3).reshape(B, Sq, Hq * Dh) @ wo

    def _B_ref(x, w_r, w_gate, w_up, w_down):
        B, S, D = x.shape
        C = 8
        r = x @ w_r
        idx = torch.argsort(-r, axis=-1)[:, :C]
        idx_e = (lambda x, n, axis: torch.repeat_interleave(x, n, dim=axis))(idx.reshape(B, C, 1), D, axis=2)
        x_sel = (lambda x, i, axis: torch.take_along_dim(x, i, dim=axis))(x, idx_e, axis=1)
        g = _silu(x_sel @ w_gate)
        u = x_sel @ w_up
        y = (g * u) @ w_down
        r_sel = _sigmoid((lambda x, i, axis: torch.take_along_dim(x, i, dim=axis))(r, idx, axis=1))
        y = y * r_sel.reshape(B, C, 1)
        b_off = (torch.arange(B) * S).reshape(B, 1)
        flat_idx = (idx + b_off).reshape(B * C)
        zero = (x * 0.0).reshape(B * S, D)
        upd = _scatter_add(zero, flat_idx, y.reshape(B * C, D), axis=0)
        return x + upd.reshape(B, S, D)

    x = A_x
    xn = _layernorm(x, axis=-1)
    s = _A_ref(xn, A_k_cache, A_v_cache, A_wq, A_wo)
    g = _silu(_B_ref(xn, B_w_r, B_w_gate, B_w_up, B_w_down))
    return x + s * g
```

```cpp
#include <cuda_runtime.h>
#include <cuda_bf16.h>
#include <cuda.h>
#include <stdint.h>

namespace {

constexpr int SEQ = 2048, DM = 576, DH = 128, FF = 4608, TOPC = 8;
constexpr int N_ATT_CTA = 128, N_CTA = 132;
constexpr int THREADS = 384;

constexpr uint32_t SM_RING = 0;
constexpr uint32_t STAGE = 32768;
constexpr uint32_t SM_SLOT = 131072;
constexpr uint32_t FSTAGE = 24576;
constexpr uint32_t SM_XSEL = 196608;
constexpr uint32_t SM_H = 205824;
constexpr uint32_t SM_MISC = 229376;
constexpr uint32_t SM_FULL = SM_MISC, SM_BAR_MISC = SM_MISC + 64, SM_BAR_XG = SM_MISC + 72, SM_XFULL = SM_MISC + 96,
                   SM_EMPTY = SM_MISC + 120, SM_TAG = SM_MISC + 288, SM_IDX = SM_MISC + 304, SM_TOPK = SM_MISC + 336,
                   SM_STATS = SM_MISC + 400;
constexpr uint32_t SM_TOTAL = SM_MISC + 1424;
constexpr uint32_t SM_X = SM_MISC - 147456;

constexpr int BAR_GATE = 6, BAR_HELPER = 7, BAR_OA = 8;
constexpr int NST_Q = 20, NST_KV = 128, NST_O = 18;
#define X_ORDER 0
#define X_PF 3
#define X_PFQ 2
#define X_C0 32
#define X_C1 56
constexpr float SM_SCALE_LOG2 = 0.08838834764831845f * 1.4426950408889634f;

struct Scratch {
  uint4 part[16 * 64 * 2 * 4 * 128];
  uint4 gate[SEQ * DM / 8];
  float r[SEQ];
  float2 stats[SEQ];
  float ypart[4 * TOPC * DM];
  float upd[TOPC * DM];
  int idx[32];
  unsigned launch[160];
  unsigned rcnt, pad0[31], ycnt, pad1[31], ffn_flag, pad2[31];
};
__device__ __align__(1024) Scratch g_scratch;

__device__ __forceinline__ void profq(int) {}
__device__ __forceinline__ void prof(int, int, int = 0) {}
__device__ __forceinline__ void profc(int, int) {}

__device__ __forceinline__ uint32_t smem_u32(const void* p) { return (uint32_t)__cvta_generic_to_shared(p); }
__device__ __forceinline__ void mbar_init(uint32_t bar, uint32_t cnt) {
  asm volatile("mbarrier.init.shared::cta.b64 [%0], %1;" ::"r"(bar), "r"(cnt) : "memory");
}
__device__ __forceinline__ void mbar_expect_tx(uint32_t bar, uint32_t bytes) {
  asm volatile("mbarrier.arrive.expect_tx.shared::cta.b64 _, [%0], %1;" ::"r"(bar), "r"(bytes) : "memory");
}
__device__ __forceinline__ void mbar_arrive(uint32_t bar) {
  asm volatile("mbarrier.arrive.shared::cta.b64 _, [%0];" ::"r"(bar) : "memory");
}
__device__ __forceinline__ void mbar_arrive_cluster(uint32_t bar_cluster_addr) {
  asm volatile("mbarrier.arrive.shared::cluster.b64 _, [%0];" ::"r"(bar_cluster_addr) : "memory");
}
template <int ID>
__device__ __forceinline__ void mbar_arrive_cluster_now(uint32_t bar_cluster_addr, bool pred) {
  asm volatile("{\n.reg .pred p, q;\nsetp.ne.u32 p, %1, 0;\nsetp.eq.u32 q, %2, %3;\n"
               "ARR_LOOP:\n@p mbarrier.arrive.shared::cluster.b64 _, [%0];\n@q bra.uni ARR_LOOP;\n}"
               ::"r"(bar_cluster_addr), "r"((uint32_t)pred), "r"(blockIdx.y), "n"(ID) : "memory");
}
__device__ __forceinline__ void block_fence(int id) {
  asm volatile("{\n.reg .pred q;\nsetp.eq.u32 q, %0, %1;\nBF_LOOP:\n@q st.volatile.shared.u32 [%0], %0;\n@q bra.uni BF_LOOP;\n}"
               ::"r"(blockIdx.y), "r"(id) : "memory");
}
__device__ __forceinline__ bool mbar_test(uint32_t bar, uint32_t parity) {
  uint32_t ok;
  asm volatile("{\n.reg .pred p;\nmbarrier.test_wait.parity.shared::cta.b64 p, [%1], %2;\nselp.u32 %0, 1, 0, p;\n}"
               : "=r"(ok) : "r"(bar), "r"(parity) : "memory");
  return ok;
}
__device__ __forceinline__ void mbar_wait(uint32_t bar, uint32_t parity) {
  asm volatile("{\n.reg .pred p, q;\n.reg .u32 n;\nmov.u32 n, 0;\n"
               "WAIT_LOOP:\nmbarrier.try_wait.parity.shared::cta.b64 p, [%0], %1;\n"
               "add.u32 n, n, 1;\nsetp.lt.u32 q, n, 4194304;\nand.pred q, q, !p;\n@q bra WAIT_LOOP;\n}"
               ::"r"(bar), "r"(parity) : "memory");
}
__device__ __forceinline__ uint32_t mapa(uint32_t addr, uint32_t rank) {
  uint32_t r;
  asm volatile("mapa.shared::cluster.u32 %0, %1, %2;" : "=r"(r) : "r"(addr), "r"(rank));
  return r;
}
__device__ __forceinline__ void cluster_arrive() { asm volatile("barrier.cluster.arrive.relaxed.aligned;" ::: "memory"); }
__device__ __forceinline__ bool elect_one() {
  uint32_t p;
  asm volatile("{\n.reg .pred p;\nelect.sync _|p, 0xffffffff;\nselp.u32 %0, 1, 0, p;\n}" : "=r"(p));
  return p;
}
__device__ __forceinline__ int read_lane() { return threadIdx.x & 31; }
__device__ __forceinline__ void cluster_wait() { asm volatile("barrier.cluster.wait.acquire.aligned;" ::: "memory"); }
__device__ __forceinline__ void bar_sync(int id, int n) { asm volatile("barrier.cta.sync %0, %1;" ::"r"(id), "r"(n) : "memory"); }
__device__ __forceinline__ void bar_arrive(int id, int n) { asm volatile("barrier.cta.arrive %0, %1;" ::"r"(id), "r"(n) : "memory"); }

__device__ __forceinline__ uint64_t policy_evict_first() {
  uint64_t p;
  asm("createpolicy.fractional.L2::evict_first.b64 %0, 1.0;" : "=l"(p));
  return p;
}
__device__ __forceinline__ uint64_t policy_evict_normal() {
  uint64_t p;
  asm("createpolicy.fractional.L2::evict_normal.b64 %0, 1.0;" : "=l"(p));
  return p;
}
__device__ __forceinline__ void tma2d_mc(uint32_t dst, const CUtensorMap* tm, int c0, int c1, uint32_t bar, uint64_t pol) {
  asm volatile("cp.async.bulk.tensor.2d.shared::cluster.global.mbarrier::complete_tx::bytes.multicast::cluster.L2::cache_hint"
               " [%0], [%1, {%2, %3}], [%4], %5, %6;"
               ::"r"(dst), "l"(tm), "r"(c0), "r"(c1), "r"(bar), "h"((uint16_t)3), "l"(pol) : "memory");
}
__device__ __forceinline__ void tma3d(uint32_t dst, const CUtensorMap* tm, int c1, int c2, uint32_t bar) {
  asm volatile("cp.async.bulk.tensor.3d.shared::cluster.global.mbarrier::complete_tx::bytes [%0], [%1, {%2, %3, %4}], [%5];"
               ::"r"(dst), "l"(tm), "r"(0), "r"(c1), "r"(c2), "r"(bar) : "memory");
}
__device__ __forceinline__ void tma2d_stream(uint32_t dst, const CUtensorMap* tm, int c0, int c1, uint32_t bar) {
  asm volatile("{\n.reg .b64 pol;\ncreatepolicy.fractional.L2::evict_first.b64 pol, 1.0;\n"
               "cp.async.bulk.tensor.2d.shared::cluster.global.mbarrier::complete_tx::bytes.L2::cache_hint [%0], [%1, {%2, %3}], [%4], pol;\n}"
               ::"r"(dst), "l"(tm), "r"(c0), "r"(c1), "r"(bar) : "memory");
}
__device__ __forceinline__ void tma2d_prefetch(const CUtensorMap* tm, int c0, int c1) {
  asm volatile("cp.async.bulk.prefetch.tensor.2d.L2.global [%0, {%1, %2}];" ::"l"(tm), "r"(c0), "r"(c1) : "memory");
}
__device__ __forceinline__ void prefetch_l2(const void* p, uint32_t bytes) {
  asm volatile("cp.async.bulk.prefetch.L2.global [%0], %1;" ::"l"(p), "r"(bytes) : "memory");
}
__device__ __forceinline__ void prefetch_tmap(const CUtensorMap* tm) {
  asm volatile("prefetch.tensormap [%0];" ::"l"(tm) : "memory");
}

__device__ __forceinline__ void wg_fence() { asm volatile("wgmma.fence.sync.aligned;" ::: "memory"); }
__device__ __forceinline__ void wg_commit() { asm volatile("wgmma.commit_group.sync.aligned;" ::: "memory"); }
template <int N> __device__ __forceinline__ void wg_wait() { asm volatile("wgmma.wait_group.sync.aligned %0;" ::"n"(N) : "memory"); }

__device__ __forceinline__ uint64_t mkdesc(uint32_t addr, uint32_t lbo_bytes) {
  return (uint64_t)(((addr & 0x3FFFF) >> 4) | ((lbo_bytes >> 4) << 16)) | ((uint64_t)0x40000040u << 32);
}
template <int N> __device__ __forceinline__ void pin(float (&a)[N]) {
#pragma unroll
  for (int i = 0; i < N; i++) asm volatile("" : "+f"(a[i])::"memory");
}
template <int N> __device__ __forceinline__ void pin(uint32_t (&a)[N]) {
#pragma unroll
  for (int i = 0; i < N; i++) asm volatile("" : "+r"(a[i])::"memory");
}

#define F8(d, o) "+f"(d[o]), "+f"(d[o + 1]), "+f"(d[o + 2]), "+f"(d[o + 3]), "+f"(d[o + 4]), "+f"(d[o + 5]), "+f"(d[o + 6]), "+f"(d[o + 7])
#define R32A "%0, %1, %2, %3, %4, %5, %6, %7, %8, %9, %10, %11, %12, %13, %14, %15, %16, %17, %18, %19, %20, %21, %22, %23, %24, %25, %26, %27, %28, %29, %30, %31"
#define R32B "%32, %33, %34, %35, %36, %37, %38, %39, %40, %41, %42, %43, %44, %45, %46, %47, %48, %49, %50, %51, %52, %53, %54, %55, %56, %57, %58, %59, %60, %61, %62, %63"

template <int TB>
__device__ __forceinline__ void mma_n128(float (&d)[64], uint32_t a0, uint32_t a1, uint32_t a2, uint32_t a3, uint64_t db, int acc) {
  asm volatile("{\n.reg .pred p;\nsetp.ne.b32 p, %69, 0;\n"
               "wgmma.mma_async.sync.aligned.m64n128k16.f32.bf16.bf16 {" R32A ", " R32B "}, {%64, %65, %66, %67}, %68, p, 1, 1, %70;\n}\n"
               : F8(d, 0), F8(d, 8), F8(d, 16), F8(d, 24), F8(d, 32), F8(d, 40), F8(d, 48), F8(d, 56)
               : "r"(a0), "r"(a1), "r"(a2), "r"(a3), "l"(db), "r"(acc), "n"(TB));
}
__device__ __forceinline__ void mma_n64t(float (&d)[32], uint32_t a0, uint32_t a1, uint32_t a2, uint32_t a3, uint64_t db, int acc) {
  asm volatile("{\n.reg .pred p;\nsetp.ne.b32 p, %37, 0;\n"
               "wgmma.mma_async.sync.aligned.m64n64k16.f32.bf16.bf16 {" R32A "}, {%32, %33, %34, %35}, %36, p, 1, 1, 1;\n}\n"
               : F8(d, 0), F8(d, 8), F8(d, 16), F8(d, 24)
               : "r"(a0), "r"(a1), "r"(a2), "r"(a3), "l"(db), "r"(acc));
}
__device__ __forceinline__ void mma_n8(float (&d)[4], uint64_t da, uint64_t db, int acc) {
  asm volatile("{\n.reg .pred p;\nsetp.ne.b32 p, %6, 0;\n"
               "wgmma.mma_async.sync.aligned.m64n8k16.f32.bf16.bf16 {%0, %1, %2, %3}, %4, %5, p, 1, 1, 1, 0;\n}\n"
               : "+f"(d[0]), "+f"(d[1]), "+f"(d[2]), "+f"(d[3])
               : "l"(da), "l"(db), "r"(acc));
}
__device__ __forceinline__ void hmma_k8(float (&d)[4], uint32_t a0, uint32_t a1, uint32_t b0) {
  asm volatile("mma.sync.aligned.m16n8k8.row.col.f32.bf16.bf16.f32 {%0, %1, %2, %3}, {%4, %5}, {%6}, {%0, %1, %2, %3};"
               : "+f"(d[0]), "+f"(d[1]), "+f"(d[2]), "+f"(d[3]) : "r"(a0), "r"(a1), "r"(b0));
}
__device__ __forceinline__ void hmma_k16(float (&d)[4], uint32_t a0, uint32_t a1, uint32_t a2, uint32_t a3, uint32_t b0, uint32_t b1) {
  asm volatile("mma.sync.aligned.m16n8k16.row.col.f32.bf16.bf16.f32 {%0, %1, %2, %3}, {%4, %5, %6, %7}, {%8, %9}, {%0, %1, %2, %3};"
               : "+f"(d[0]), "+f"(d[1]), "+f"(d[2]), "+f"(d[3]) : "r"(a0), "r"(a1), "r"(a2), "r"(a3), "r"(b0), "r"(b1));
}

__device__ __forceinline__ uint32_t pack2(float lo, float hi) {
  uint32_t r;
  asm("cvt.rn.bf16x2.f32 %0, %1, %2;" : "=r"(r) : "f"(hi), "f"(lo));
  return r;
}
__device__ __forceinline__ float bf_lo(uint32_t w) { return __uint_as_float(w << 16); }
__device__ __forceinline__ float bf_hi(uint32_t w) { return __uint_as_float(w & 0xFFFF0000u); }
__device__ __forceinline__ float bfr(float x) { return __bfloat162float(__float2bfloat16_rn(x)); }
__device__ __forceinline__ uint32_t sub2(uint32_t a, uint32_t b) {
  uint32_t r;
  asm("sub.rn.bf16x2 %0, %1, %2;" : "=r"(r) : "r"(a), "r"(b));
  return r;
}
__device__ __forceinline__ uint32_t add2(uint32_t a, uint32_t b) {
  uint32_t r;
  asm("add.rn.bf16x2 %0, %1, %2;" : "=r"(r) : "r"(a), "r"(b));
  return r;
}
__device__ __forceinline__ float ex2(float x) {
  float r;
  asm("ex2.approx.ftz.f32 %0, %1;" : "=f"(r) : "f"(x));
  return r;
}
__device__ __forceinline__ float rcp(float x) {
  float r;
  asm("rcp.approx.ftz.f32 %0, %1;" : "=f"(r) : "f"(x));
  return r;
}
__device__ __forceinline__ float silu_f(float t) { return t * rcp(1.0f + ex2(-1.4426950408889634f * t)); }
__device__ __forceinline__ void sts128(uint32_t a, uint32_t x, uint32_t y, uint32_t z, uint32_t w) {
  asm volatile("st.shared.v4.u32 [%0], {%1, %2, %3, %4};" ::"r"(a), "r"(x), "r"(y), "r"(z), "r"(w) : "memory");
}
__device__ __forceinline__ void lds128(uint32_t a, uint32_t& x, uint32_t& y, uint32_t& z, uint32_t& w) {
  asm volatile("ld.shared.v4.u32 {%0, %1, %2, %3}, [%4];" : "=r"(x), "=r"(y), "=r"(z), "=r"(w) : "r"(a) : "memory");
}
__device__ __forceinline__ void ldsm4(uint32_t a, uint32_t& x, uint32_t& y, uint32_t& z, uint32_t& w) {
  asm volatile("ldmatrix.sync.aligned.m8n8.x4.shared.b16 {%0, %1, %2, %3}, [%4];" : "=r"(x), "=r"(y), "=r"(z), "=r"(w) : "r"(a) : "memory");
}
__device__ __forceinline__ void st_gran(uint4* p, uint32_t x, uint32_t y, uint32_t z, uint32_t w) {
  asm volatile("st.relaxed.gpu.global.v4.b32 [%0], {%1, %2, %3, %4};" ::"l"(p), "r"(x), "r"(y), "r"(z), "r"(w) : "memory");
}
__device__ __forceinline__ void ld_gran(const uint4* p, uint32_t& x, uint32_t& y, uint32_t& z, uint32_t& w) {
  asm volatile("ld.relaxed.gpu.global.v4.b32 {%0, %1, %2, %3}, [%4];" : "=r"(x), "=r"(y), "=r"(z), "=r"(w) : "l"(p) : "memory");
}
__device__ __forceinline__ void stsm4(uint32_t a, uint32_t x, uint32_t y, uint32_t z, uint32_t w) {
  asm volatile("stmatrix.sync.aligned.m8n8.x4.shared.b16 [%0], {%1, %2, %3, %4};" ::"r"(a), "r"(x), "r"(y), "r"(z), "r"(w) : "memory");
}
__device__ __forceinline__ void cp16(uint32_t dst, const void* src) {
  asm volatile("cp.async.cg.shared.global [%0], [%1], 16;" ::"r"(dst), "l"(src) : "memory");
}
__device__ __forceinline__ void cp_wait_all() { asm volatile("cp.async.wait_all;" ::: "memory"); }
__device__ __forceinline__ void add_granules(float (&red)[32], const uint32_t (&g)[16]) {
#pragma unroll
  for (int i = 0; i < 16; i++) { red[2 * i] += bf_lo((i & 3) ? g[i] : g[i] & ~1u); red[2 * i + 1] += bf_hi(g[i]); }
}
__device__ __forceinline__ bool granules_ok(const uint32_t (&g)[16], uint32_t tag) {
  return __all_sync(0xffffffffu, (((g[0] ^ tag) | (g[4] ^ tag) | (g[8] ^ tag) | (g[12] ^ tag)) & 1) == 0);
}
__device__ __forceinline__ unsigned ld_acquire(const unsigned* p) {
  unsigned v;
  asm volatile("ld.acquire.gpu.global.u32 %0, [%1];" : "=r"(v) : "l"(p) : "memory");
  return v;
}
__device__ __forceinline__ unsigned atom_add_acq_rel(unsigned* p) {
  unsigned v;
  asm volatile("atom.acq_rel.gpu.global.add.u32 %0, [%1], 1;" : "=r"(v) : "l"(p) : "memory");
  return v;
}
__device__ __forceinline__ void st_release(unsigned* p, unsigned v) {
  asm volatile("st.release.gpu.global.u32 [%0], %1;" ::"l"(p), "r"(v) : "memory");
}

struct LnAcc {
  float sm[2][4], sq[8][4];
  __device__ __forceinline__ void clear() {
#pragma unroll
    for (int i = 0; i < 4; i++) {
      sm[0][i] = sm[1][i] = 0.f;
#pragma unroll
      for (int j = 0; j < 8; j++) sq[j][i] = 0.f;
    }
  }
};
template <int K0, int K1>
__device__ __forceinline__ void ln_fetch(uint32_t (&xa)[144], uint32_t boxes, uint32_t lo) {
#pragma unroll
  for (int k = K0; k < K1; k++) ldsm4(boxes + (k >> 2) * 8192 + (lo ^ ((k & 3) << 5)), xa[4 * k], xa[4 * k + 1], xa[4 * k + 2], xa[4 * k + 3]);
}
__device__ __forceinline__ void ln_accum1(LnAcc& a, int h, uint32_t x0, uint32_t x1, uint32_t x2, uint32_t x3) {
  const uint32_t ONES = 0x3F803F80u;
  hmma_k16(a.sm[h], x0, x1, x2, x3, ONES, ONES);
  hmma_k8(a.sq[4 * h], x0, x1, x0);
  hmma_k8(a.sq[4 * h + 1], x0, x1, x1);
  hmma_k8(a.sq[4 * h + 2], x2, x3, x2);
  hmma_k8(a.sq[4 * h + 3], x2, x3, x3);
}
template <int K0, int K1>
__device__ __forceinline__ void ln_accum(const uint32_t (&xa)[144], LnAcc& a) {
#pragma unroll
  for (int k = K0; k < K1; k++) ln_accum1(a, k & 1, xa[4 * k], xa[4 * k + 1], xa[4 * k + 2], xa[4 * k + 3]);
}
template <int K0, int K1>
__device__ __forceinline__ void ln_sums(const uint32_t (&xa)[144], float (&sm)[4][4]) {
#pragma unroll
  for (int k = K0; k < K1; k++) hmma_k16(sm[k & 3], xa[4 * k], xa[4 * k + 1], xa[4 * k + 2], xa[4 * k + 3], 0x3F803F80u, 0x3F803F80u);
}
__device__ __forceinline__ uint32_t sq8(const uint32_t* a) {
  uint32_t t, u;
  asm("mul.rn.bf16x2 %0, %1, %1;" : "=r"(t) : "r"(a[0]));
  asm("mul.rn.bf16x2 %0, %1, %1;" : "=r"(u) : "r"(a[2]));
#pragma unroll
  for (int i = 4; i < 16; i += 4) {
    asm("fma.rn.bf16x2 %0, %1, %1, %0;" : "+r"(t) : "r"(a[i]));
    asm("fma.rn.bf16x2 %0, %1, %1, %0;" : "+r"(u) : "r"(a[i + 2]));
  }
  return add2(t, u);
}
__device__ __forceinline__ void ln_centre(uint32_t (&xa)[144], int j0, int j1, uint32_t mm0, uint32_t mm1, float& sq0, float& sq1) {
#pragma unroll
  for (int j = 0; j < 72; j += 8)
    if (j >= j0 && j < j1) {
#pragma unroll
      for (int k = j; k < j + 8; k++) {
        xa[2 * k] = sub2(xa[2 * k], mm0);
        xa[2 * k + 1] = sub2(xa[2 * k + 1], mm1);
      }
      const uint32_t t0 = sq8(xa + 2 * j), t1 = sq8(xa + 2 * j + 1);
      sq0 += bf_lo(t0) + bf_hi(t0);
      sq1 += bf_lo(t1) + bf_hi(t1);
    }
}
__device__ __forceinline__ float ln_rstd(float msq, float d) {
  float sd;
  asm("sqrt.approx.f32 %0, %1;" : "=f"(sd) : "f"(bfr(bfr(fmaxf(msq - d * d, 0.0f)) + 1e-5f)));
  return rcp(bfr(sd));
}
__device__ __forceinline__ void ln_row(float sum, float sq, float& mean_b, float& rstd) {
  const float mean = sum * (1.0f / DM);
  mean_b = bfr(mean);
  rstd = ln_rstd(sq * (1.0f / DM), mean);
}
__device__ __forceinline__ void ln_diag(const LnAcc& a, int lane, float& t0, float& t1) {
  const bool odd = (lane >> 2) & 1;
  t0 = odd ? (a.sq[0][1] + a.sq[2][1]) + (a.sq[4][1] + a.sq[6][1]) : (a.sq[0][0] + a.sq[2][0]) + (a.sq[4][0] + a.sq[6][0]);
  t1 = odd ? (a.sq[1][3] + a.sq[3][3]) + (a.sq[5][3] + a.sq[7][3]) : (a.sq[1][2] + a.sq[3][2]) + (a.sq[5][2] + a.sq[7][2]);
}
__device__ __forceinline__ void ln_stats(const LnAcc& a, int lane, float& mean0, float& rstd0, float& mean1, float& rstd1) {
  float t0, t1;
  ln_diag(a, lane, t0, t1);
  const int src = (lane & ~3) | (lane >> 3);
  t0 = __shfl_sync(0xffffffffu, t0, src);
  t1 = __shfl_sync(0xffffffffu, t1, src);
  ln_row(a.sm[0][0] + a.sm[1][0], t0, mean0, rstd0);
  ln_row(a.sm[0][2] + a.sm[1][2], t1, mean1, rstd1);
}

template <bool ROUTED>
__device__ __forceinline__ uint32_t gate2(uint32_t x2, float mean_b, float rstd, float2 upd = make_float2(0.f, 0.f)) {
  const uint32_t xc = sub2(x2, pack2(mean_b, mean_b));
  uint32_t t = pack2(bf_lo(xc) * rstd, bf_hi(xc) * rstd);
  if (ROUTED) t = pack2(bf_lo(t) + upd.x, bf_hi(t) + upd.y);
  return pack2(silu_f(bf_lo(t)), silu_f(bf_hi(t)));
}

template <int V> struct IC { static constexpr int value = V; };

struct Ctx {
  uint32_t sb;
  uint8_t* sp;
  uint32_t rank;
  Scratch* gs;
};

__device__ __forceinline__ void dly(int) {}
__device__ __forceinline__ void attn_producer(const Ctx& cx, int qb, int hs, const CUtensorMap* tmX, const CUtensorMap* tmK, const CUtensorMap* tmV,
                                              const CUtensorMap* tmWq, const CUtensorMap* tmWo) {
  const uint32_t full = cx.sb + SM_FULL, empty = cx.sb + SM_EMPTY, ring = cx.sb + SM_RING + cx.rank * 16384;
  const uint64_t keep = policy_evict_normal(), last_use = policy_evict_first();
  int st = 0;
#pragma unroll 1
  for (int p = 0; p < 4; p++) {
    const int n0 = (hs * 4 + ((p + 1) & 3)) * DH + cx.rank * 64;
#pragma unroll 1
    for (int i = 0; i < 5; i++, st++) {
      const uint32_t sl = st & 3;
      if (st == X_ORDER) {
#pragma unroll 1
        for (int j = 0; j < 3; j++) {
          mbar_expect_tx(cx.sb + SM_XFULL + 96 + 8 * j, 24576);
          tma3d(cx.sb + SM_X + 73728 + j * 24576, tmX, qb * 128 + 64, j * 3, cx.sb + SM_XFULL + 96 + 8 * j);
        }
      }
      mbar_wait(empty + 8 * sl, ((st >> 2) ^ (sl >> 1) ^ 1) & 1);
      dly(st);
      mbar_expect_tx(full + 8 * sl, i == 2 ? 16384 : 32768);
      const int k0 = i < 3 ? 128 * i : 128 * i - 64;
      tma2d_mc(ring + sl * STAGE, tmWq, n0, k0, full + 8 * sl, last_use);
      if (i != 2) tma2d_mc(ring + sl * STAGE + 8192, tmWq, n0, k0 + 64, full + 8 * sl, last_use);
      if (st == X_PFQ) {
#pragma unroll 1
        for (int b = 8 + qb; b < 72; b += 16) tma2d_prefetch(tmWq, (hs * 4 + ((b / 18 + 1) & 3)) * DH + (b & 1) * 64, ((b % 18) >> 1) * 64);
      }
    }
  }
#pragma unroll 1
  for (int u = 0; u < NST_KV; u++, st++) {
    const bool isK = (u == 0) || ((u & 1) && u != 127);
    const int it = u == 0 ? 0 : (u == 127 ? 63 : (isK ? (u + 1) >> 1 : (u >> 1) - 1));
    const int row = (hs * 2 + (it >> 5)) * SEQ + (it & 15) * 128;
    const uint32_t sl = st & 3;
    mbar_wait(empty + 8 * sl, ((st >> 2) ^ (sl >> 1) ^ 1) & 1);
    dly(st);
    mbar_expect_tx(full + 8 * sl, 32768);
    tma2d_mc(ring + sl * STAGE, isK ? tmK : tmV, cx.rank * 64, row, full + 8 * sl, (it & 16) ? last_use : keep);
  }
#pragma unroll 1
  for (int u = 0; u < NST_O; u++, st++) {
    const int s = u >> 1;
    const int blk = s == 0 ? 8 : ((hs + s) & 7);
    const uint32_t sl = st & 3;
    mbar_wait(empty + 8 * sl, ((st >> 2) ^ (sl >> 1) ^ 1) & 1);
    dly(st);
    mbar_expect_tx(full + 8 * sl, 32768);
    tma2d_mc(ring + sl * STAGE, tmWo, blk * 64, hs * 512 + (((u & 1) * 2 + cx.rank + 3) & 3) * 128, full + 8 * sl, last_use);
  }
}

__device__ __forceinline__ void attn_gate(const Ctx& cx, int qb, int hs, int t, const __nv_bfloat16* x) {
  uint4 nx = *(const uint4*)(x + (size_t)(qb * 128 + (t >> 3)) * DM + hs * 64 + (t & 7) * 8);
  bar_sync(BAR_GATE, 352);
#pragma unroll 1
  for (int ch = t; ch < 1152; ch += 96) {
    const uint4 v = nx;
    const int n = ch + 96;
    if (n < 1152) nx = *(const uint4*)(x + (size_t)(qb * 128 + (n < 1024 ? n >> 3 : hs * 16 + ((n - 1024) >> 3))) * DM + (n < 1024 ? hs * 64 : 512) + (t & 7) * 8);
    const int lr = ch < 1024 ? ch >> 3 : hs * 16 + ((ch - 1024) >> 3);
    const float2 st = *(const float2*)(cx.sp + SM_STATS + 8 * lr);
    cx.gs->gate[((qb * 128 + lr) * DM + (ch < 1024 ? hs * 64 : 512) + (t & 7) * 8) >> 3] =
        make_uint4(gate2<false>(v.x, st.x, st.y), gate2<false>(v.y, st.x, st.y), gate2<false>(v.z, st.x, st.y), gate2<false>(v.w, st.x, st.y));
  }
}

constexpr uint32_t SM_XO = SM_SLOT, SM_GO = SM_SLOT + 128 * 144;
constexpr uint32_t SM_X8 = SM_SLOT + 2 * STAGE + 20480, SM_G8 = SM_X8 + 16 * 144;
__device__ __forceinline__ void attn_stage_xg(const Ctx& cx, int qb, int hs, int t, const __nv_bfloat16* x) {
  bar_sync(BAR_OA, 352);
#pragma unroll 1
  for (int ch = t; ch < 1024; ch += 64) {
    const size_t o = (size_t)(qb * 128 + (ch >> 3)) * DM + hs * 64 + (ch & 7) * 8;
    cp16(cx.sb + SM_XO + (ch >> 3) * 144 + (ch & 7) * 16, x + o);
    cp16(cx.sb + SM_GO + (ch >> 3) * 144 + (ch & 7) * 16, (const __nv_bfloat16*)cx.gs->gate + o);
  }
  cp_wait_all();
  mbar_arrive(cx.sb + SM_BAR_XG);
}

__device__ __forceinline__ void attn_helper(const Ctx& cx, int qb, int hs, int lane, const __nv_bfloat16* x, const __nv_bfloat16* wo) {
  unsigned e = 0;
  if (lane == 0) {
    e = cx.gs->launch[blockIdx.x];
    cx.gs->launch[blockIdx.x] = e + 1;
  }
  e = __shfl_sync(0xffffffffu, e, 0);
  bar_sync(BAR_HELPER, 128);
  prefetch_l2(wo + (size_t)(hs * 512 + qb * 32 + lane) * DM, DM * 2);
#pragma unroll 1
  for (int n = 0; n < (1 << 16) && ld_acquire(&cx.gs->ffn_flag) != e + 1; n++) __nanosleep(1000);
  const uint32_t tag = ~e & 1;
  {
#pragma unroll 1
    for (int i = 0; i < 2 * TOPC; i++) {
      const int lr = __ldcg(&cx.gs->idx[i >> 1]) - qb * 128, col = ((i & 1) ? 512 : hs * 64) + 2 * lane;
      if ((i & 1) ? (lr >> 4) == hs : (lr >> 7) == 0) {
        const float2 st = *(const float2*)(cx.sp + SM_STATS + 8 * lr);
        const int o = (qb * 128 + lr) * DM + col;
        *(uint32_t*)((__nv_bfloat16*)cx.gs->gate + o) =
            gate2<true>(*(const uint32_t*)(x + o), st.x, st.y, __ldcg((const float2*)(cx.gs->upd + (i >> 1) * DM + col)));
      }
    }
  }
  if (lane == 0) *(uint32_t*)(cx.sp + SM_TAG) = tag;
  __syncwarp();
  if (lane == 0) mbar_arrive(cx.sb + SM_BAR_MISC);

  const uint4* src = cx.gs->part + (size_t)((qb * 64 + 56) * 2 + (hs >> 2)) * 4 * 128 + (hs & 3) * 32 + lane;
  const uint32_t stg = cx.sb + SM_SLOT + 2 * STAGE + lane * 16;
  bar_sync(BAR_OA, 352);

#pragma unroll 1
  for (int i = 0; i < 4; i++) {
    const int ch = i * 32 + lane;
    const size_t o = (size_t)(qb * 128 + hs * 16 + (ch >> 3)) * DM + 512 + (ch & 7) * 8;
    cp16(cx.sb + SM_X8 + (ch >> 3) * 144 + (ch & 7) * 16, x + o);
    cp16(cx.sb + SM_G8 + (ch >> 3) * 144 + (ch & 7) * 16, (const __nv_bfloat16*)cx.gs->gate + o);
  }
#pragma unroll 1
  for (int n = 0; n < (1 << 16); n++) {
    __nanosleep(n ? 500 : 2000);
    uint32_t a, b, d, t;
    ld_gran(src - lane + (lane & 7) * (2 * 4 * 128) + 3 * 128 + 31, a, b, d, t);
    if (__all_sync(0xffffffffu, (a & 1) == tag)) break;
  }
#pragma unroll 1
  for (int n = 0; n < (1 << 16); n++) {
#pragma unroll 1
    for (int i = 0; i < 8; i++) {
#pragma unroll
      for (int g = 0; g < 4; g++) cp16(stg + (i * 4 + g) * 512, src + i * (2 * 4 * 128) + g * 128);
    }
    cp_wait_all();
    uint32_t bad = 0;
#pragma unroll 4
    for (int i = 0; i < 32; i++) bad |= *(const volatile uint32_t*)(cx.sp + SM_SLOT + 2 * STAGE + lane * 16 + i * 512) ^ tag;
    if (__all_sync(0xffffffffu, (bad & 1) == 0)) break;
  }

}
__device__ __forceinline__ void attn_finish8(const Ctx& cx, int qb, int hs, int hw, int lane, __nv_bfloat16* out) {
  bar_sync(BAR_GATE, 96);
#pragma unroll 1
  for (int g = hw; g < 4; g += 3) {
    float acc[8] = {0.f, 0.f, 0.f, 0.f, 0.f, 0.f, 0.f, 0.f};
#pragma unroll 2
    for (int sidx = 0; sidx < 8; sidx++) {
      uint32_t a, b, d, t;
      lds128(cx.sb + SM_SLOT + 2 * STAGE + lane * 16 + (sidx * 4 + g) * 512, a, b, d, t);
      acc[0] += bf_lo(a & ~1u); acc[1] += bf_hi(a); acc[2] += bf_lo(b); acc[3] += bf_hi(b);
      acc[4] += bf_lo(d); acc[5] += bf_hi(d); acc[6] += bf_lo(t); acc[7] += bf_hi(t);
    }
#pragma unroll
    for (int j = 0; j < 4; j++) {
      const int o = ((lane >> 2) + (j & 1) * 8) * 144 + (2 * g + (j >> 1)) * 16 + (lane & 3) * 4;
      uint32_t* xp = (uint32_t*)(cx.sp + SM_X8 + o);
      const uint32_t xw = *xp, gw = *(const uint32_t*)(cx.sp + SM_G8 + o);
      *xp = pack2(fmaf(acc[2 * j], bf_lo(gw), bf_lo(xw)), fmaf(acc[2 * j + 1], bf_hi(gw), bf_hi(xw)));
    }
  }
  bar_sync(BAR_GATE, 96);
  for (int ch = hw * 32 + lane; ch < 128; ch += 96)
    *(uint4*)(out + (size_t)(qb * 128 + hs * 16 + (ch >> 3)) * DM + 512 + (ch & 7) * 8) =
        *(const uint4*)(cx.sp + SM_X8 + (ch >> 3) * 144 + (ch & 7) * 16);
}

constexpr float SUM_HI = 1.8446744e19f, SUM_LO = 9.0949470e-13f;

__device__ __forceinline__ void softmax_shift(float (&s)[64], float n0, float n1) {
#pragma unroll
  for (int i = 0; i < 64; i++) s[i] += (i & 2) ? n1 : n0;
}
template <int LO, int HI>
__device__ __forceinline__ void softmax_exp(float (&s)[64]) {
#pragma unroll
  for (int i = LO; i < HI; i++) s[i] = ex2(s[i]);
}
__device__ __forceinline__ void row_sums(const uint32_t (&pf)[32], float& l0, float& l1) {
  uint32_t t[16];
#pragma unroll
  for (int i = 0; i < 16; i++) t[i] = add2(pf[(i >> 1) * 4 + (i & 1)], pf[(i >> 1) * 4 + 2 + (i & 1)]);
#pragma unroll
  for (int i = 0; i < 8; i++) t[i] = add2(t[(i >> 1) * 4 + (i & 1)], t[(i >> 1) * 4 + 2 + (i & 1)]);
#pragma unroll
  for (int i = 0; i < 4; i++) t[i] = add2(t[(i >> 1) * 4 + (i & 1)], t[(i >> 1) * 4 + 2 + (i & 1)]);
  l0 += (bf_lo(t[0]) + bf_lo(t[2])) + (bf_hi(t[0]) + bf_hi(t[2]));
  l1 += (bf_lo(t[1]) + bf_lo(t[3])) + (bf_hi(t[1]) + bf_hi(t[3]));
}
__device__ __forceinline__ void row_max(const float (&s)[64], float& x0, float& x1) {
  x0 = s[0];
  x1 = s[2];
#pragma unroll
  for (int i = 0; i < 64; i += 4) { x0 = fmaxf(x0, fmaxf(s[i], s[i + 1])); x1 = fmaxf(x1, fmaxf(s[i + 2], s[i + 3])); }
  x0 = fmaxf(x0, __shfl_xor_sync(0xffffffffu, x0, 1));
  x1 = fmaxf(x1, __shfl_xor_sync(0xffffffffu, x1, 1));
  x0 = fmaxf(x0, __shfl_xor_sync(0xffffffffu, x0, 2));
  x1 = fmaxf(x1, __shfl_xor_sync(0xffffffffu, x1, 2));
}
__device__ __forceinline__ void softmax_rebase(float (&s)[64], float& n0, float& n1, float& sc0, float& sc1) {
  float x0, x1;
  row_max(s, x0, x1);
  x0 = fmaxf(x0, 1.f);
  x1 = fmaxf(x1, 1.f);
  n0 -= __log2f(x0);
  n1 -= __log2f(x1);
  sc0 = exp2f(-__log2f(x0));
  sc1 = exp2f(-__log2f(x1));
#pragma unroll
  for (int i = 0; i < 64; i++) s[i] *= (i & 2) ? sc1 : sc0;
}
__device__ __forceinline__ void softmax_redo(float (&s)[64], const uint32_t (&q)[32], const __nv_bfloat16* kblk, int lane, float& n0,
                                             float& n1, float& sc0, float& sc1) {
  const __nv_bfloat16* kp = kblk + (lane >> 2) * DH + (lane & 3) * 2;
#pragma unroll
  for (int nb = 0; nb < 16; nb++) {
    float d[4] = {0.f, 0.f, 0.f, 0.f};
#pragma unroll
    for (int k = 0; k < 8; k++)
      hmma_k16(d, q[4 * k], q[4 * k + 1], q[4 * k + 2], q[4 * k + 3], *(const uint32_t*)(kp + nb * 8 * DH + k * 16),
               *(const uint32_t*)(kp + nb * 8 * DH + k * 16 + 8));
    s[4 * nb] = d[0]; s[4 * nb + 1] = d[1]; s[4 * nb + 2] = d[2]; s[4 * nb + 3] = d[3];
    block_fence(100 + nb);
  }
  float x0, x1;
  row_max(s, x0, x1);
  const float m0 = fminf(n0, -x0), m1 = fminf(n1, -x1);
  sc0 = ex2(m0 - n0);
  sc1 = ex2(m1 - n1);
  n0 = m0; n1 = m1;
  softmax_shift(s, n0, n1);
  softmax_exp<0, 64>(s);
}

__device__ __forceinline__ void attn_consumer(const Ctx& cx, int qb, int hs, int wg, int cw, int lane, const __nv_bfloat16* x,
                                              const __nv_bfloat16* kc, __nv_bfloat16* out) {
  const int r = lane >> 2, c = lane & 3, tw = (cw & 3) * 32 + lane;
  const int lr0 = cw * 16 + r;
  const uint32_t full = cx.sb + SM_FULL;
  const uint32_t ring = cx.sb + SM_RING;
  const uint32_t slot = cx.sb + SM_SLOT + wg * 16384 + tw * 16;
  const bool signaller = lane == 0 && (cw & 3) < 2;
  const int my_turn = 1 + wg, other_turn = 2 - wg;

  uint32_t q[32];
  uint32_t empty_c;
  {
    uint32_t xa[144];
    float rstd0, rstd1, sq0 = 0.f, sq1 = 0.f;
    {
      const uint32_t xb = cx.sb + SM_X + wg * 73728, xf = cx.sb + SM_XFULL + wg * 96;
      const uint32_t lo = ((cw & 3) * 16 + (lane & 15)) * 128 + (((lane >> 4) ^ (lane & 7)) << 4);
      float sm[4][4] = {};
      prof(wg, 0);
      empty_c = mapa(cx.sb + SM_EMPTY, cw & 1);
      mbar_wait(xf, 0);
      if ((threadIdx.x & 127) == 0) profc(wg, 30);
      ln_fetch<0, 12>(xa, xb, lo);
      mbar_wait(xf + 8, 0);
      ln_fetch<12, 24>(xa, xb, lo);
      ln_sums<0, 12>(xa, sm);
      mbar_wait(xf + 16, 0);
      if ((threadIdx.x & 127) == 0) profc(wg, 1);
      ln_fetch<24, 36>(xa, xb, lo);
      ln_sums<12, 36>(xa, sm);
      rstd0 = ((sm[0][0] + sm[1][0]) + (sm[2][0] + sm[3][0])) * (1.0f / DM);
      rstd1 = ((sm[0][2] + sm[1][2]) + (sm[2][2] + sm[3][2])) * (1.0f / DM);
    }
    asm volatile("" : "+f"(rstd0), "+f"(rstd1)::"memory");
    if (wg) {
      bar_arrive(other_turn, 256);
    } else {
      bar_sync(4, 128);
      if (signaller) {
        asm volatile("mbarrier.arrive.shared::cluster.b64 _, [%0], 2;" ::"r"(empty_c + 16) : "memory");
        asm volatile("mbarrier.arrive.shared::cluster.b64 _, [%0], 2;" ::"r"(empty_c + 24) : "memory");
      }
    }
    const uint32_t mm0 = pack2(rstd0, rstd0), mm1 = pack2(rstd1, rstd1);
    ln_centre(xa, 0, X_C0, mm0, mm1, sq0, sq1);
    pin(xa);
    if ((threadIdx.x & 127) == 0) profc(wg, 2);

    float acc[64];
#pragma unroll 1
    for (int p = 0; p < 4; p++) {
      const int st0 = p * 5;
#pragma unroll
      for (int i = 0; i < 5; i++) {
        const int st = st0 + i;
        const uint32_t sl = st & 3;
        mbar_wait(full + 8 * sl, (st >> 2) & 1);
        if (st == 0 && (threadIdx.x & 127) == 0) profc(wg, 31);
        if (i != (wg ? 4 : 1)) bar_sync(my_turn, 256);
        wg_fence();
        const uint64_t db = mkdesc(ring + sl * STAGE, 16384);
        const int kb0 = i < 3 ? 8 * i : 8 * i - 4;
#pragma unroll
        for (int k = 0; k < (i == 2 ? 4 : 8); k++) {
          const int kb = kb0 + k;
          mma_n128<1>(acc, xa[4 * kb], xa[4 * kb + 1], xa[4 * kb + 2], xa[4 * kb + 3], db + k * 128, kb > 0);
        }
        wg_commit();
        if (i != (wg ? 3 : 0)) bar_arrive(other_turn, 256);
        if (p == 0 && (i == 1 || i == 2)) {
          ln_centre(xa, i == 1 ? X_C0 : X_C1, i == 1 ? X_C1 : 72, mm0, mm1, sq0, sq1);
          if (i == 2) {
            sq0 += __shfl_xor_sync(0xffffffffu, sq0, 1); sq1 += __shfl_xor_sync(0xffffffffu, sq1, 1);
            sq0 += __shfl_xor_sync(0xffffffffu, sq0, 2); sq1 += __shfl_xor_sync(0xffffffffu, sq1, 2);
            rstd0 = ln_rstd(sq0 * (1.0f / DM), rstd0 - bf_lo(mm0));
            rstd1 = ln_rstd(sq1 * (1.0f / DM), rstd1 - bf_lo(mm1));
            if (c == 0) {
              *(float2*)(cx.sp + SM_STATS + 8 * lr0) = make_float2(bf_lo(mm0), rstd0);
              *(float2*)(cx.sp + SM_STATS + 8 * (lr0 + 8)) = make_float2(bf_lo(mm1), rstd1);
            }
            bar_arrive(BAR_GATE, 352);
            bar_sync(4 + wg, 128);
            rstd0 *= SM_SCALE_LOG2;
            rstd1 *= SM_SCALE_LOG2;
          }
          pin(xa);
        }
        if (i == 0) {
          if (wg) {
            wg_wait<0>();
            if (signaller) mbar_arrive_cluster(empty_c + 8 * sl);
          }
        } else if (i != 3) {
          if (i != 2) {
            wg_wait<1>();
            if (signaller && (i == 4 || !wg)) mbar_arrive_cluster(empty_c + 8 * ((st - 1) & 3));
          }
          wg_wait<0>();
          if (signaller) mbar_arrive_cluster(empty_c + 8 * sl);
        }
      }
      pin(acc);
      prof(wg, 3 + p);
      if (p < 3) {
#pragma unroll
        for (int i = 0; i < 8; i++)
          sts128(slot + p * STAGE + i * 2048, pack2(acc[8 * i] * rstd0, acc[8 * i + 1] * rstd0), pack2(acc[8 * i + 2] * rstd1, acc[8 * i + 3] * rstd1),
                 pack2(acc[8 * i + 4] * rstd0, acc[8 * i + 5] * rstd0), pack2(acc[8 * i + 6] * rstd1, acc[8 * i + 7] * rstd1));
      }
    }
#pragma unroll
    for (int i = 0; i < 16; i++) {
      q[2 * i] = pack2(acc[4 * i] * rstd0, acc[4 * i + 1] * rstd0);
      q[2 * i + 1] = pack2(acc[4 * i + 2] * rstd1, acc[4 * i + 3] * rstd1);
    }
  }

  uint32_t pf[32], oa[96];
  {
    float s[64], o[64];
    float n0, n1, l0 = 0.f, l1 = 0.f;
#pragma unroll
    for (int i = 0; i < 64; i++) o[i] = 0.f;
    float lp0, lp1;
    float i0 = 0.f, i1 = 0.f;
    bool redo, shift;
    auto turn = [&](int it, auto kc_) -> bool {
      constexpr int KIND = decltype(kc_)::value;
      constexpr uint32_t slk = KIND == 0 ? 0 : (KIND == 1 ? 1 : 3), slv = KIND == 1 ? 2 : 0, slkn = KIND == 1 ? 3 : 1;
      constexpr int SPLIT = 44, PARK1 = 5;
      const uint32_t par = ((it + 10) >> 1) & 1;
      if (KIND == 3) {
#pragma unroll
        for (int i = 0; i < 8; i++) lds128(slot + ((it >> 4) - 1) * STAGE + i * 2048, q[4 * i], q[4 * i + 1], q[4 * i + 2], q[4 * i + 3]);
      }
      const uint64_t dk = mkdesc(ring + slk * STAGE, 16), dv = mkdesc(ring + slv * STAGE, 16384);
      auto qk = [&]() {
#pragma unroll
        for (int k = 0; k < 8; k++)
          mma_n128<0>(s, q[4 * k], q[4 * k + 1], q[4 * k + 2], q[4 * k + 3], dk + (k >> 2) * 1024 + (k & 3) * 2, k > 0);
        wg_commit();
      };
      auto pv = [&]() {
#pragma unroll
        for (int k = 0; k < 8; k++)
          mma_n128<1>(o, pf[4 * k], pf[4 * k + 1], pf[4 * k + 2], pf[4 * k + 3], dv + k * 128, k > 0 || KIND != 1 || (it & 15) != 1);
        wg_commit();
      };
      lp0 = l0; lp1 = l1;
      {
        bar_sync(my_turn, 256);
        pin(q); pin(pf); pin(o);
        wg_fence();
        qk();
        if (KIND == 1 && (it & 15) == 1 && it > 1) {
#pragma unroll
          for (int i = PARK1; i < 8; i++)
            sts128(slot + ((it >> 4) - 1) * STAGE + i * 2048, pack2(o[8 * i] * i0, o[8 * i + 1] * i0), pack2(o[8 * i + 2] * i1, o[8 * i + 3] * i1),
                   pack2(o[8 * i + 4] * i0, o[8 * i + 5] * i0), pack2(o[8 * i + 6] * i1, o[8 * i + 7] * i1));
          wg_fence();
        }
        if (KIND) {
          mbar_wait(full + 8 * slv, par);
          pv();
        }
        bar_arrive(other_turn, 256);
        if (KIND == 3) {
          const float t0 = lp0 + __shfl_xor_sync(0xffffffffu, lp0, 1), t1 = lp1 + __shfl_xor_sync(0xffffffffu, lp1, 1);
          i0 = rcp(t0 + __shfl_xor_sync(0xffffffffu, t0, 2));
          i1 = rcp(t1 + __shfl_xor_sync(0xffffffffu, t1, 2));
        }
        if (KIND) wg_wait<1>(); else wg_wait<0>();
      }
      pin(s);
      mbar_arrive_cluster_now<10 * KIND + 3>(empty_c + 8 * slk, signaller);
      if (KIND == 0 || KIND == 3) {
        shift = false;
        n0 = n1 = l0 = l1 = 0.f;
      } else if (shift) {
        softmax_shift(s, n0, n1);
        pin(s);
      }
      softmax_exp<0, SPLIT>(s);
      if (KIND) {
        pin(s);
        block_fence(10 * KIND + 4);
        wg_wait<0>();
        pin(o); pin(pf);
        mbar_arrive_cluster_now<10 * KIND + 5>(empty_c + 8 * slv, signaller);
      }
      const bool kready = mbar_test(full + 8 * slkn, par);
      softmax_exp<SPLIT, 64>(s);
#pragma unroll
      for (int i = 0; i < 32; i++) pf[i] = pack2(s[2 * i], s[2 * i + 1]);
      row_sums(pf, l0, l1);
      if (KIND == 3) {
#pragma unroll
        for (int i = 0; i < PARK1; i++)
          sts128(slot + ((it >> 4) - 1) * STAGE + i * 2048, pack2(o[8 * i] * i0, o[8 * i + 1] * i0), pack2(o[8 * i + 2] * i1, o[8 * i + 3] * i1),
                 pack2(o[8 * i + 4] * i0, o[8 * i + 5] * i0), pack2(o[8 * i + 6] * i1, o[8 * i + 7] * i1));
        prof(wg, 6 + (it >> 4));
        if (it == 48 && cw == 0) bar_arrive(BAR_HELPER, 128);
      }
      redo = !(l0 + l1 <= SUM_HI) || ((KIND == 0 || KIND == 3) && fminf(l0, l1) < SUM_LO);
      const bool leave = __any_sync(0xffffffffu, redo || !kready);
      return leave;
    };
    int it = 0;
    mbar_wait(full, (NST_Q >> 2) & 1);
    bool slow = turn(0, IC<0>());
#pragma unroll 1
    while (true) {
      if (!slow) {
        it++;
#pragma unroll 1
        while (true) {
          if (it & 1) {
            if (turn(it, IC<1>()) || it == 63) break;
            it++;
          }
          if (it & 15) {
            if (turn(it, IC<2>())) break;
          } else {
            if (turn(it, IC<3>())) break;
          }
          it++;
        }
      }
      if (__any_sync(0xffffffffu, redo)) {
        const int j = it & 15;
        float sc0, sc1;
        if (__all_sync(0xffffffffu, l0 + l1 < 3.0e38f && (j || fminf(l0, l1) >= SUM_LO))) {
          softmax_rebase(s, n0, n1, sc0, sc1);
        } else {
          if (j == 0) n0 = n1 = 3.0e38f;
          softmax_redo(s, q, kc + (size_t)((hs * 2 + (it >> 5)) * SEQ + j * 128) * DH, lane, n0, n1, sc0, sc1);
        }
        l0 = j ? lp0 * sc0 : 0.f;
        l1 = j ? lp1 * sc1 : 0.f;
        shift = true;
        if (j == 0) sc0 = sc1 = 1.f;
#pragma unroll
        for (int i = 0; i < 16; i++) { o[4 * i] *= sc0; o[4 * i + 1] *= sc0; o[4 * i + 2] *= sc1; o[4 * i + 3] *= sc1; }
#pragma unroll
        for (int i = 0; i < 32; i++) pf[i] = pack2(s[2 * i], s[2 * i + 1]);
        row_sums(pf, l0, l1);
      }
      if (it == 63) break;
      mbar_wait(full + 8 * ((it & 1) ? 3 : 1), ((it + 10) >> 1) & 1);
      slow = false;
    }
    {
      const int st = NST_Q + NST_KV - 1;
      const uint32_t sl = st & 3;
      mbar_wait(full + 8 * sl, (st >> 2) & 1);
      bar_sync(my_turn, 256);
      pin(pf); pin(o);
      wg_fence();
      const uint64_t dv = mkdesc(ring + sl * STAGE, 16384);
#pragma unroll
      for (int k = 0; k < 8; k++) mma_n128<1>(o, pf[4 * k], pf[4 * k + 1], pf[4 * k + 2], pf[4 * k + 3], dv + k * 128, 1);
      wg_commit();
      bar_arrive(other_turn, 256);
      l0 += __shfl_xor_sync(0xffffffffu, l0, 1); l1 += __shfl_xor_sync(0xffffffffu, l1, 1);
      l0 += __shfl_xor_sync(0xffffffffu, l0, 2); l1 += __shfl_xor_sync(0xffffffffu, l1, 2);
      float f0 = fmaxf(rcp(l0), 0.f), f1 = fmaxf(rcp(l1), 0.f);
      asm volatile("" : "+f"(f0), "+f"(f1)::"memory");
      block_fence(61);
#pragma unroll
      for (int i = 0; i < 16; i++) lds128(slot + (i >> 3) * STAGE + (i & 7) * 2048, oa[4 * i], oa[4 * i + 1], oa[4 * i + 2], oa[4 * i + 3]);
      mbar_wait(cx.sb + SM_BAR_MISC, 0);
      mbar_wait(full + 8 * ((st + 1) & 3), ((st + 1) >> 2) & 1);
      wg_wait<0>();
      pin(o); pin(pf);
      if (signaller) mbar_arrive_cluster(empty_c + 8 * sl);
#pragma unroll
      for (int i = 0; i < 16; i++) {
        pf[2 * i] = pack2(o[4 * i] * f0, o[4 * i + 1] * f0);
        pf[2 * i + 1] = pack2(o[4 * i + 2] * f1, o[4 * i + 3] * f1);
      }
    }
  }

  prof(wg, 10);
  {
    float acc[32], red[32];
#pragma unroll
    for (int i = 0; i < 32; i++) red[i] = 0.f;
    const uint32_t tag = *(const uint32_t*)(cx.sp + SM_TAG);
    uint4* const xch = cx.gs->part + (size_t)(qb * 64 * 2 + wg) * 4 * 128 + tw;
    int nrx = 1;
    auto half_step = [&](int s, auto hc, bool arrive) {
      constexpr int h = decltype(hc)::value;
      const int st = NST_Q + NST_KV + 2 * s + h;
      const uint64_t db = mkdesc(ring + (st & 3) * STAGE, 16);
      bar_sync(my_turn, 256);
      if (h == 0) {
        pin(pf);
#pragma unroll
        for (int i = 0; i < 32; i++) asm volatile("" : "+r"(oa[i])::"memory");
      } else {
        pin(oa);
      }
      wg_fence();
#pragma unroll
      for (int k = 0; k < 16; k++) {
        const int kb = h * 16 + k - 8;
        if (kb >= 0) mma_n64t(acc, oa[4 * kb], oa[4 * kb + 1], oa[4 * kb + 2], oa[4 * kb + 3], db + k * 128, 1);
        else mma_n64t(acc, pf[4 * k], pf[4 * k + 1], pf[4 * k + 2], pf[4 * k + 3], db + k * 128, k > 0);
      }
      wg_commit();
      if (arrive) bar_arrive(other_turn, 256);
    };
    auto await = [&](int st) { mbar_wait(full + 8 * (st & 3), (st >> 2) & 1); };
    auto fetch = [&](uint32_t (&g)[16], int n) {
      const uint4* p = xch + (hs * 7 + n - 1) * (2 * 4 * 128);
#pragma unroll
      for (int i = 0; i < 4; i++) ld_gran(p + i * 128, g[4 * i], g[4 * i + 1], g[4 * i + 2], g[4 * i + 3]);
    };
    uint32_t g[16];
    bool pend = false;
#pragma unroll 1
    for (int s = 0; s < 8; s++) {
      const int st = NST_Q + NST_KV + 2 * s;
      half_step(s, IC<0>(), true);
      if (s == 0) {
#pragma unroll
        for (int i = 16; i < 24; i++) lds128(slot + 2 * STAGE + (i & 7) * 2048, oa[4 * i], oa[4 * i + 1], oa[4 * i + 2], oa[4 * i + 3]);
      }
      await(st + 1);
      if (pend && granules_ok(g, tag)) { add_granules(red, g); nrx++; }
      wg_wait<0>();
      if (signaller && s < 7) mbar_arrive_cluster(empty_c + 8 * (st & 3));
      pend = nrx < s - 1;
      if (pend) fetch(g, nrx);
      half_step(s, IC<1>(), true);
      if (s == 0) bar_arrive(BAR_OA, 352);
      await(st + 2);
      wg_wait<0>();
      if (signaller && s < 7) mbar_arrive_cluster(empty_c + 8 * (st & 3) + 8);
      pin(acc);
      prof(wg, 12 + s);
      uint4* p = xch + (s == 0 ? 56 + hs : ((hs + s) & 7) * 7 + s - 1) * (2 * 4 * 128);
#pragma unroll
      for (int i = 0; i < 4; i++)
        st_gran(p + i * 128, (pack2(acc[8 * i], acc[8 * i + 1]) & ~1u) | tag, pack2(acc[8 * i + 2], acc[8 * i + 3]),
                pack2(acc[8 * i + 4], acc[8 * i + 5]), pack2(acc[8 * i + 6], acc[8 * i + 7]));
    }
    float gf[32], xf[32];
    {
      const int s = 8;
      uint32_t g2[16], xv[16], gt[16];
      half_step(s, IC<0>(), true);
      if (pend && granules_ok(g, tag)) { add_granules(red, g); nrx++; }
      await(NST_Q + NST_KV + NST_O - 1);
      mbar_wait(cx.sb + SM_BAR_XG, 0);
      wg_wait<0>();
      fetch(g, nrx);
#pragma unroll
      for (int i = 0; i < 16; i++) {
        const uint8_t* p = cx.sp + (lr0 + (i & 1) * 8) * 144 + (i >> 1) * 16 + c * 4;
        xv[i] = *(const uint32_t*)(p + SM_XO);
        gt[i] = *(const uint32_t*)(p + SM_GO);
      }
      half_step(s, IC<1>(), wg == 0);
      fetch(g2, 7);
      int last = 8;
      const bool two = nrx < 7;
      if (granules_ok(g, tag)) { add_granules(red, g); nrx++; }
#pragma unroll
      for (int i = 0; i < 16; i++) {
        gf[2 * i] = bf_lo(gt[i]); gf[2 * i + 1] = bf_hi(gt[i]);
        xf[2 * i] = bf_lo(xv[i]); xf[2 * i + 1] = bf_hi(xv[i]);
      }
      wg_wait<0>();
      pin(acc);
#pragma unroll
      for (int i = 0; i < 32; i++) red[i] += acc[i];
      pin(red); pin(gf); pin(xf);
      block_fence(60);
      if (two && granules_ok(g2, tag)) { add_granules(red, g2); last = 7; }
#pragma unroll 1
      for (int spins = 0; nrx < last && spins < (1 << 16); spins++) {
        fetch(g, nrx);
        if (granules_ok(g, tag)) { add_granules(red, g); nrx++; }
      }
    }
    prof(wg, 20);
    const uint32_t ot = ring + 2 * STAGE + cw * (16 * 144);
    uint32_t ow[16];
#pragma unroll
    for (int i = 0; i < 16; i++) ow[i] = pack2(fmaf(red[2 * i], gf[2 * i], xf[2 * i]), fmaf(red[2 * i + 1], gf[2 * i + 1], xf[2 * i + 1]));
#pragma unroll
    for (int i = 0; i < 4; i++)
      stsm4(ot + (lane & 15) * 144 + (2 * i + (lane >> 4)) * 16, ow[4 * i], ow[4 * i + 1], ow[4 * i + 2], ow[4 * i + 3]);
    __syncwarp();
#pragma unroll
    for (int i = 0; i < 4; i++) {
      uint4 v;
      lds128(ot + (i * 4 + (lane >> 3)) * 144 + (lane & 7) * 16, v.x, v.y, v.z, v.w);
      *(uint4*)(out + (size_t)(qb * 128 + cw * 16 + i * 4 + (lane >> 3)) * DM + hs * 64 + (lane & 7) * 8) = v;
    }
    prof(wg, 22);
  }
}

constexpr int FST_X = 24, FST_END = FST_X + 14 * 12;
__device__ __forceinline__ void ffn_producer(const Ctx& cx, int f, const CUtensorMap* tmX, const CUtensorMap* tmG,
                                             const CUtensorMap* tmU, const CUtensorMap* tmD) {
  const uint32_t full = cx.sb + SM_FULL, empty = cx.sb + SM_EMPTY;
  int pair = -2, u = 0;
#pragma unroll 1
  for (int st = 0; st < FST_END; st++) {
    const uint32_t sl = st & 7;
    const int unit = pair * 2 + (u & 1), k = u >> 1, k3 = k >= 3 ? k - 3 : k;
    if (unit < 27) {
      mbar_wait(empty + 8 * sl, ((st >> 3) & 1) ^ 1);
      mbar_expect_tx(full + 8 * sl, FSTAGE);
      if (pair < 0) tma3d(cx.sb + sl * FSTAGE, tmX, f * 512 + ((pair + 2) * 4 + (k >= 3) * 2 + (u & 1)) * 64, k3 * 3, full + 8 * sl);
      else if (pair < 9) tma2d_stream(cx.sb + sl * FSTAGE, k < 3 ? tmG : tmU, f * 1152 + unit * 64, k3 * 192, full + 8 * sl);
      else tma2d_stream(cx.sb + sl * FSTAGE, tmD, (unit - 18) * 64, f * 1152 + k * 192, full + 8 * sl);
    }
    if (++u == 12) { u = 0; pair++; }
  }
}

__device__ __forceinline__ void ffn_consumer(const Ctx& cx, int f, int wg, int cw, int lane, const __nv_bfloat16* x,
                                             const __nv_bfloat16* w_r) {
  const int r = lane >> 2, c = lane & 3, tid = cw * 32 + lane;
  unsigned e = 0;
  if (tid == 0) {
    e = cx.gs->launch[blockIdx.x];
    cx.gs->launch[blockIdx.x] = e + 1;
    *(unsigned*)(cx.sp + SM_TAG) = e;
  }
  if (tid < 72) *(uint4*)(cx.sp + SM_H + tid * 16) = *(const uint4*)(w_r + tid * 8);
  bar_sync(3, 256);
  prof(wg, 0);
  const uint32_t full = cx.sb + SM_FULL, empty = cx.sb + SM_EMPTY;
  const bool signaller = (tid & 127) == 0;
#pragma unroll 1
  for (int b = wg; b < 8; b += 2) {
    const int row0 = f * 512 + b * 64 + (cw & 3) * 16 + r;
    const uint32_t lo = ((cw & 3) * 16 + (lane & 15)) * 128 + (((lane >> 4) ^ (lane & 7)) << 4);
    LnAcc a;
    a.clear();
#pragma unroll 1
    for (int bx = 0; bx < 9; bx++) {
      const int st = (b >> 1) * 6 + (bx / 3) * 2 + wg;
      if (bx % 3 == 0) mbar_wait(full + 8 * (st & 7), (st >> 3) & 1);
#pragma unroll
      for (int k = 0; k < 4; k++) {
        uint32_t x0, x1, x2, x3;
        ldsm4(cx.sb + (st & 7) * FSTAGE + (bx % 3) * 8192 + (lo ^ (k << 5)), x0, x1, x2, x3);
        ln_accum1(a, k & 1, x0, x1, x2, x3);
      }
    }
    prof(wg, 8 + (b >> 1) * 3);
    float mean0, rstd0, mean1, rstd1;
    ln_stats(a, lane, mean0, rstd0, mean1, rstd1);
    prof(wg, 9 + (b >> 1) * 3);
    const uint32_t mm0 = pack2(mean0, mean0), mm1 = pack2(mean1, mean1);
    float d0[4] = {0, 0, 0, 0}, d1[4] = {0, 0, 0, 0};
#pragma unroll 1
    for (int bx = 0; bx < 9; bx++) {
      const int st = (b >> 1) * 6 + (bx / 3) * 2 + wg;
#pragma unroll
      for (int k = 0; k < 4; k++) {
        uint32_t n[4];
        ldsm4(cx.sb + (st & 7) * FSTAGE + (bx % 3) * 8192 + (lo ^ (k << 5)), n[0], n[1], n[2], n[3]);
        const uint8_t* wp = cx.sp + SM_H + (bx * 4 + k) * 32 + 4 * c;
#pragma unroll
        for (int i = 0; i < 4; i++) {
          const uint32_t t = sub2(n[i], (i & 1) ? mm1 : mm0);
          const float rs = (i & 1) ? rstd1 : rstd0;
          n[i] = pack2(bf_lo(t) * rs, bf_hi(t) * rs);
        }
        if (k & 1) hmma_k16(d1, n[0], n[1], n[2], n[3], *(const uint32_t*)wp, *(const uint32_t*)(wp + 16));
        else hmma_k16(d0, n[0], n[1], n[2], n[3], *(const uint32_t*)wp, *(const uint32_t*)(wp + 16));
      }
    }
    prof(wg, 10 + (b >> 1) * 3);
    bar_sync(4 + wg, 128);
    if (signaller) {
#pragma unroll
      for (int i = 0; i < 3; i++) mbar_arrive(empty + 8 * (((b >> 1) * 6 + i * 2 + wg) & 7));
    }
    if (c == 0) {
      cx.gs->r[row0] = bfr(d0[0] + d1[0]);
      cx.gs->r[row0 + 8] = bfr(d0[2] + d1[2]);
      cx.gs->stats[row0] = make_float2(mean0, rstd0);
      cx.gs->stats[row0 + 8] = make_float2(mean1, rstd1);
    }
  }
  prof(wg, 1);
  bar_sync(3, 256);
  e = *(const unsigned*)(cx.sp + SM_TAG);
  if (tid == 0) {
    atom_add_acq_rel(&cx.gs->rcnt);
#pragma unroll 1
    for (int n = 0; n < (1 << 16) && (int)(ld_acquire(&cx.gs->rcnt) - 4 * (e + 1)) < 0; n++) {}
  }
  bar_sync(3, 256);
  prof(wg, 2);
  uint32_t key[8];
#pragma unroll
  for (int i = 0; i < 8; i++) {
    const int row = i * 256 + tid;
    const uint32_t b = __float_as_uint(__ldcg(&cx.gs->r[row])) >> 16;
    key[i] = (((b & 0x8000u) ? (~b & 0xFFFFu) : (b | 0x8000u)) << 16) | (uint32_t)(0xFFFF - row);
  }
  int mysel = 0;
#pragma unroll 1
  for (int k = 0; k < TOPC; k++) {
    uint32_t m = key[0];
#pragma unroll
    for (int i = 1; i < 8; i++) m = max(m, key[i]);
    m = __reduce_max_sync(0xffffffffu, m);
    uint32_t* tk = (uint32_t*)(cx.sp + SM_TOPK) + (k & 1) * 8;
    if (lane == 0) tk[cw] = m;
    bar_sync(3, 256);
    m = __reduce_max_sync(0xffffffffu, tk[lane & 7]);
#pragma unroll
    for (int i = 0; i < 8; i++) if (key[i] == m) key[i] = 0;
    if (k == cw) mysel = 0xFFFF - (int)(m & 0xFFFF);
  }
  {
    const float2 st = __ldcg(&cx.gs->stats[mysel]);
    const uint32_t mm = pack2(st.x, st.x);
#pragma unroll 3
    for (int i = 0; i < 9; i++) {
      const uint32_t t = sub2(*(const uint32_t*)(x + (size_t)mysel * DM + i * 64 + 2 * lane), mm);
      *(uint32_t*)(cx.sp + SM_XSEL + i * 1024 + cw * 128 + (((lane >> 2) ^ cw) << 4) + (lane & 3) * 4) =
          pack2(bf_lo(t) * st.y, bf_hi(t) * st.y);
    }
    if (lane == 0) *(int*)(cx.sp + SM_IDX + 4 * cw) = mysel;
  }
  asm volatile("fence.proxy.async.shared::cta;" ::: "memory");
  bar_sync(3, 256);
  prof(wg, 3);
  auto run = [&](float (&acc)[4], int st, int n, uint32_t b) {
#pragma unroll 1
    for (int u = 0; u < n; u++, st += 2, b += 3072) {
      const uint32_t sl = st & 7;
      mbar_wait(full + 8 * sl, (st >> 3) & 1);
      wg_fence();
      const uint64_t da = mkdesc(cx.sb + sl * FSTAGE, 16), db = mkdesc(b, 16);
#pragma unroll
      for (int k = 0; k < 12; k++) mma_n8(acc, da + k * 128, db + (k >> 2) * 64 + (k & 3) * 2, u > 0 || k > 0);
      wg_commit();
      wg_wait<0>();
      if (signaller) mbar_arrive(empty + 8 * sl);
    }
    pin(acc);
  };
#pragma unroll 1
  for (int unit = wg; unit < 27; unit += 2) {
    if (unit >> 1 == 9) {
      asm volatile("fence.proxy.async.shared::cta;" ::: "memory");
      bar_sync(3, 256);
      prof(wg, 4);
    }
    const bool gu = unit < 18;
    float a0[4], a1[4];
#pragma unroll 1
    for (int m = 0; m < (gu ? 2 : 1); m++) {
      run(a1, FST_X + (unit >> 1) * 12 + m * 6 + wg, gu ? 3 : 6, cx.sb + (gu ? SM_XSEL : SM_H));
      if (m == 0) { a0[0] = a1[0]; a0[1] = a1[1]; a0[2] = a1[2]; a0[3] = a1[3]; }
    }
#pragma unroll
    for (int i = 0; i < 4; i++) {
      const int fl = (cw & 3) * 16 + r + (i >> 1) * 8, tok = 2 * c + (i & 1);
      if (gu) {
        const float h = bfr(silu_f(bfr(a0[i]))) * bfr(a1[i]);
        *(__nv_bfloat16*)(cx.sp + SM_H + unit * 1024 + tok * 128 + (((fl >> 3) ^ tok) << 4) + (fl & 7) * 2) = __float2bfloat16_rn(h);
      } else {
        cx.gs->ypart[(f * TOPC + tok) * DM + (unit - 18) * 64 + fl] = a1[i];
      }
    }
  }
  prof(wg, 5);
  bar_sync(3, 256);
  if (tid == 0) *(unsigned*)(cx.sp + SM_TOPK) = atom_add_acq_rel(&cx.gs->ycnt) == 4 * e + 3;
  bar_sync(3, 256);
  if (*(const unsigned*)(cx.sp + SM_TOPK)) {
    const int row = *(const int*)(cx.sp + SM_IDX + 4 * cw);
    const float rs = bfr(rcp(1.0f + ex2(-1.4426950408889634f * __ldcg(&cx.gs->r[row]))));
#pragma unroll 1
    for (int d = lane * 2; d < DM; d += 192) {
#pragma unroll
      for (int i = 0; i < 3; i++) {
        const float* p = cx.gs->ypart + cw * DM + d + i * 64;
        const float2 a = __ldcg((const float2*)p), b = __ldcg((const float2*)(p + TOPC * DM)),
                     e2 = __ldcg((const float2*)(p + 2 * TOPC * DM)), h = __ldcg((const float2*)(p + 3 * TOPC * DM));
        const uint32_t y = pack2((a.x + b.x) + (e2.x + h.x), (a.y + b.y) + (e2.y + h.y));
        const uint32_t u = pack2(bf_lo(y) * rs, bf_hi(y) * rs);
        *(float2*)(cx.gs->upd + cw * DM + d + i * 64) = make_float2(bf_lo(u), bf_hi(u));
      }
    }
    if (lane == 0) cx.gs->idx[cw] = row;
    bar_sync(3, 256);
    if (tid == 0) st_release(&cx.gs->ffn_flag, e + 1);
    prof(wg, 6);
  }
}

struct Maps { CUtensorMap m[8]; };
__global__ void __cluster_dims__(2, 1, 1) __launch_bounds__(THREADS, 1)
fused_kernel(const __nv_bfloat16* __restrict__ x, const __nv_bfloat16* __restrict__ w_r, const __nv_bfloat16* __restrict__ wq,
             const __nv_bfloat16* __restrict__ wo, __nv_bfloat16* __restrict__ out, Scratch* gs,
             const __grid_constant__ Maps maps, const __nv_bfloat16* __restrict__ kc) {
  const CUtensorMap &tmX = maps.m[0], &tmWq = maps.m[1], &tmK = maps.m[2], &tmV = maps.m[3], &tmWo = maps.m[4], &tmG = maps.m[5],
                    &tmU = maps.m[6], &tmD = maps.m[7];
  extern __shared__ __align__(1024) uint8_t smem_raw[];
  prof(0, 23, 511);
  Ctx cx;
  cx.sb = smem_u32(smem_raw);
  cx.sp = smem_raw;
  cx.gs = gs;
  cx.rank = blockIdx.x & 1;
  const int warp = __shfl_sync(0xffffffffu, threadIdx.x >> 5, 0);
  const int cluster = blockIdx.x >> 1;
  const bool is_ffn = blockIdx.x >= N_ATT_CTA;
  const int c7 = ((cluster - 36) * 37) >> 8;
  const int hs = cluster < 4 ? 4 + cluster : cluster < 36 ? (cluster - 4) >> 3 : 4 + c7;
  const int qb = (cluster < 4 ? 0 : cluster < 36 ? (cluster - 4) & 7 : cluster - 35 - 7 * c7) * 2 + cx.rank;

  extern __shared__ __align__(1024) uint8_t smem_alias[];
  const uint32_t xf = smem_u32(smem_alias) + SM_MISC + warp * 24;
  if (warp == 4 && elect_one()) prefetch_tmap(&tmX);
  if (warp == 6 && !is_ffn && elect_one()) prefetch_l2(x + (size_t)(qb * 128 + hs * 8) * DM, 8 * DM * 2);
  if (elect_one()) {
    const uint32_t cnt = warp == 3 ? 64 : (warp > 4 && warp < 8 && !is_ffn) ? 4 : 1;
#pragma unroll
    for (int i = 0; i < 3; i++) mbar_init(xf + 8 * i, cnt);
    asm volatile("fence.proxy.async.shared::cta;" ::: "memory");
    asm volatile("fence.mbarrier_init.release.cluster;" ::: "memory");
  }
  __syncwarp();
  cluster_arrive();
  if (warp == 4 && !is_ffn) {
    if (elect_one()) {
      profc(0, 28);
#pragma unroll
      for (int i = 0; i < 3; i++) {
        mbar_expect_tx(xf + 8 * i, 24576);
        tma3d(xf - SM_XFULL + SM_X + i * 24576, &tmX, qb * 128, i * 3, xf + 8 * i);
      }
      profc(0, 29);
    }
  } else if (warp > 8 && elect_one()) {
    prefetch_tmap(&tmX + (is_ffn ? warp - 4 : warp - 8));
  }
  __syncwarp();

  if (warp < 4) {
    asm volatile("setmaxnreg.dec.sync.aligned.u32 24;");
    cluster_wait();
    prof(0, 24, 511);
    if (warp == 0) {
      if (elect_one()) {
        if (is_ffn) ffn_producer(cx, blockIdx.x - N_ATT_CTA, &tmX, &tmG, &tmU, &tmD);
        else attn_producer(cx, qb, hs, &tmX, &tmK, &tmV, &tmWq, &tmWo);
        prof(0, 25, 511);
      }
    } else if (!is_ffn) {
      attn_gate(cx, qb, hs, threadIdx.x - 32, x);
      if (warp == 1) attn_helper(cx, qb, hs, read_lane(), x, wo);
      else { bar_arrive(BAR_HELPER, 128); attn_stage_xg(cx, qb, hs, threadIdx.x - 64, x); }
      attn_finish8(cx, qb, hs, warp - 1, read_lane(), out);

    }
    __syncwarp();
    cluster_arrive();
    cluster_wait();
  } else {
    asm volatile("setmaxnreg.inc.sync.aligned.u32 240;");
    cluster_wait();
    const int cw = warp - 4, wg = cw >> 2;
    if (is_ffn) ffn_consumer(cx, blockIdx.x - N_ATT_CTA, wg, cw, read_lane(), x, w_r);
    else attn_consumer(cx, qb, hs, wg, cw, read_lane(), x, kc, out);
  }
}

typedef CUresult (*EncodeFn)(CUtensorMap*, CUtensorMapDataType, cuuint32_t, void*, const cuuint64_t*, const cuuint64_t*,
                             const cuuint32_t*, const cuuint32_t*, CUtensorMapInterleave, CUtensorMapSwizzle,
                             CUtensorMapL2promotion, CUtensorMapFloatOOBfill);

void encode(EncodeFn fn, CUtensorMap* m, const void* p, int rank, const cuuint64_t* dims, const cuuint64_t* strides,
            const cuuint32_t* box) {
  const cuuint32_t es[5] = {1, 1, 1, 1, 1};
  fn(m, CU_TENSOR_MAP_DATA_TYPE_BFLOAT16, rank, const_cast<void*>(p), dims, strides, box, es, CU_TENSOR_MAP_INTERLEAVE_NONE,
     CU_TENSOR_MAP_SWIZZLE_128B, CU_TENSOR_MAP_L2_PROMOTION_L2_128B, CU_TENSOR_MAP_FLOAT_OOB_FILL_NONE);
}
void encode2d(EncodeFn fn, CUtensorMap* m, const void* p, uint64_t rows, uint64_t cols, uint32_t box_rows) {
  const cuuint64_t dims[2] = {cols, rows}, strides[1] = {cols * 2};
  const cuuint32_t box[2] = {64, box_rows};
  encode(fn, m, p, 2, dims, strides, box);
}

}

extern "C" void kernel_launch(void* const* d_in, const int* in_sizes, int n_in, void* d_out, int out_size) {
  (void)in_sizes; (void)n_in; (void)out_size;
  void* fnp = nullptr;
  cudaDriverEntryPointQueryResult qr;
  cudaGetDriverEntryPoint("cuTensorMapEncodeTiled", &fnp, cudaEnableDefault, &qr);
  EncodeFn fn = (EncodeFn)fnp;
  Maps maps;
  CUtensorMap &tmX = maps.m[0], &tmWq = maps.m[1], &tmK = maps.m[2], &tmV = maps.m[3], &tmWo = maps.m[4], &tmG = maps.m[5],
              &tmU = maps.m[6], &tmD = maps.m[7];
  encode2d(fn, &tmK, d_in[1], 16 * SEQ, DH, 128);
  encode2d(fn, &tmV, d_in[2], 16 * SEQ, DH, 128);
  encode2d(fn, &tmWq, d_in[3], DM, 4096, 64);
  {
    const cuuint64_t dims[3] = {64, SEQ, 9}, strides[2] = {DM * 2, 128};
    const cuuint32_t box[3] = {64, 64, 3};
    encode(fn, &tmX, d_in[0], 3, dims, strides, box);
  }
  encode2d(fn, &tmWo, d_in[4], 4096, DM, 128);
  encode2d(fn, &tmG, d_in[7], DM, FF, 192);
  encode2d(fn, &tmU, d_in[8], DM, FF, 192);
  encode2d(fn, &tmD, d_in[9], FF, DM, 192);
  cudaFuncSetAttribute(fused_kernel, cudaFuncAttributeMaxDynamicSharedMemorySize, SM_TOTAL);
  void* gs = nullptr;
  cudaGetSymbolAddress(&gs, g_scratch);
  fused_kernel<<<N_CTA, THREADS, SM_TOTAL>>>((const __nv_bfloat16*)d_in[0], (const __nv_bfloat16*)d_in[6], (const __nv_bfloat16*)d_in[3],
                                            (const __nv_bfloat16*)d_in[4], (__nv_bfloat16*)d_out, (Scratch*)gs, maps, (const __nv_bfloat16*)d_in[1]);
}
```

```cpp
#include <cuda_runtime.h>
#include <cuda_bf16.h>
#include <cuda.h>
#include <stdint.h>

namespace {

constexpr int SEQ = 2048, DM = 576, DH = 128, FF = 4608, TOPC = 8;
constexpr int N_ATT_CTA = 128, N_CTA = 132;
constexpr int THREADS = 384;

constexpr uint32_t SM_RING = 0;
constexpr uint32_t STAGE = 32768;
constexpr uint32_t SM_SLOT = 131072;
constexpr uint32_t FSTAGE = 24576;
constexpr uint32_t SM_XSEL = 196608;
constexpr uint32_t SM_H = 205824;
constexpr uint32_t SM_MISC = 229376;
constexpr uint32_t SM_FULL = SM_MISC, SM_BAR_MISC = SM_MISC + 64, SM_BAR_XG = SM_MISC + 72, SM_XFULL = SM_MISC + 96,
                   SM_EMPTY = SM_MISC + 120, SM_TAG = SM_MISC + 288, SM_IDX = SM_MISC + 304, SM_TOPK = SM_MISC + 336,
                   SM_STATS = SM_MISC + 400;
constexpr uint32_t SM_TOTAL = SM_MISC + 1424;
constexpr uint32_t SM_X = SM_MISC - 147456;

constexpr int BAR_GATE = 6, BAR_HELPER = 7, BAR_OA = 8;
constexpr int NST_Q = 20, NST_KV = 128, NST_O = 18;
#define X_ORDER 0
#define X_PF 3
#define X_PFQ 2
#define X_REL 0
#define X_C0 32
#define X_C1 56
constexpr float SM_SCALE_LOG2 = 0.08838834764831845f * 1.4426950408889634f;

struct Scratch {
  uint4 part[16 * 64 * 2 * 4 * 128];
  uint4 gate[SEQ * DM / 8];
  float r[SEQ];
  float2 stats[SEQ];
  float ypart[4 * TOPC * DM];
  float upd[TOPC * DM];
  int idx[32];
  unsigned launch[160];
  unsigned rcnt, pad0[31], ycnt, pad1[31], ffn_flag, pad2[31];
};
__device__ __align__(1024) Scratch g_scratch;

__device__ __forceinline__ void profq(int) {}
__device__ __forceinline__ void prof(int, int, int = 0) {}
__device__ __forceinline__ void profc(int, int) {}

__device__ __forceinline__ uint32_t smem_u32(const void* p) { return (uint32_t)__cvta_generic_to_shared(p); }
__device__ __forceinline__ void mbar_init(uint32_t bar, uint32_t cnt) {
  asm volatile("mbarrier.init.shared::cta.b64 [%0], %1;" ::"r"(bar), "r"(cnt) : "memory");
}
__device__ __forceinline__ void mbar_expect_tx(uint32_t bar, uint32_t bytes) {
  asm volatile("mbarrier.arrive.expect_tx.shared::cta.b64 _, [%0], %1;" ::"r"(bar), "r"(bytes) : "memory");
}
__device__ __forceinline__ void mbar_arrive(uint32_t bar) {
  asm volatile("mbarrier.arrive.shared::cta.b64 _, [%0];" ::"r"(bar) : "memory");
}
__device__ __forceinline__ void mbar_arrive_cluster(uint32_t bar_cluster_addr) {
  asm volatile("mbarrier.arrive.shared::cluster.b64 _, [%0];" ::"r"(bar_cluster_addr) : "memory");
}
template <int ID>
__device__ __forceinline__ void mbar_arrive_cluster_now(uint32_t bar_cluster_addr, bool pred) {
  asm volatile("{\n.reg .pred p, q;\nsetp.ne.u32 p, %1, 0;\nsetp.eq.u32 q, %2, %3;\n"
               "ARR_LOOP:\n@p mbarrier.arrive.shared::cluster.b64 _, [%0];\n@q bra.uni ARR_LOOP;\n}"
               ::"r"(bar_cluster_addr), "r"((uint32_t)pred), "r"(blockIdx.y), "n"(ID) : "memory");
}
__device__ __forceinline__ void block_fence(int id) {
  asm volatile("{\n.reg .pred q;\nsetp.eq.u32 q, %0, %1;\nBF_LOOP:\n@q st.volatile.shared.u32 [%0], %0;\n@q bra.uni BF_LOOP;\n}"
               ::"r"(blockIdx.y), "r"(id) : "memory");
}
__device__ __forceinline__ bool mbar_test(uint32_t bar, uint32_t parity) {
  uint32_t ok;
  asm volatile("{\n.reg .pred p;\nmbarrier.test_wait.parity.shared::cta.b64 p, [%1], %2;\nselp.u32 %0, 1, 0, p;\n}"
               : "=r"(ok) : "r"(bar), "r"(parity) : "memory");
  return ok;
}
__device__ __forceinline__ void mbar_wait(uint32_t bar, uint32_t parity) {
  asm volatile("{\n.reg .pred p, q;\n.reg .u32 n;\nmov.u32 n, 0;\n"
               "WAIT_LOOP:\nmbarrier.try_wait.parity.shared::cta.b64 p, [%0], %1;\n"
               "add.u32 n, n, 1;\nsetp.lt.u32 q, n, 4194304;\nand.pred q, q, !p;\n@q bra WAIT_LOOP;\n}"
               ::"r"(bar), "r"(parity) : "memory");
}
__device__ __forceinline__ uint32_t mapa(uint32_t addr, uint32_t rank) {
  uint32_t r;
  asm volatile("mapa.shared::cluster.u32 %0, %1, %2;" : "=r"(r) : "r"(addr), "r"(rank));
  return r;
}
__device__ __forceinline__ void cluster_arrive() { asm volatile("barrier.cluster.arrive.relaxed.aligned;" ::: "memory"); }
__device__ __forceinline__ bool elect_one() {
  uint32_t p;
  asm volatile("{\n.reg .pred p;\nelect.sync _|p, 0xffffffff;\nselp.u32 %0, 1, 0, p;\n}" : "=r"(p));
  return p;
}
__device__ __forceinline__ int read_lane() { return threadIdx.x & 31; }
__device__ __forceinline__ void cluster_wait() { asm volatile("barrier.cluster.wait.acquire.aligned;" ::: "memory"); }
__device__ __forceinline__ void bar_sync(int id, int n) { asm volatile("barrier.cta.sync %0, %1;" ::"r"(id), "r"(n) : "memory"); }
__device__ __forceinline__ void bar_arrive(int id, int n) { asm volatile("barrier.cta.arrive %0, %1;" ::"r"(id), "r"(n) : "memory"); }

__device__ __forceinline__ uint64_t policy_evict_first() {
  uint64_t p;
  asm("createpolicy.fractional.L2::evict_first.b64 %0, 1.0;" : "=l"(p));
  return p;
}
__device__ __forceinline__ uint64_t policy_evict_normal() {
  uint64_t p;
  asm("createpolicy.fractional.L2::evict_normal.b64 %0, 1.0;" : "=l"(p));
  return p;
}
__device__ __forceinline__ void tma2d_mc(uint32_t dst, const CUtensorMap* tm, int c0, int c1, uint32_t bar, uint64_t pol) {
  asm volatile("cp.async.bulk.tensor.2d.shared::cluster.global.mbarrier::complete_tx::bytes.multicast::cluster.L2::cache_hint"
               " [%0], [%1, {%2, %3}], [%4], %5, %6;"
               ::"r"(dst), "l"(tm), "r"(c0), "r"(c1), "r"(bar), "h"((uint16_t)3), "l"(pol) : "memory");
}
__device__ __forceinline__ void tma3d(uint32_t dst, const CUtensorMap* tm, int c1, int c2, uint32_t bar) {
  asm volatile("cp.async.bulk.tensor.3d.shared::cluster.global.mbarrier::complete_tx::bytes [%0], [%1, {%2, %3, %4}], [%5];"
               ::"r"(dst), "l"(tm), "r"(0), "r"(c1), "r"(c2), "r"(bar) : "memory");
}
__device__ __forceinline__ void tma2d_stream(uint32_t dst, const CUtensorMap* tm, int c0, int c1, uint32_t bar) {
  asm volatile("{\n.reg .b64 pol;\ncreatepolicy.fractional.L2::evict_first.b64 pol, 1.0;\n"
               "cp.async.bulk.tensor.2d.shared::cluster.global.mbarrier::complete_tx::bytes.L2::cache_hint [%0], [%1, {%2, %3}], [%4], pol;\n}"
               ::"r"(dst), "l"(tm), "r"(c0), "r"(c1), "r"(bar) : "memory");
}
__device__ __forceinline__ void tma2d_prefetch(const CUtensorMap* tm, int c0, int c1) {
  asm volatile("cp.async.bulk.prefetch.tensor.2d.L2.global [%0, {%1, %2}];" ::"l"(tm), "r"(c0), "r"(c1) : "memory");
}
__device__ __forceinline__ void prefetch_l2(const void* p, uint32_t bytes) {
  asm volatile("cp.async.bulk.prefetch.L2.global [%0], %1;" ::"l"(p), "r"(bytes) : "memory");
}
__device__ __forceinline__ void prefetch_tmap(const CUtensorMap* tm) {
  asm volatile("prefetch.tensormap [%0];" ::"l"(tm) : "memory");
}

__device__ __forceinline__ void wg_fence() { asm volatile("wgmma.fence.sync.aligned;" ::: "memory"); }
__device__ __forceinline__ void wg_commit() { asm volatile("wgmma.commit_group.sync.aligned;" ::: "memory"); }
template <int N> __device__ __forceinline__ void wg_wait() { asm volatile("wgmma.wait_group.sync.aligned %0;" ::"n"(N) : "memory"); }

__device__ __forceinline__ uint64_t mkdesc(uint32_t addr, uint32_t lbo_bytes) {
  return (uint64_t)(((addr & 0x3FFFF) >> 4) | ((lbo_bytes >> 4) << 16)) | ((uint64_t)0x40000040u << 32);
}
template <int N> __device__ __forceinline__ void pin(float (&a)[N]) {
#pragma unroll
  for (int i = 0; i < N; i++) asm volatile("" : "+f"(a[i])::"memory");
}
template <int N> __device__ __forceinline__ void pin(uint32_t (&a)[N]) {
#pragma unroll
  for (int i = 0; i < N; i++) asm volatile("" : "+r"(a[i])::"memory");
}

#define F8(d, o) "+f"(d[o]), "+f"(d[o + 1]), "+f"(d[o + 2]), "+f"(d[o + 3]), "+f"(d[o + 4]), "+f"(d[o + 5]), "+f"(d[o + 6]), "+f"(d[o + 7])
#define R32A "%0, %1, %2, %3, %4, %5, %6, %7, %8, %9, %10, %11, %12, %13, %14, %15, %16, %17, %18, %19, %20, %21, %22, %23, %24, %25, %26, %27, %28, %29, %30, %31"
#define R32B "%32, %33, %34, %35, %36, %37, %38, %39, %40, %41, %42, %43, %44, %45, %46, %47, %48, %49, %50, %51, %52, %53, %54, %55, %56, %57, %58, %59, %60, %61, %62, %63"

template <int TB>
__device__ __forceinline__ void mma_n128(float (&d)[64], uint32_t a0, uint32_t a1, uint32_t a2, uint32_t a3, uint64_t db, int acc) {
  asm volatile("{\n.reg .pred p;\nsetp.ne.b32 p, %69, 0;\n"
               "wgmma.mma_async.sync.aligned.m64n128k16.f32.bf16.bf16 {" R32A ", " R32B "}, {%64, %65, %66, %67}, %68, p, 1, 1, %70;\n}\n"
               : F8(d, 0), F8(d, 8), F8(d, 16), F8(d, 24), F8(d, 32), F8(d, 40), F8(d, 48), F8(d, 56)
               : "r"(a0), "r"(a1), "r"(a2), "r"(a3), "l"(db), "r"(acc), "n"(TB));
}
__device__ __forceinline__ void mma_n64t(float (&d)[32], uint32_t a0, uint32_t a1, uint32_t a2, uint32_t a3, uint64_t db, int acc) {
  asm volatile("{\n.reg .pred p;\nsetp.ne.b32 p, %37, 0;\n"
               "wgmma.mma_async.sync.aligned.m64n64k16.f32.bf16.bf16 {" R32A "}, {%32, %33, %34, %35}, %36, p, 1, 1, 1;\n}\n"
               : F8(d, 0), F8(d, 8), F8(d, 16), F8(d, 24)
               : "r"(a0), "r"(a1), "r"(a2), "r"(a3), "l"(db), "r"(acc));
}
__device__ __forceinline__ void mma_n8(float (&d)[4], uint64_t da, uint64_t db, int acc) {
  asm volatile("{\n.reg .pred p;\nsetp.ne.b32 p, %6, 0;\n"
               "wgmma.mma_async.sync.aligned.m64n8k16.f32.bf16.bf16 {%0, %1, %2, %3}, %4, %5, p, 1, 1, 1, 0;\n}\n"
               : "+f"(d[0]), "+f"(d[1]), "+f"(d[2]), "+f"(d[3])
               : "l"(da), "l"(db), "r"(acc));
}
__device__ __forceinline__ void hmma_k8(float (&d)[4], uint32_t a0, uint32_t a1, uint32_t b0) {
  asm volatile("mma.sync.aligned.m16n8k8.row.col.f32.bf16.bf16.f32 {%0, %1, %2, %3}, {%4, %5}, {%6}, {%0, %1, %2, %3};"
               : "+f"(d[0]), "+f"(d[1]), "+f"(d[2]), "+f"(d[3]) : "r"(a0), "r"(a1), "r"(b0));
}
__device__ __forceinline__ void hmma_k16(float (&d)[4], uint32_t a0, uint32_t a1, uint32_t a2, uint32_t a3, uint32_t b0, uint32_t b1) {
  asm volatile("mma.sync.aligned.m16n8k16.row.col.f32.bf16.bf16.f32 {%0, %1, %2, %3}, {%4, %5, %6, %7}, {%8, %9}, {%0, %1, %2, %3};"
               : "+f"(d[0]), "+f"(d[1]), "+f"(d[2]), "+f"(d[3]) : "r"(a0), "r"(a1), "r"(a2), "r"(a3), "r"(b0), "r"(b1));
}

__device__ __forceinline__ uint32_t pack2(float lo, float hi) {
  uint32_t r;
  asm("cvt.rn.bf16x2.f32 %0, %1, %2;" : "=r"(r) : "f"(hi), "f"(lo));
  return r;
}
__device__ __forceinline__ float bf_lo(uint32_t w) { return __uint_as_float(w << 16); }
__device__ __forceinline__ float bf_hi(uint32_t w) { return __uint_as_float(w & 0xFFFF0000u); }
__device__ __forceinline__ float bfr(float x) { return __bfloat162float(__float2bfloat16_rn(x)); }
__device__ __forceinline__ uint32_t sub2(uint32_t a, uint32_t b) {
  uint32_t r;
  asm("sub.rn.bf16x2 %0, %1, %2;" : "=r"(r) : "r"(a), "r"(b));
  return r;
}
__device__ __forceinline__ uint32_t add2(uint32_t a, uint32_t b) {
  uint32_t r;
  asm("add.rn.bf16x2 %0, %1, %2;" : "=r"(r) : "r"(a), "r"(b));
  return r;
}
__device__ __forceinline__ float ex2(float x) {
  float r;
  asm("ex2.approx.ftz.f32 %0, %1;" : "=f"(r) : "f"(x));
  return r;
}
__device__ __forceinline__ float rcp(float x) {
  float r;
  asm("rcp.approx.ftz.f32 %0, %1;" : "=f"(r) : "f"(x));
  return r;
}
__device__ __forceinline__ float silu_f(float t) { return t * rcp(1.0f + ex2(-1.4426950408889634f * t)); }
__device__ __forceinline__ void sts128(uint32_t a, uint32_t x, uint32_t y, uint32_t z, uint32_t w) {
  asm volatile("st.shared.v4.u32 [%0], {%1, %2, %3, %4};" ::"r"(a), "r"(x), "r"(y), "r"(z), "r"(w) : "memory");
}
__device__ __forceinline__ void lds128(uint32_t a, uint32_t& x, uint32_t& y, uint32_t& z, uint32_t& w) {
  asm volatile("ld.shared.v4.u32 {%0, %1, %2, %3}, [%4];" : "=r"(x), "=r"(y), "=r"(z), "=r"(w) : "r"(a) : "memory");
}
__device__ __forceinline__ void ldsm4(uint32_t a, uint32_t& x, uint32_t& y, uint32_t& z, uint32_t& w) {
  asm volatile("ldmatrix.sync.aligned.m8n8.x4.shared.b16 {%0, %1, %2, %3}, [%4];" : "=r"(x), "=r"(y), "=r"(z), "=r"(w) : "r"(a) : "memory");
}
__device__ __forceinline__ void st_gran(uint4* p, uint32_t x, uint32_t y, uint32_t z, uint32_t w) {
  asm volatile("st.relaxed.gpu.global.v4.b32 [%0], {%1, %2, %3, %4};" ::"l"(p), "r"(x), "r"(y), "r"(z), "r"(w) : "memory");
}
__device__ __forceinline__ void ld_gran(const uint4* p, uint32_t& x, uint32_t& y, uint32_t& z, uint32_t& w) {
  asm volatile("ld.relaxed.gpu.global.v4.b32 {%0, %1, %2, %3}, [%4];" : "=r"(x), "=r"(y), "=r"(z), "=r"(w) : "l"(p) : "memory");
}
__device__ __forceinline__ void stsm4(uint32_t a, uint32_t x, uint32_t y, uint32_t z, uint32_t w) {
  asm volatile("stmatrix.sync.aligned.m8n8.x4.shared.b16 [%0], {%1, %2, %3, %4};" ::"r"(a), "r"(x), "r"(y), "r"(z), "r"(w) : "memory");
}
__device__ __forceinline__ void cp16(uint32_t dst, const void* src) {
  asm volatile("cp.async.cg.shared.global [%0], [%1], 16;" ::"r"(dst), "l"(src) : "memory");
}
template <class T>
__device__ __forceinline__ T* at(const void* base, uint32_t off) {
  uint64_t r;
  asm("{\n.reg .u32 lo, hi;\nmov.b64 {lo, hi}, %1;\nadd.cc.u32 lo, lo, %2;\naddc.u32 hi, hi, 0;\nmov.b64 %0, {lo, hi};\n}"
      : "=l"(r) : "l"(base), "r"(off));
  return (T*)__cvta_global_to_generic(r);
}
__device__ __forceinline__ void cp_wait_all() { asm volatile("cp.async.wait_all;" ::: "memory"); }
__device__ __forceinline__ void add_granules(float (&red)[32], const uint32_t (&g)[16]) {
#pragma unroll
  for (int i = 0; i < 16; i++) { red[2 * i] += bf_lo((i & 3) ? g[i] : g[i] & ~1u); red[2 * i + 1] += bf_hi(g[i]); }
}
__device__ __forceinline__ bool granules_ok(const uint32_t (&g)[16], uint32_t tag) {
  return __all_sync(0xffffffffu, (((g[0] ^ tag) | (g[4] ^ tag) | (g[8] ^ tag) | (g[12] ^ tag)) & 1) == 0);
}
__device__ __forceinline__ unsigned ld_acquire(const unsigned* p) {
  unsigned v;
  asm volatile("ld.acquire.gpu.global.u32 %0, [%1];" : "=r"(v) : "l"(p) : "memory");
  return v;
}
__device__ __forceinline__ unsigned atom_add_acq_rel(unsigned* p) {
  unsigned v;
  asm volatile("atom.acq_rel.gpu.global.add.u32 %0, [%1], 1;" : "=r"(v) : "l"(p) : "memory");
  return v;
}
__device__ __forceinline__ void st_release(unsigned* p, unsigned v) {
  asm volatile("st.release.gpu.global.u32 [%0], %1;" ::"l"(p), "r"(v) : "memory");
}

struct LnAcc {
  float sm[2][4], sq[8][4];
  __device__ __forceinline__ void clear() {
#pragma unroll
    for (int i = 0; i < 4; i++) {
      sm[0][i] = sm[1][i] = 0.f;
#pragma unroll
      for (int j = 0; j < 8; j++) sq[j][i] = 0.f;
    }
  }
};
template <int K0, int K1>
__device__ __forceinline__ void ln_fetch(uint32_t (&xa)[144], uint32_t boxes, uint32_t lo) {
#pragma unroll
  for (int k = K0; k < K1; k++) ldsm4(boxes + (k >> 2) * 8192 + (lo ^ ((k & 3) << 5)), xa[4 * k], xa[4 * k + 1], xa[4 * k + 2], xa[4 * k + 3]);
}
__device__ __forceinline__ void ln_accum1(LnAcc& a, int h, uint32_t x0, uint32_t x1, uint32_t x2, uint32_t x3) {
  const uint32_t ONES = 0x3F803F80u;
  hmma_k16(a.sm[h], x0, x1, x2, x3, ONES, ONES);
  hmma_k8(a.sq[4 * h], x0, x1, x0);
  hmma_k8(a.sq[4 * h + 1], x0, x1, x1);
  hmma_k8(a.sq[4 * h + 2], x2, x3, x2);
  hmma_k8(a.sq[4 * h + 3], x2, x3, x3);
}
template <int K0, int K1>
__device__ __forceinline__ void ln_accum(const uint32_t (&xa)[144], LnAcc& a) {
#pragma unroll
  for (int k = K0; k < K1; k++) ln_accum1(a, k & 1, xa[4 * k], xa[4 * k + 1], xa[4 * k + 2], xa[4 * k + 3]);
}
template <int K0, int K1>
__device__ __forceinline__ void ln_sums(const uint32_t (&xa)[144], float (&sm)[4][4]) {
#pragma unroll
  for (int k = K0; k < K1; k++) hmma_k16(sm[k & 3], xa[4 * k], xa[4 * k + 1], xa[4 * k + 2], xa[4 * k + 3], 0x3F803F80u, 0x3F803F80u);
}
__device__ __forceinline__ uint32_t sq8(const uint32_t* a) {
  uint32_t t, u;
  asm("mul.rn.bf16x2 %0, %1, %1;" : "=r"(t) : "r"(a[0]));
  asm("mul.rn.bf16x2 %0, %1, %1;" : "=r"(u) : "r"(a[2]));
#pragma unroll
  for (int i = 4; i < 16; i += 4) {
    asm("fma.rn.bf16x2 %0, %1, %1, %0;" : "+r"(t) : "r"(a[i]));
    asm("fma.rn.bf16x2 %0, %1, %1, %0;" : "+r"(u) : "r"(a[i + 2]));
  }
  return add2(t, u);
}
__device__ __forceinline__ void ln_centre(uint32_t (&xa)[144], int j0, int j1, uint32_t mm0, uint32_t mm1, float& sq0, float& sq1) {
#pragma unroll
  for (int j = 0; j < 72; j += 8)
    if (j >= j0 && j < j1) {
#pragma unroll
      for (int k = j; k < j + 8; k++) {
        xa[2 * k] = sub2(xa[2 * k], mm0);
        xa[2 * k + 1] = sub2(xa[2 * k + 1], mm1);
      }
      const uint32_t t0 = sq8(xa + 2 * j), t1 = sq8(xa + 2 * j + 1);
      sq0 += bf_lo(t0) + bf_hi(t0);
      sq1 += bf_lo(t1) + bf_hi(t1);
    }
}
__device__ __forceinline__ float ln_rstd(float msq, float d) {
  float sd;
  asm("sqrt.approx.f32 %0, %1;" : "=f"(sd) : "f"(bfr(bfr(fmaxf(msq - d * d, 0.0f)) + 1e-5f)));
  return rcp(bfr(sd));
}
__device__ __forceinline__ void ln_row(float sum, float sq, float& mean_b, float& rstd) {
  const float mean = sum * (1.0f / DM);
  mean_b = bfr(mean);
  rstd = ln_rstd(sq * (1.0f / DM), mean);
}
__device__ __forceinline__ void ln_diag(const LnAcc& a, int lane, float& t0, float& t1) {
  const bool odd = (lane >> 2) & 1;
  t0 = odd ? (a.sq[0][1] + a.sq[2][1]) + (a.sq[4][1] + a.sq[6][1]) : (a.sq[0][0] + a.sq[2][0]) + (a.sq[4][0] + a.sq[6][0]);
  t1 = odd ? (a.sq[1][3] + a.sq[3][3]) + (a.sq[5][3] + a.sq[7][3]) : (a.sq[1][2] + a.sq[3][2]) + (a.sq[5][2] + a.sq[7][2]);
}
__device__ __forceinline__ void ln_stats(const LnAcc& a, int lane, float& mean0, float& rstd0, float& mean1, float& rstd1) {
  float t0, t1;
  ln_diag(a, lane, t0, t1);
  const int src = (lane & ~3) | (lane >> 3);
  t0 = __shfl_sync(0xffffffffu, t0, src);
  t1 = __shfl_sync(0xffffffffu, t1, src);
  ln_row(a.sm[0][0] + a.sm[1][0], t0, mean0, rstd0);
  ln_row(a.sm[0][2] + a.sm[1][2], t1, mean1, rstd1);
}

template <bool ROUTED>
__device__ __forceinline__ uint32_t gate2(uint32_t x2, float mean_b, float rstd, float2 upd = make_float2(0.f, 0.f)) {
  const uint32_t xc = sub2(x2, pack2(mean_b, mean_b));
  uint32_t t = pack2(bf_lo(xc) * rstd, bf_hi(xc) * rstd);
  if (ROUTED) t = pack2(bf_lo(t) + upd.x, bf_hi(t) + upd.y);
  return pack2(silu_f(bf_lo(t)), silu_f(bf_hi(t)));
}

template <int V> struct IC { static constexpr int value = V; };

struct Ctx {
  uint32_t sb;
  uint8_t* sp;
  uint32_t rank;
  Scratch* gs;
};

__device__ __forceinline__ void dly(int) {}
__device__ __forceinline__ void attn_producer(const Ctx& cx, int qb, int hs, const CUtensorMap* tmX, const CUtensorMap* tmK, const CUtensorMap* tmV,
                                              const CUtensorMap* tmWq, const CUtensorMap* tmWo) {
  const uint32_t full = cx.sb + SM_FULL, empty = cx.sb + SM_EMPTY, ring = cx.sb + SM_RING + cx.rank * 16384;
  const uint64_t keep = policy_evict_normal(), last_use = policy_evict_first();
  int st = 0;
#pragma unroll 1
  for (int p = 0; p < 4; p++) {
    const int n0 = (hs * 4 + ((p + 1) & 3)) * DH + cx.rank * 64;
#pragma unroll 1
    for (int i = 0; i < 5; i++, st++) {
      const uint32_t sl = st & 3;
      if (st == X_ORDER) {
#pragma unroll 1
        for (int j = 0; j < 3; j++) {
          mbar_expect_tx(cx.sb + SM_XFULL + 96 + 8 * j, 24576);
          tma3d(cx.sb + SM_X + 73728 + j * 24576, tmX, qb * 128 + 64, j * 3, cx.sb + SM_XFULL + 96 + 8 * j);
        }
      }
      mbar_wait(empty + 8 * sl, ((st >> 2) ^ (sl >> 1) ^ 1) & 1);
      dly(st);
      mbar_expect_tx(full + 8 * sl, i == 2 ? 16384 : 32768);
      const int k0 = i < 3 ? 128 * i : 128 * i - 64;
      tma2d_mc(ring + sl * STAGE, tmWq, n0, k0, full + 8 * sl, last_use);
      if (i != 2) tma2d_mc(ring + sl * STAGE + 8192, tmWq, n0, k0 + 64, full + 8 * sl, last_use);
      if (st == X_PFQ) {
#pragma unroll 1
        for (int b = 8 + qb; b < 72; b += 16) tma2d_prefetch(tmWq, (hs * 4 + ((b / 18 + 1) & 3)) * DH + (b & 1) * 64, ((b % 18) >> 1) * 64);
      }
    }
  }
#pragma unroll 1
  for (int u = 0; u < NST_KV; u++, st++) {
    const bool isK = (u == 0) || ((u & 1) && u != 127);
    const int it = u == 0 ? 0 : (u == 127 ? 63 : (isK ? (u + 1) >> 1 : (u >> 1) - 1));
    const int row = (hs * 2 + (it >> 5)) * SEQ + (it & 15) * 128;
    const uint32_t sl = st & 3;
    mbar_wait(empty + 8 * sl, ((st >> 2) ^ (sl >> 1) ^ 1) & 1);
    dly(st);
    mbar_expect_tx(full + 8 * sl, 32768);
    tma2d_mc(ring + sl * STAGE, isK ? tmK : tmV, cx.rank * 64, row, full + 8 * sl, (it & 16) ? last_use : keep);
  }
#pragma unroll 1
  for (int u = 0; u < NST_O; u++, st++) {
    const int s = u >> 1;
    const int blk = s == 0 ? 8 : ((hs + s) & 7);
    const uint32_t sl = st & 3;
    mbar_wait(empty + 8 * sl, ((st >> 2) ^ (sl >> 1) ^ 1) & 1);
    dly(st);
    mbar_expect_tx(full + 8 * sl, 32768);
    tma2d_mc(ring + sl * STAGE, tmWo, blk * 64, hs * 512 + (((u & 1) * 2 + cx.rank + 3) & 3) * 128, full + 8 * sl, last_use);
  }
}

__device__ __forceinline__ void attn_gate(const Ctx& cx, int qb, int hs, int t, const __nv_bfloat16* x) {
  const uint32_t base = (qb * 128 * DM + (t & 7) * 8) * 2;
  uint32_t lr = t >> 3, o = base + (lr * DM + hs * 64) * 2;
  uint4 nx = __ldg(at<const uint4>(x, o));
  bar_sync(BAR_GATE, 352);
#pragma unroll 1
  for (uint32_t n = (t >> 3) + 12; n < 156; n += 12) {
    const uint4 v = nx;
    const float2 st = *(const float2*)(cx.sp + SM_STATS + 8 * lr);
    uint4* dst = at<uint4>(cx.gs->gate, o);
    lr = n < 128 ? n : n + hs * 16 - 128;
    o = base + (lr * DM + (n < 128 ? hs * 64 : 512)) * 2;
    if (n < 144) nx = __ldg(at<const uint4>(x, o));
    *dst = make_uint4(gate2<false>(v.x, st.x, st.y), gate2<false>(v.y, st.x, st.y), gate2<false>(v.z, st.x, st.y), gate2<false>(v.w, st.x, st.y));
  }
}

constexpr uint32_t SM_XO = SM_SLOT, SM_GO = SM_SLOT + 128 * 144;
constexpr uint32_t SM_X8 = SM_SLOT + 2 * STAGE + 20480, SM_G8 = SM_X8 + 16 * 144;
__device__ __forceinline__ void attn_stage_xg(const Ctx& cx, int qb, int hs, int t, const __nv_bfloat16* x) {
  bar_sync(BAR_OA, 352);
#pragma unroll 1
  for (uint32_t lr = t >> 3; lr < 128; lr += 8) {
    const uint32_t o = ((qb * 128 + lr) * DM + hs * 64 + (t & 7) * 8) * 2;
    cp16(cx.sb + SM_XO + lr * 144 + (t & 7) * 16, at<const void>(x, o));
    cp16(cx.sb + SM_GO + lr * 144 + (t & 7) * 16, at<const void>(cx.gs->gate, o));
  }
  cp_wait_all();
  mbar_arrive(cx.sb + SM_BAR_XG);
}

__device__ __forceinline__ void attn_helper(const Ctx& cx, int qb, int hs, int lane, const __nv_bfloat16* x, const __nv_bfloat16* wo) {
  unsigned e = 0;
  if (lane == 0) {
    e = cx.gs->launch[blockIdx.x];
    cx.gs->launch[blockIdx.x] = e + 1;
  }
  e = __shfl_sync(0xffffffffu, e, 0);
  bar_sync(BAR_HELPER, 128);
  prefetch_l2(at<const void>(wo, (hs * 512 + qb * 32 + lane) * (DM * 2)), DM * 2);
#pragma unroll 1
  for (int n = 0; n < (1 << 16) && ld_acquire(&cx.gs->ffn_flag) != e + 1; n++) __nanosleep(1000);
  const uint32_t tag = ~e & 1;
  {
#pragma unroll 1
    for (int i = 0; i < 2 * TOPC; i++) {
      const int lr = __ldcg(&cx.gs->idx[i >> 1]) - qb * 128, col = ((i & 1) ? 512 : hs * 64) + 2 * lane;
      if ((i & 1) ? (lr >> 4) == hs : (lr >> 7) == 0) {
        const float2 st = *(const float2*)(cx.sp + SM_STATS + 8 * lr);
        const uint32_t o = ((qb * 128 + lr) * DM + col) * 2;
        *at<uint32_t>(cx.gs->gate, o) =
            gate2<true>(*at<const uint32_t>(x, o), st.x, st.y, __ldcg(at<const float2>(cx.gs->upd, ((i >> 1) * DM + col) * 4)));
      }
    }
  }
  if (lane == 0) *(uint32_t*)(cx.sp + SM_TAG) = tag;
  __syncwarp();
  if (lane == 0) mbar_arrive(cx.sb + SM_BAR_MISC);

  const uint4* src = at<const uint4>(cx.gs->part, (((qb * 64 + 56) * 2 + (hs >> 2)) * 4 * 128 + (hs & 3) * 32 + lane) * 16);
  const uint32_t stg = cx.sb + SM_SLOT + 2 * STAGE + lane * 16;
  bar_sync(BAR_OA, 352);

#pragma unroll 1
  for (int i = 0; i < 4; i++) {
    const int ch = i * 32 + lane;
    const uint32_t o = ((qb * 128 + hs * 16 + (ch >> 3)) * DM + 512 + (ch & 7) * 8) * 2;
    cp16(cx.sb + SM_X8 + (ch >> 3) * 144 + (ch & 7) * 16, at<const void>(x, o));
    cp16(cx.sb + SM_G8 + (ch >> 3) * 144 + (ch & 7) * 16, at<const void>(cx.gs->gate, o));
  }
#pragma unroll 1
  for (int n = 0; n < (1 << 16); n++) {
    __nanosleep(n ? 500 : 2000);
    uint32_t a, b, d, t;
    ld_gran(at<const uint4>(src, ((lane & 7) * (2 * 4 * 128) + 3 * 128 + 31 - lane) * 16), a, b, d, t);
    if (__all_sync(0xffffffffu, (a & 1) == tag)) break;
  }
#pragma unroll 1
  for (int n = 0; n < (1 << 16); n++) {
#pragma unroll 1
    for (int i = 0; i < 8; i++) {
#pragma unroll
      for (int g = 0; g < 4; g++) cp16(stg + (i * 4 + g) * 512, src + i * (2 * 4 * 128) + g * 128);
    }
    cp_wait_all();
    uint32_t bad = 0;
#pragma unroll 4
    for (int i = 0; i < 32; i++) bad |= *(const volatile uint32_t*)(cx.sp + SM_SLOT + 2 * STAGE + lane * 16 + i * 512) ^ tag;
    if (__all_sync(0xffffffffu, (bad & 1) == 0)) break;
  }

}
__device__ __forceinline__ void attn_finish8(const Ctx& cx, int qb, int hs, int hw, int lane, __nv_bfloat16* out) {
  bar_sync(BAR_GATE, 96);
#pragma unroll 1
  for (int g = hw; g < 4; g += 3) {
    float acc[8] = {0.f, 0.f, 0.f, 0.f, 0.f, 0.f, 0.f, 0.f};
#pragma unroll 2
    for (int sidx = 0; sidx < 8; sidx++) {
      uint32_t a, b, d, t;
      lds128(cx.sb + SM_SLOT + 2 * STAGE + lane * 16 + (sidx * 4 + g) * 512, a, b, d, t);
      acc[0] += bf_lo(a & ~1u); acc[1] += bf_hi(a); acc[2] += bf_lo(b); acc[3] += bf_hi(b);
      acc[4] += bf_lo(d); acc[5] += bf_hi(d); acc[6] += bf_lo(t); acc[7] += bf_hi(t);
    }
#pragma unroll
    for (int j = 0; j < 4; j++) {
      const int o = ((lane >> 2) + (j & 1) * 8) * 144 + (2 * g + (j >> 1)) * 16 + (lane & 3) * 4;
      uint32_t* xp = (uint32_t*)(cx.sp + SM_X8 + o);
      const uint32_t xw = *xp, gw = *(const uint32_t*)(cx.sp + SM_G8 + o);
      *xp = pack2(fmaf(acc[2 * j], bf_lo(gw), bf_lo(xw)), fmaf(acc[2 * j + 1], bf_hi(gw), bf_hi(xw)));
    }
  }
  bar_sync(BAR_GATE, 96);
#pragma unroll 1
  for (int ch = hw * 32 + lane; ch < 128; ch += 96)
    *at<uint4>(out, ((qb * 128 + hs * 16 + (ch >> 3)) * DM + 512 + (ch & 7) * 8) * 2) =
        *(const uint4*)(cx.sp + SM_X8 + (ch >> 3) * 144 + (ch & 7) * 16);
}

constexpr float SUM_HI = 1.8446744e19f, SUM_LO = 9.0949470e-13f;

__device__ __forceinline__ void softmax_shift(float (&s)[64], float n0, float n1) {
#pragma unroll
  for (int i = 0; i < 64; i++) s[i] += (i & 2) ? n1 : n0;
}
template <int LO, int HI>
__device__ __forceinline__ void softmax_exp(float (&s)[64]) {
#pragma unroll
  for (int i = LO; i < HI; i++) s[i] = ex2(s[i]);
}
__device__ __forceinline__ void row_sums(const uint32_t (&pf)[32], float& l0, float& l1) {
  uint32_t t[16];
#pragma unroll
  for (int i = 0; i < 16; i++) t[i] = add2(pf[(i >> 1) * 4 + (i & 1)], pf[(i >> 1) * 4 + 2 + (i & 1)]);
#pragma unroll
  for (int i = 0; i < 8; i++) t[i] = add2(t[(i >> 1) * 4 + (i & 1)], t[(i >> 1) * 4 + 2 + (i & 1)]);
#pragma unroll
  for (int i = 0; i < 4; i++) t[i] = add2(t[(i >> 1) * 4 + (i & 1)], t[(i >> 1) * 4 + 2 + (i & 1)]);
  l0 += (bf_lo(t[0]) + bf_lo(t[2])) + (bf_hi(t[0]) + bf_hi(t[2]));
  l1 += (bf_lo(t[1]) + bf_lo(t[3])) + (bf_hi(t[1]) + bf_hi(t[3]));
}
__device__ __forceinline__ void row_max(const float (&s)[64], float& x0, float& x1) {
  x0 = s[0];
  x1 = s[2];
#pragma unroll
  for (int i = 0; i < 64; i += 4) { x0 = fmaxf(x0, fmaxf(s[i], s[i + 1])); x1 = fmaxf(x1, fmaxf(s[i + 2], s[i + 3])); }
  x0 = fmaxf(x0, __shfl_xor_sync(0xffffffffu, x0, 1));
  x1 = fmaxf(x1, __shfl_xor_sync(0xffffffffu, x1, 1));
  x0 = fmaxf(x0, __shfl_xor_sync(0xffffffffu, x0, 2));
  x1 = fmaxf(x1, __shfl_xor_sync(0xffffffffu, x1, 2));
}
__device__ __forceinline__ void softmax_rebase(float (&s)[64], float& n0, float& n1, float& sc0, float& sc1) {
  float x0, x1;
  row_max(s, x0, x1);
  x0 = fmaxf(x0, 1.f);
  x1 = fmaxf(x1, 1.f);
  n0 -= __log2f(x0);
  n1 -= __log2f(x1);
  sc0 = exp2f(-__log2f(x0));
  sc1 = exp2f(-__log2f(x1));
#pragma unroll
  for (int i = 0; i < 64; i++) s[i] *= (i & 2) ? sc1 : sc0;
}
__device__ __forceinline__ void softmax_redo(float (&s)[64], const uint32_t (&q)[32], const __nv_bfloat16* kblk, int lane, float& n0,
                                             float& n1, float& sc0, float& sc1) {
  const __nv_bfloat16* kp = kblk + (lane >> 2) * DH + (lane & 3) * 2;
#pragma unroll
  for (int nb = 0; nb < 16; nb++) {
    float d[4] = {0.f, 0.f, 0.f, 0.f};
#pragma unroll
    for (int k = 0; k < 8; k++)
      hmma_k16(d, q[4 * k], q[4 * k + 1], q[4 * k + 2], q[4 * k + 3], *(const uint32_t*)(kp + nb * 8 * DH + k * 16),
               *(const uint32_t*)(kp + nb * 8 * DH + k * 16 + 8));
    s[4 * nb] = d[0]; s[4 * nb + 1] = d[1]; s[4 * nb + 2] = d[2]; s[4 * nb + 3] = d[3];
    block_fence(100 + nb);
  }
  float x0, x1;
  row_max(s, x0, x1);
  const float m0 = fminf(n0, -x0), m1 = fminf(n1, -x1);
  sc0 = ex2(m0 - n0);
  sc1 = ex2(m1 - n1);
  n0 = m0; n1 = m1;
  softmax_shift(s, n0, n1);
  softmax_exp<0, 64>(s);
}

__device__ __forceinline__ void attn_consumer(const Ctx& cx, int qb, int hs, int wg, int cw, int lane, const __nv_bfloat16* x,
                                              const __nv_bfloat16* kc, __nv_bfloat16* out) {
  const int r = lane >> 2, c = lane & 3, tw = (cw & 3) * 32 + lane;
  const int lr0 = cw * 16 + r;
  const uint32_t full = cx.sb + SM_FULL;
  const uint32_t ring = cx.sb + SM_RING;
  const uint32_t slot = cx.sb + SM_SLOT + wg * 16384 + tw * 16;
  const bool signaller = lane == 0 && (cw & 3) < 2;
  const int my_turn = 1 + wg, other_turn = 2 - wg;

  uint32_t q[32];
  uint32_t empty_c;
  {
    uint32_t xa[144];
    float rstd0, rstd1, sq0 = 0.f, sq1 = 0.f;
    {
      const uint32_t xb = cx.sb + SM_X + wg * 73728, xf = cx.sb + SM_XFULL + wg * 96;
      const uint32_t lo = ((cw & 3) * 16 + (lane & 15)) * 128 + (((lane >> 4) ^ (lane & 7)) << 4);
      float sm[4][4] = {};
      prof(wg, 0);
      empty_c = mapa(cx.sb + SM_EMPTY, cw & 1);
      mbar_wait(xf, 0);
      if ((threadIdx.x & 127) == 0) profc(wg, 30);
      ln_fetch<0, 12>(xa, xb, lo);
      mbar_wait(xf + 8, 0);
      ln_fetch<12, 24>(xa, xb, lo);
      ln_sums<0, 12>(xa, sm);
      mbar_wait(xf + 16, 0);
      if ((threadIdx.x & 127) == 0) profc(wg, 1);
      ln_fetch<24, 36>(xa, xb, lo);
      ln_sums<12, 36>(xa, sm);
      rstd0 = ((sm[0][0] + sm[1][0]) + (sm[2][0] + sm[3][0])) * (1.0f / DM);
      rstd1 = ((sm[0][2] + sm[1][2]) + (sm[2][2] + sm[3][2])) * (1.0f / DM);
    }
    asm volatile("" : "+f"(rstd0), "+f"(rstd1)::"memory");
    if (wg) {
      bar_arrive(other_turn, 256);
    } else {
      bar_sync(4, 128);
      if (signaller) {
        asm volatile("mbarrier.arrive.shared::cluster.b64 _, [%0], 2;" ::"r"(empty_c + 16) : "memory");
        asm volatile("mbarrier.arrive.shared::cluster.b64 _, [%0], 2;" ::"r"(empty_c + 24) : "memory");
      }
    }
    const uint32_t mm0 = pack2(rstd0, rstd0), mm1 = pack2(rstd1, rstd1);
    ln_centre(xa, 0, X_C0, mm0, mm1, sq0, sq1);
    pin(xa);
    if ((threadIdx.x & 127) == 0) profc(wg, 2);

    float acc[64];
#pragma unroll 1
    for (int p = 0; p < 4; p++) {
      const int st0 = p * 5;
#pragma unroll
      for (int i = 0; i < 5; i++) {
        const int st = st0 + i;
        const uint32_t sl = st & 3;
        mbar_wait(full + 8 * sl, (st >> 2) & 1);
        if (st == 0 && (threadIdx.x & 127) == 0) profc(wg, 31);
        if (i != (wg ? 4 : 1)) bar_sync(my_turn, 256);
        wg_fence();
        const uint64_t db = mkdesc(ring + sl * STAGE, 16384);
        const int kb0 = i < 3 ? 8 * i : 8 * i - 4;
#pragma unroll
        for (int k = 0; k < (i == 2 ? 4 : 8); k++) {
          const int kb = kb0 + k;
          mma_n128<1>(acc, xa[4 * kb], xa[4 * kb + 1], xa[4 * kb + 2], xa[4 * kb + 3], db + k * 128, kb > 0);
        }
        wg_commit();
        if (i != (wg ? 3 : 0)) bar_arrive(other_turn, 256);
        if (p == 0 && (i == 1 || i == 2)) {
          ln_centre(xa, i == 1 ? X_C0 : X_C1, i == 1 ? X_C1 : 72, mm0, mm1, sq0, sq1);
          if (i == 2) {
            sq0 += __shfl_xor_sync(0xffffffffu, sq0, 1); sq1 += __shfl_xor_sync(0xffffffffu, sq1, 1);
            sq0 += __shfl_xor_sync(0xffffffffu, sq0, 2); sq1 += __shfl_xor_sync(0xffffffffu, sq1, 2);
            rstd0 = ln_rstd(sq0 * (1.0f / DM), rstd0 - bf_lo(mm0));
            rstd1 = ln_rstd(sq1 * (1.0f / DM), rstd1 - bf_lo(mm1));
            if (c == 0) {
              *(float2*)(cx.sp + SM_STATS + 8 * lr0) = make_float2(bf_lo(mm0), rstd0);
              *(float2*)(cx.sp + SM_STATS + 8 * (lr0 + 8)) = make_float2(bf_lo(mm1), rstd1);
            }
            bar_arrive(BAR_GATE, 352);
            bar_sync(4 + wg, 128);
            rstd0 *= SM_SCALE_LOG2;
            rstd1 *= SM_SCALE_LOG2;
          }
          pin(xa);
        }
        if (i == 0) {
          if (wg) {
            wg_wait<0>();
            if (signaller) mbar_arrive_cluster(empty_c + 8 * sl);
          }
        } else if (i != 3) {
          if (i != 2) {
            wg_wait<1>();
            if (signaller && (i == 4 || !wg)) mbar_arrive_cluster(empty_c + 8 * ((st - 1) & 3));
          }
          wg_wait<0>();
          if (signaller) mbar_arrive_cluster(empty_c + 8 * sl);
        }
      }
      pin(acc);
      prof(wg, 3 + p);
      if (p < 3) {
#pragma unroll
        for (int i = 0; i < 8; i++)
          sts128(slot + p * STAGE + i * 2048, pack2(acc[8 * i] * rstd0, acc[8 * i + 1] * rstd0), pack2(acc[8 * i + 2] * rstd1, acc[8 * i + 3] * rstd1),
                 pack2(acc[8 * i + 4] * rstd0, acc[8 * i + 5] * rstd0), pack2(acc[8 * i + 6] * rstd1, acc[8 * i + 7] * rstd1));
      }
    }
#pragma unroll
    for (int i = 0; i < 16; i++) {
      q[2 * i] = pack2(acc[4 * i] * rstd0, acc[4 * i + 1] * rstd0);
      q[2 * i + 1] = pack2(acc[4 * i + 2] * rstd1, acc[4 * i + 3] * rstd1);
    }
  }

  uint32_t pf[32], oa[96];
  {
    float s[64], o[64];
    float n0, n1, l0 = 0.f, l1 = 0.f;
#pragma unroll
    for (int i = 0; i < 64; i++) o[i] = 0.f;
    float lp0, lp1;
    float i0 = 0.f, i1 = 0.f;
    bool redo, shift;
    auto turn = [&](int it, auto kc_) -> bool {
      constexpr int KIND = decltype(kc_)::value;
      constexpr uint32_t slk = KIND == 0 ? 0 : (KIND == 1 ? 1 : 3), slv = KIND == 1 ? 2 : 0, slkn = KIND == 1 ? 3 : 1;
      constexpr int SPLIT = 44, PARK1 = 5;
      const uint32_t par = ((it + 10) >> 1) & 1;
      if (KIND == 3) {
#pragma unroll
        for (int i = 0; i < 8; i++) lds128(slot + ((it >> 4) - 1) * STAGE + i * 2048, q[4 * i], q[4 * i + 1], q[4 * i + 2], q[4 * i + 3]);
      }
      const uint64_t dk = mkdesc(ring + slk * STAGE, 16), dv = mkdesc(ring + slv * STAGE, 16384);
      auto qk = [&]() {
#pragma unroll
        for (int k = 0; k < 8; k++)
          mma_n128<0>(s, q[4 * k], q[4 * k + 1], q[4 * k + 2], q[4 * k + 3], dk + (k >> 2) * 1024 + (k & 3) * 2, k > 0);
        wg_commit();
      };
      auto pv = [&]() {
#pragma unroll
        for (int k = 0; k < 8; k++)
          mma_n128<1>(o, pf[4 * k], pf[4 * k + 1], pf[4 * k + 2], pf[4 * k + 3], dv + k * 128, k > 0 || KIND != 1 || (it & 15) != 1);
        wg_commit();
      };
      lp0 = l0; lp1 = l1;
      {
        bar_sync(my_turn, 256);
        pin(q); pin(pf); pin(o);
        wg_fence();
        qk();
        if (KIND == 1 && (it & 15) == 1 && it > 1) {
#pragma unroll
          for (int i = PARK1; i < 8; i++)
            sts128(slot + ((it >> 4) - 1) * STAGE + i * 2048, pack2(o[8 * i] * i0, o[8 * i + 1] * i0), pack2(o[8 * i + 2] * i1, o[8 * i + 3] * i1),
                   pack2(o[8 * i + 4] * i0, o[8 * i + 5] * i0), pack2(o[8 * i + 6] * i1, o[8 * i + 7] * i1));
          wg_fence();
        }
        if (KIND) {
          mbar_wait(full + 8 * slv, par);
          pv();
        }
        bar_arrive(other_turn, 256);
        if (KIND == 3) {
          const float t0 = lp0 + __shfl_xor_sync(0xffffffffu, lp0, 1), t1 = lp1 + __shfl_xor_sync(0xffffffffu, lp1, 1);
          i0 = rcp(t0 + __shfl_xor_sync(0xffffffffu, t0, 2));
          i1 = rcp(t1 + __shfl_xor_sync(0xffffffffu, t1, 2));
        }
        if (KIND) wg_wait<1>(); else wg_wait<0>();
      }
      pin(s);
      mbar_arrive_cluster_now<10 * KIND + 3>(empty_c + 8 * slk, signaller);
      if (KIND == 0 || KIND == 3) {
        shift = false;
        n0 = n1 = l0 = l1 = 0.f;
      } else if (shift) {
        softmax_shift(s, n0, n1);
        pin(s);
      }
      softmax_exp<0, SPLIT>(s);
      if (KIND) {
        pin(s);
        block_fence(10 * KIND + 4);
        wg_wait<0>();
        pin(o); pin(pf);
        mbar_arrive_cluster_now<10 * KIND + 5>(empty_c + 8 * slv, signaller);
      }
      const bool kready = mbar_test(full + 8 * slkn, par);
      softmax_exp<SPLIT, 64>(s);
#pragma unroll
      for (int i = 0; i < 32; i++) pf[i] = pack2(s[2 * i], s[2 * i + 1]);
      row_sums(pf, l0, l1);
      if (KIND == 3) {
#pragma unroll
        for (int i = 0; i < PARK1; i++)
          sts128(slot + ((it >> 4) - 1) * STAGE + i * 2048, pack2(o[8 * i] * i0, o[8 * i + 1] * i0), pack2(o[8 * i + 2] * i1, o[8 * i + 3] * i1),
                 pack2(o[8 * i + 4] * i0, o[8 * i + 5] * i0), pack2(o[8 * i + 6] * i1, o[8 * i + 7] * i1));
        prof(wg, 6 + (it >> 4));
        if (it == 48 && cw == 0) bar_arrive(BAR_HELPER, 128);
      }
      redo = !(l0 + l1 <= SUM_HI) || ((KIND == 0 || KIND == 3) && fminf(l0, l1) < SUM_LO);
      const bool leave = __any_sync(0xffffffffu, redo || !kready);
      return leave;
    };
    int it = 0;
    mbar_wait(full, (NST_Q >> 2) & 1);
    bool slow = turn(0, IC<0>());
#pragma unroll 1
    while (true) {
      if (!slow) {
        it++;
#pragma unroll 1
        while (true) {
          if (it & 1) {
            if (turn(it, IC<1>()) || it == 63) break;
            it++;
          }
          if (it & 15) {
            if (turn(it, IC<2>())) break;
          } else {
            if (turn(it, IC<3>())) break;
          }
          it++;
        }
      }
      if (__any_sync(0xffffffffu, redo)) {
        const int j = it & 15;
        float sc0, sc1;
        if (__all_sync(0xffffffffu, l0 + l1 < 3.0e38f && (j || fminf(l0, l1) >= SUM_LO))) {
          softmax_rebase(s, n0, n1, sc0, sc1);
        } else {
          if (j == 0) n0 = n1 = 3.0e38f;
          softmax_redo(s, q, kc + (size_t)((hs * 2 + (it >> 5)) * SEQ + j * 128) * DH, lane, n0, n1, sc0, sc1);
        }
        l0 = j ? lp0 * sc0 : 0.f;
        l1 = j ? lp1 * sc1 : 0.f;
        shift = true;
        if (j == 0) sc0 = sc1 = 1.f;
#pragma unroll
        for (int i = 0; i < 16; i++) { o[4 * i] *= sc0; o[4 * i + 1] *= sc0; o[4 * i + 2] *= sc1; o[4 * i + 3] *= sc1; }
#pragma unroll
        for (int i = 0; i < 32; i++) pf[i] = pack2(s[2 * i], s[2 * i + 1]);
        row_sums(pf, l0, l1);
      }
      if (it == 63) break;
      mbar_wait(full + 8 * ((it & 1) ? 3 : 1), ((it + 10) >> 1) & 1);
      slow = false;
    }
    {
      const int st = NST_Q + NST_KV - 1;
      const uint32_t sl = st & 3;
      mbar_wait(full + 8 * sl, (st >> 2) & 1);
      bar_sync(my_turn, 256);
      pin(pf); pin(o);
      wg_fence();
      const uint64_t dv = mkdesc(ring + sl * STAGE, 16384);
#pragma unroll
      for (int k = 0; k < 8; k++) mma_n128<1>(o, pf[4 * k], pf[4 * k + 1], pf[4 * k + 2], pf[4 * k + 3], dv + k * 128, 1);
      wg_commit();
      bar_arrive(other_turn, 256);
      l0 += __shfl_xor_sync(0xffffffffu, l0, 1); l1 += __shfl_xor_sync(0xffffffffu, l1, 1);
      l0 += __shfl_xor_sync(0xffffffffu, l0, 2); l1 += __shfl_xor_sync(0xffffffffu, l1, 2);
      float f0 = fmaxf(rcp(l0), 0.f), f1 = fmaxf(rcp(l1), 0.f);
      asm volatile("" : "+f"(f0), "+f"(f1)::"memory");
      block_fence(61);
#pragma unroll
      for (int i = 0; i < 16; i++) lds128(slot + (i >> 3) * STAGE + (i & 7) * 2048, oa[4 * i], oa[4 * i + 1], oa[4 * i + 2], oa[4 * i + 3]);
      mbar_wait(cx.sb + SM_BAR_MISC, 0);
      mbar_wait(full + 8 * ((st + 1) & 3), ((st + 1) >> 2) & 1);
      wg_wait<0>();
      pin(o); pin(pf);
      if (signaller) mbar_arrive_cluster(empty_c + 8 * sl);
#pragma unroll
      for (int i = 0; i < 16; i++) {
        pf[2 * i] = pack2(o[4 * i] * f0, o[4 * i + 1] * f0);
        pf[2 * i + 1] = pack2(o[4 * i + 2] * f1, o[4 * i + 3] * f1);
      }
    }
  }

  prof(wg, 10);
  {
    float acc[32], red[32];
#pragma unroll
    for (int i = 0; i < 32; i++) red[i] = 0.f;
    const uint32_t tag = *(const uint32_t*)(cx.sp + SM_TAG);
    uint4* const xch = cx.gs->part + (size_t)(qb * 64 * 2 + wg) * 4 * 128 + tw;
    int nrx = 1;
    auto half_step = [&](int s, auto hc, bool arrive) {
      constexpr int h = decltype(hc)::value;
      const int st = NST_Q + NST_KV + 2 * s + h;
      const uint64_t db = mkdesc(ring + (st & 3) * STAGE, 16);
      bar_sync(my_turn, 256);
      if (h == 0) {
        pin(pf);
#pragma unroll
        for (int i = 0; i < 32; i++) asm volatile("" : "+r"(oa[i])::"memory");
      } else {
        pin(oa);
      }
      wg_fence();
#pragma unroll
      for (int k = 0; k < 16; k++) {
        const int kb = h * 16 + k - 8;
        if (kb >= 0) mma_n64t(acc, oa[4 * kb], oa[4 * kb + 1], oa[4 * kb + 2], oa[4 * kb + 3], db + k * 128, 1);
        else mma_n64t(acc, pf[4 * k], pf[4 * k + 1], pf[4 * k + 2], pf[4 * k + 3], db + k * 128, k > 0);
      }
      wg_commit();
      if (arrive) bar_arrive(other_turn, 256);
    };
    auto await = [&](int st) { mbar_wait(full + 8 * (st & 3), (st >> 2) & 1); };
    auto fetch = [&](uint32_t (&g)[16], int n) {
      const uint4* p = xch + (hs * 7 + n - 1) * (2 * 4 * 128);
#pragma unroll
      for (int i = 0; i < 4; i++) ld_gran(p + i * 128, g[4 * i], g[4 * i + 1], g[4 * i + 2], g[4 * i + 3]);
    };
    uint32_t g[16];
    bool pend = false;
#pragma unroll 1
    for (int s = 0; s < 8; s++) {
      const int st = NST_Q + NST_KV + 2 * s;
      half_step(s, IC<0>(), true);
      if (s == 0) {
#pragma unroll
        for (int i = 16; i < 24; i++) lds128(slot + 2 * STAGE + (i & 7) * 2048, oa[4 * i], oa[4 * i + 1], oa[4 * i + 2], oa[4 * i + 3]);
      }
      await(st + 1);
      if (pend && granules_ok(g, tag)) { add_granules(red, g); nrx++; }
      wg_wait<0>();
      if (signaller && s < 7) mbar_arrive_cluster(empty_c + 8 * (st & 3));
      pend = nrx < s - 1;
      if (pend) fetch(g, nrx);
      half_step(s, IC<1>(), true);
      if (s == 0) bar_arrive(BAR_OA, 352);
      await(st + 2);
      wg_wait<0>();
      if (signaller && s < 7) mbar_arrive_cluster(empty_c + 8 * (st & 3) + 8);
      pin(acc);
      prof(wg, 12 + s);
      uint4* p = xch + (s == 0 ? 56 + hs : ((hs + s) & 7) * 7 + s - 1) * (2 * 4 * 128);
#pragma unroll
      for (int i = 0; i < 4; i++)
        st_gran(p + i * 128, (pack2(acc[8 * i], acc[8 * i + 1]) & ~1u) | tag, pack2(acc[8 * i + 2], acc[8 * i + 3]),
                pack2(acc[8 * i + 4], acc[8 * i + 5]), pack2(acc[8 * i + 6], acc[8 * i + 7]));
    }
    float gf[32], xf[32];
    {
      const int s = 8;
      uint32_t g2[16], xv[16], gt[16];
      half_step(s, IC<0>(), true);
      if (pend && granules_ok(g, tag)) { add_granules(red, g); nrx++; }
      await(NST_Q + NST_KV + NST_O - 1);
      mbar_wait(cx.sb + SM_BAR_XG, 0);
      wg_wait<0>();
      fetch(g, nrx);
#pragma unroll
      for (int i = 0; i < 16; i++) {
        const uint8_t* p = cx.sp + (lr0 + (i & 1) * 8) * 144 + (i >> 1) * 16 + c * 4;
        xv[i] = *(const uint32_t*)(p + SM_XO);
        gt[i] = *(const uint32_t*)(p + SM_GO);
      }
      half_step(s, IC<1>(), wg == 0);
      fetch(g2, 7);
      int last = 8;
      const bool two = nrx < 7;
      if (granules_ok(g, tag)) { add_granules(red, g); nrx++; }
#pragma unroll
      for (int i = 0; i < 16; i++) {
        gf[2 * i] = bf_lo(gt[i]); gf[2 * i + 1] = bf_hi(gt[i]);
        xf[2 * i] = bf_lo(xv[i]); xf[2 * i + 1] = bf_hi(xv[i]);
      }
      wg_wait<0>();
      pin(acc);
#pragma unroll
      for (int i = 0; i < 32; i++) red[i] += acc[i];
      pin(red); pin(gf); pin(xf);
      block_fence(60);
      if (two && granules_ok(g2, tag)) { add_granules(red, g2); last = 7; }
#pragma unroll 1
      for (int spins = 0; nrx < last && spins < (1 << 16); spins++) {
        fetch(g, nrx);
        if (granules_ok(g, tag)) { add_granules(red, g); nrx++; }
      }
    }
    prof(wg, 20);
    const uint32_t ot = ring + 2 * STAGE + cw * (16 * 144);
    uint32_t ow[16];
#pragma unroll
    for (int i = 0; i < 16; i++) ow[i] = pack2(fmaf(red[2 * i], gf[2 * i], xf[2 * i]), fmaf(red[2 * i + 1], gf[2 * i + 1], xf[2 * i + 1]));
#pragma unroll
    for (int i = 0; i < 4; i++)
      stsm4(ot + (lane & 15) * 144 + (2 * i + (lane >> 4)) * 16, ow[4 * i], ow[4 * i + 1], ow[4 * i + 2], ow[4 * i + 3]);
    __syncwarp();
#pragma unroll
    for (int i = 0; i < 4; i++) {
      uint4 v;
      lds128(ot + (i * 4 + (lane >> 3)) * 144 + (lane & 7) * 16, v.x, v.y, v.z, v.w);
      at<uint4>(out, ((qb * 128 + cw * 16 + (lane >> 3)) * DM + hs * 64 + (lane & 7) * 8) * 2)[i * (4 * DM / 8)] = v;
    }
    prof(wg, 22);
  }
}

constexpr int FST_X = 24, FST_END = FST_X + 14 * 12;
__device__ __forceinline__ void ffn_producer(const Ctx& cx, int f, const CUtensorMap* tmX, const CUtensorMap* tmG,
                                             const CUtensorMap* tmU, const CUtensorMap* tmD) {
  const uint32_t full = cx.sb + SM_FULL, empty = cx.sb + SM_EMPTY;
  int pair = -2, u = 0;
#pragma unroll 1
  for (int st = 0; st < FST_END; st++) {
    const uint32_t sl = st & 7;
    const int unit = pair * 2 + (u & 1), k = u >> 1, k3 = k >= 3 ? k - 3 : k;
    if (unit < 27) {
      mbar_wait(empty + 8 * sl, ((st >> 3) & 1) ^ 1);
      mbar_expect_tx(full + 8 * sl, FSTAGE);
      if (pair < 0) tma3d(cx.sb + sl * FSTAGE, tmX, f * 512 + ((pair + 2) * 4 + (k >= 3) * 2 + (u & 1)) * 64, k3 * 3, full + 8 * sl);
      else if (pair < 9) tma2d_stream(cx.sb + sl * FSTAGE, k < 3 ? tmG : tmU, f * 1152 + unit * 64, k3 * 192, full + 8 * sl);
      else tma2d_stream(cx.sb + sl * FSTAGE, tmD, (unit - 18) * 64, f * 1152 + k * 192, full + 8 * sl);
    }
    if (++u == 12) { u = 0; pair++; }
  }
}

__device__ __forceinline__ void ffn_consumer(const Ctx& cx, int f, int wg, int cw, int lane, const __nv_bfloat16* x,
                                             const __nv_bfloat16* w_r) {
  const int r = lane >> 2, c = lane & 3, tid = cw * 32 + lane;
  unsigned e = 0;
  if (tid == 0) {
    e = cx.gs->launch[blockIdx.x];
    cx.gs->launch[blockIdx.x] = e + 1;
    *(unsigned*)(cx.sp + SM_TAG) = e;
  }
  if (tid < 72) *(uint4*)(cx.sp + SM_H + tid * 16) = *(const uint4*)(w_r + tid * 8);
  bar_sync(3, 256);
  prof(wg, 0);
  const uint32_t full = cx.sb + SM_FULL, empty = cx.sb + SM_EMPTY;
  const bool signaller = (tid & 127) == 0;
#pragma unroll 1
  for (int b = wg; b < 8; b += 2) {
    const int row0 = f * 512 + b * 64 + (cw & 3) * 16 + r;
    const uint32_t lo = ((cw & 3) * 16 + (lane & 15)) * 128 + (((lane >> 4) ^ (lane & 7)) << 4);
    LnAcc a;
    a.clear();
#pragma unroll 1
    for (int bx = 0; bx < 9; bx++) {
      const int st = (b >> 1) * 6 + (bx / 3) * 2 + wg;
      if (bx % 3 == 0) mbar_wait(full + 8 * (st & 7), (st >> 3) & 1);
#pragma unroll
      for (int k = 0; k < 4; k++) {
        uint32_t x0, x1, x2, x3;
        ldsm4(cx.sb + (st & 7) * FSTAGE + (bx % 3) * 8192 + (lo ^ (k << 5)), x0, x1, x2, x3);
        ln_accum1(a, k & 1, x0, x1, x2, x3);
      }
    }
    prof(wg, 8 + (b >> 1) * 3);
    float mean0, rstd0, mean1, rstd1;
    ln_stats(a, lane, mean0, rstd0, mean1, rstd1);
    prof(wg, 9 + (b >> 1) * 3);
    const uint32_t mm0 = pack2(mean0, mean0), mm1 = pack2(mean1, mean1);
    float d0[4] = {0, 0, 0, 0}, d1[4] = {0, 0, 0, 0};
#pragma unroll 1
    for (int bx = 0; bx < 9; bx++) {
      const int st = (b >> 1) * 6 + (bx / 3) * 2 + wg;
#pragma unroll
      for (int k = 0; k < 4; k++) {
        uint32_t n[4];
        ldsm4(cx.sb + (st & 7) * FSTAGE + (bx % 3) * 8192 + (lo ^ (k << 5)), n[0], n[1], n[2], n[3]);
        const uint8_t* wp = cx.sp + SM_H + (bx * 4 + k) * 32 + 4 * c;
#pragma unroll
        for (int i = 0; i < 4; i++) {
          const uint32_t t = sub2(n[i], (i & 1) ? mm1 : mm0);
          const float rs = (i & 1) ? rstd1 : rstd0;
          n[i] = pack2(bf_lo(t) * rs, bf_hi(t) * rs);
        }
        if (k & 1) hmma_k16(d1, n[0], n[1], n[2], n[3], *(const uint32_t*)wp, *(const uint32_t*)(wp + 16));
        else hmma_k16(d0, n[0], n[1], n[2], n[3], *(const uint32_t*)wp, *(const uint32_t*)(wp + 16));
      }
    }
    prof(wg, 10 + (b >> 1) * 3);
    bar_sync(4 + wg, 128);
    if (signaller) {
#pragma unroll
      for (int i = 0; i < 3; i++) mbar_arrive(empty + 8 * (((b >> 1) * 6 + i * 2 + wg) & 7));
    }
    if (c == 0) {
      cx.gs->r[row0] = bfr(d0[0] + d1[0]);
      cx.gs->r[row0 + 8] = bfr(d0[2] + d1[2]);
      cx.gs->stats[row0] = make_float2(mean0, rstd0);
      cx.gs->stats[row0 + 8] = make_float2(mean1, rstd1);
    }
  }
  prof(wg, 1);
  bar_sync(3, 256);
  e = *(const unsigned*)(cx.sp + SM_TAG);
  if (tid == 0) {
    atom_add_acq_rel(&cx.gs->rcnt);
#pragma unroll 1
    for (int n = 0; n < (1 << 16) && (int)(ld_acquire(&cx.gs->rcnt) - 4 * (e + 1)) < 0; n++) {}
  }
  bar_sync(3, 256);
  prof(wg, 2);
  uint32_t key[8];
#pragma unroll
  for (int i = 0; i < 8; i++) {
    const int row = i * 256 + tid;
    const uint32_t b = __float_as_uint(__ldcg(&cx.gs->r[row])) >> 16;
    key[i] = (((b & 0x8000u) ? (~b & 0xFFFFu) : (b | 0x8000u)) << 16) | (uint32_t)(0xFFFF - row);
  }
  int mysel = 0;
#pragma unroll 1
  for (int k = 0; k < TOPC; k++) {
    uint32_t m = key[0];
#pragma unroll
    for (int i = 1; i < 8; i++) m = max(m, key[i]);
    m = __reduce_max_sync(0xffffffffu, m);
    uint32_t* tk = (uint32_t*)(cx.sp + SM_TOPK) + (k & 1) * 8;
    if (lane == 0) tk[cw] = m;
    bar_sync(3, 256);
    m = __reduce_max_sync(0xffffffffu, tk[lane & 7]);
#pragma unroll
    for (int i = 0; i < 8; i++) if (key[i] == m) key[i] = 0;
    if (k == cw) mysel = 0xFFFF - (int)(m & 0xFFFF);
  }
  {
    const float2 st = __ldcg(&cx.gs->stats[mysel]);
    const uint32_t mm = pack2(st.x, st.x);
#pragma unroll 3
    for (int i = 0; i < 9; i++) {
      const uint32_t t = sub2(*(const uint32_t*)(x + (size_t)mysel * DM + i * 64 + 2 * lane), mm);
      *(uint32_t*)(cx.sp + SM_XSEL + i * 1024 + cw * 128 + (((lane >> 2) ^ cw) << 4) + (lane & 3) * 4) =
          pack2(bf_lo(t) * st.y, bf_hi(t) * st.y);
    }
    if (lane == 0) *(int*)(cx.sp + SM_IDX + 4 * cw) = mysel;
  }
  asm volatile("fence.proxy.async.shared::cta;" ::: "memory");
  bar_sync(3, 256);
  prof(wg, 3);
  auto run = [&](float (&acc)[4], int st, int n, uint32_t b) {
#pragma unroll 1
    for (int u = 0; u < n; u++, st += 2, b += 3072) {
      const uint32_t sl = st & 7;
      mbar_wait(full + 8 * sl, (st >> 3) & 1);
      wg_fence();
      const uint64_t da = mkdesc(cx.sb + sl * FSTAGE, 16), db = mkdesc(b, 16);
#pragma unroll
      for (int k = 0; k < 12; k++) mma_n8(acc, da + k * 128, db + (k >> 2) * 64 + (k & 3) * 2, u > 0 || k > 0);
      wg_commit();
      wg_wait<0>();
      if (signaller) mbar_arrive(empty + 8 * sl);
    }
    pin(acc);
  };
#pragma unroll 1
  for (int unit = wg; unit < 27; unit += 2) {
    if (unit >> 1 == 9) {
      asm volatile("fence.proxy.async.shared::cta;" ::: "memory");
      bar_sync(3, 256);
      prof(wg, 4);
    }
    const bool gu = unit < 18;
    float a0[4], a1[4];
#pragma unroll 1
    for (int m = 0; m < (gu ? 2 : 1); m++) {
      run(a1, FST_X + (unit >> 1) * 12 + m * 6 + wg, gu ? 3 : 6, cx.sb + (gu ? SM_XSEL : SM_H));
      if (m == 0) { a0[0] = a1[0]; a0[1] = a1[1]; a0[2] = a1[2]; a0[3] = a1[3]; }
    }
#pragma unroll
    for (int i = 0; i < 4; i++) {
      const int fl = (cw & 3) * 16 + r + (i >> 1) * 8, tok = 2 * c + (i & 1);
      if (gu) {
        const float h = bfr(silu_f(bfr(a0[i]))) * bfr(a1[i]);
        *(__nv_bfloat16*)(cx.sp + SM_H + unit * 1024 + tok * 128 + (((fl >> 3) ^ tok) << 4) + (fl & 7) * 2) = __float2bfloat16_rn(h);
      } else {
        cx.gs->ypart[(f * TOPC + tok) * DM + (unit - 18) * 64 + fl] = a1[i];
      }
    }
  }
  prof(wg, 5);
  bar_sync(3, 256);
  if (tid == 0) *(unsigned*)(cx.sp + SM_TOPK) = atom_add_acq_rel(&cx.gs->ycnt) == 4 * e + 3;
  bar_sync(3, 256);
  if (*(const unsigned*)(cx.sp + SM_TOPK)) {
    const int row = *(const int*)(cx.sp + SM_IDX + 4 * cw);
    const float rs = bfr(rcp(1.0f + ex2(-1.4426950408889634f * __ldcg(&cx.gs->r[row]))));
#pragma unroll 1
    for (int d = lane * 2; d < DM; d += 192) {
#pragma unroll
      for (int i = 0; i < 3; i++) {
        const float* p = cx.gs->ypart + cw * DM + d + i * 64;
        const float2 a = __ldcg((const float2*)p), b = __ldcg((const float2*)(p + TOPC * DM)),
                     e2 = __ldcg((const float2*)(p + 2 * TOPC * DM)), h = __ldcg((const float2*)(p + 3 * TOPC * DM));
        const uint32_t y = pack2((a.x + b.x) + (e2.x + h.x), (a.y + b.y) + (e2.y + h.y));
        const uint32_t u = pack2(bf_lo(y) * rs, bf_hi(y) * rs);
        *(float2*)(cx.gs->upd + cw * DM + d + i * 64) = make_float2(bf_lo(u), bf_hi(u));
      }
    }
    if (lane == 0) cx.gs->idx[cw] = row;
    bar_sync(3, 256);
    if (tid == 0) st_release(&cx.gs->ffn_flag, e + 1);
    prof(wg, 6);
  }
}

struct Maps { CUtensorMap m[8]; };
__global__ void __cluster_dims__(2, 1, 1) __launch_bounds__(THREADS, 1)
fused_kernel(const __nv_bfloat16* __restrict__ x, const __nv_bfloat16* __restrict__ w_r, const __nv_bfloat16* __restrict__ wq,
             const __nv_bfloat16* __restrict__ wo, __nv_bfloat16* __restrict__ out, Scratch* gs,
             const __grid_constant__ Maps maps, const __nv_bfloat16* __restrict__ kc) {
  const CUtensorMap &tmX = maps.m[0], &tmWq = maps.m[1], &tmK = maps.m[2], &tmV = maps.m[3], &tmWo = maps.m[4], &tmG = maps.m[5],
                    &tmU = maps.m[6], &tmD = maps.m[7];
  extern __shared__ __align__(1024) uint8_t smem_raw[];
  prof(0, 23, 511);
  Ctx cx;
  cx.sb = smem_u32(smem_raw);
  cx.sp = smem_raw;
  cx.gs = gs;
  cx.rank = blockIdx.x & 1;
  const int warp = __shfl_sync(0xffffffffu, threadIdx.x >> 5, 0);
  const int cluster = blockIdx.x >> 1;
  const bool is_ffn = blockIdx.x >= N_ATT_CTA;
  const int c7 = ((cluster - 36) * 37) >> 8;
  const int hs = cluster < 4 ? 4 + cluster : cluster < 36 ? (cluster - 4) >> 3 : 4 + c7;
  const int qb = (cluster < 4 ? 0 : cluster < 36 ? (cluster - 4) & 7 : cluster - 35 - 7 * c7) * 2 + cx.rank;

  extern __shared__ __align__(1024) uint8_t smem_alias[];
  const uint32_t xf = smem_u32(smem_alias) + SM_MISC + warp * 24;
  if (warp == 4 && elect_one()) prefetch_tmap(&tmX);
  if (warp == 6 && !is_ffn && elect_one()) prefetch_l2(x + (size_t)(qb * 128 + hs * 8) * DM, 8 * DM * 2);
  if (elect_one()) {
    const uint32_t cnt = warp == 3 ? 64 : (warp > 4 && warp < 8 && !is_ffn) ? 4 : 1;
#pragma unroll
    for (int i = 0; i < 3; i++) mbar_init(xf + 8 * i, cnt);
    asm volatile("fence.proxy.async.shared::cta;" ::: "memory");
    asm volatile("fence.mbarrier_init.release.cluster;" ::: "memory");
  }
  __syncwarp();
  cluster_arrive();
  if (warp == 4 && !is_ffn) {
    if (elect_one()) {
      profc(0, 28);
#pragma unroll
      for (int i = 0; i < 3; i++) {
        mbar_expect_tx(xf + 8 * i, 24576);
        tma3d(xf - SM_XFULL + SM_X + i * 24576, &tmX, qb * 128, i * 3, xf + 8 * i);
      }
      profc(0, 29);
    }
  } else if (warp > 8 && elect_one()) {
    prefetch_tmap(&tmX + (is_ffn ? warp - 4 : warp - 8));
  }
  __syncwarp();

  if (warp < 4) {
    asm volatile("setmaxnreg.dec.sync.aligned.u32 24;");
    cluster_wait();
    prof(0, 24, 511);
    if (warp == 0) {
      if (elect_one()) {
        if (is_ffn) ffn_producer(cx, blockIdx.x - N_ATT_CTA, &tmX, &tmG, &tmU, &tmD);
        else attn_producer(cx, qb, hs, &tmX, &tmK, &tmV, &tmWq, &tmWo);
        prof(0, 25, 511);
      }
    } else if (!is_ffn) {
      attn_gate(cx, qb, hs, threadIdx.x - 32, x);
      if (warp == 1) attn_helper(cx, qb, hs, read_lane(), x, wo);
      else { bar_arrive(BAR_HELPER, 128); attn_stage_xg(cx, qb, hs, threadIdx.x - 64, x); }
      attn_finish8(cx, qb, hs, warp - 1, read_lane(), out);

    }
    __syncwarp();
    cluster_arrive();
    cluster_wait();
  } else {
    asm volatile("setmaxnreg.inc.sync.aligned.u32 240;");
    cluster_wait();
    const int cw = warp - 4, wg = cw >> 2;
    if (is_ffn) ffn_consumer(cx, blockIdx.x - N_ATT_CTA, wg, cw, read_lane(), x, w_r);
    else attn_consumer(cx, qb, hs, wg, cw, read_lane(), x, kc, out);
  }
}

typedef CUresult (*EncodeFn)(CUtensorMap*, CUtensorMapDataType, cuuint32_t, void*, const cuuint64_t*, const cuuint64_t*,
                             const cuuint32_t*, const cuuint32_t*, CUtensorMapInterleave, CUtensorMapSwizzle,
                             CUtensorMapL2promotion, CUtensorMapFloatOOBfill);

void encode(EncodeFn fn, CUtensorMap* m, const void* p, int rank, const cuuint64_t* dims, const cuuint64_t* strides,
            const cuuint32_t* box) {
  const cuuint32_t es[5] = {1, 1, 1, 1, 1};
  fn(m, CU_TENSOR_MAP_DATA_TYPE_BFLOAT16, rank, const_cast<void*>(p), dims, strides, box, es, CU_TENSOR_MAP_INTERLEAVE_NONE,
     CU_TENSOR_MAP_SWIZZLE_128B, CU_TENSOR_MAP_L2_PROMOTION_L2_128B, CU_TENSOR_MAP_FLOAT_OOB_FILL_NONE);
}
void encode2d(EncodeFn fn, CUtensorMap* m, const void* p, uint64_t rows, uint64_t cols, uint32_t box_rows) {
  const cuuint64_t dims[2] = {cols, rows}, strides[1] = {cols * 2};
  const cuuint32_t box[2] = {64, box_rows};
  encode(fn, m, p, 2, dims, strides, box);
}

}

extern "C" void kernel_launch(void* const* d_in, const int* in_sizes, int n_in, void* d_out, int out_size) {
  (void)in_sizes; (void)n_in; (void)out_size;
  void* fnp = nullptr;
  cudaDriverEntryPointQueryResult qr;
  cudaGetDriverEntryPoint("cuTensorMapEncodeTiled", &fnp, cudaEnableDefault, &qr);
  EncodeFn fn = (EncodeFn)fnp;
  Maps maps;
  CUtensorMap &tmX = maps.m[0], &tmWq = maps.m[1], &tmK = maps.m[2], &tmV = maps.m[3], &tmWo = maps.m[4], &tmG = maps.m[5],
              &tmU = maps.m[6], &tmD = maps.m[7];
  encode2d(fn, &tmK, d_in[1], 16 * SEQ, DH, 128);
  encode2d(fn, &tmV, d_in[2], 16 * SEQ, DH, 128);
  encode2d(fn, &tmWq, d_in[3], DM, 4096, 64);
  {
    const cuuint64_t dims[3] = {64, SEQ, 9}, strides[2] = {DM * 2, 128};
    const cuuint32_t box[3] = {64, 64, 3};
    encode(fn, &tmX, d_in[0], 3, dims, strides, box);
  }
  encode2d(fn, &tmWo, d_in[4], 4096, DM, 128);
  encode2d(fn, &tmG, d_in[7], DM, FF, 192);
  encode2d(fn, &tmU, d_in[8], DM, FF, 192);
  encode2d(fn, &tmD, d_in[9], FF, DM, 192);
  cudaFuncSetAttribute(fused_kernel, cudaFuncAttributeMaxDynamicSharedMemorySize, SM_TOTAL);
  void* gs = nullptr;
  cudaGetSymbolAddress(&gs, g_scratch);
  fused_kernel<<<N_CTA, THREADS, SM_TOTAL>>>((const __nv_bfloat16*)d_in[0], (const __nv_bfloat16*)d_in[6], (const __nv_bfloat16*)d_in[3],
                                            (const __nv_bfloat16*)d_in[4], (__nv_bfloat16*)d_out, (Scratch*)gs, maps, (const __nv_bfloat16*)d_in[1]);
}
```

```cpp
#include <cuda_runtime.h>
#include <cuda_bf16.h>
#include <cuda.h>
#include <stdint.h>

namespace {

constexpr int SEQ = 2048, DM = 576, DH = 128, FF = 4608, TOPC = 8;
constexpr int N_ATT_CTA = 128, N_CTA = 132;
constexpr int THREADS = 384;

constexpr uint32_t SM_RING = 0;
constexpr uint32_t STAGE = 32768;
constexpr uint32_t SM_SLOT = 131072;
constexpr uint32_t FSTAGE = 24576;
constexpr uint32_t SM_XSEL = 196608;
constexpr uint32_t SM_H = 205824;
constexpr uint32_t SM_MISC = 229376;
constexpr uint32_t SM_FULL = SM_MISC, SM_BAR_MISC = SM_MISC + 64, SM_BAR_XG = SM_MISC + 72, SM_XFULL = SM_MISC + 96,
                   SM_EMPTY = SM_MISC + 120, SM_TAG = SM_MISC + 288, SM_IDX = SM_MISC + 304, SM_TOPK = SM_MISC + 336,
                   SM_STATS = SM_MISC + 400;
constexpr uint32_t SM_TOTAL = SM_MISC + 1424;
constexpr uint32_t SM_X = SM_MISC - 147456;

constexpr int BAR_GATE = 6, BAR_HELPER = 7, BAR_OA = 8;
constexpr int NST_Q = 20, NST_KV = 128, NST_O = 18;
#define X_ORDER 0
#define X_PF 3
#define X_PFQ 2
#define X_REL 0
#define X_N1 4
#define X_SPLIT 44
#define X_PARK 6
#define X_HO 9
#define X_C0 32
#define X_C1 56
constexpr float SM_SCALE_LOG2 = 0.08838834764831845f * 1.4426950408889634f;

struct Scratch {
  uint4 part[16 * 64 * 2 * 4 * 128];
  uint4 gate[SEQ * DM / 8];
  float r[SEQ];
  float2 stats[SEQ];
  float ypart[4 * TOPC * DM];
  float upd[TOPC * DM];
  int idx[32];
  unsigned launch[160];
  unsigned rcnt, pad0[31], ycnt, pad1[31], ffn_flag, pad2[31];
};
__device__ __align__(1024) Scratch g_scratch;

__device__ __forceinline__ void profq(int) {}
__device__ __forceinline__ void prof(int, int, int = 0) {}
__device__ __forceinline__ void profc(int, int) {}

__device__ __forceinline__ uint32_t smem_u32(const void* p) { return (uint32_t)__cvta_generic_to_shared(p); }
__device__ __forceinline__ void mbar_init(uint32_t bar, uint32_t cnt) {
  asm volatile("mbarrier.init.shared::cta.b64 [%0], %1;" ::"r"(bar), "r"(cnt) : "memory");
}
__device__ __forceinline__ void mbar_expect_tx(uint32_t bar, uint32_t bytes) {
  asm volatile("mbarrier.arrive.expect_tx.shared::cta.b64 _, [%0], %1;" ::"r"(bar), "r"(bytes) : "memory");
}
__device__ __forceinline__ void mbar_arrive(uint32_t bar) {
  asm volatile("mbarrier.arrive.shared::cta.b64 _, [%0];" ::"r"(bar) : "memory");
}
__device__ __forceinline__ void mbar_arrive_cluster(uint32_t bar_cluster_addr) {
  asm volatile("mbarrier.arrive.shared::cluster.b64 _, [%0];" ::"r"(bar_cluster_addr) : "memory");
}
template <int ID>
__device__ __forceinline__ void mbar_arrive_cluster_now(uint32_t bar_cluster_addr, bool pred, uint32_t zero) {
  asm volatile("{\n.reg .pred p, q;\nsetp.ne.u32 p, %1, 0;\nsetp.eq.u32 q, %2, %3;\n"
               "ARR_LOOP:\n@p mbarrier.arrive.shared::cluster.b64 _, [%0];\n@q bra.uni ARR_LOOP;\n}"
               ::"r"(bar_cluster_addr), "r"((uint32_t)pred), "r"(zero), "n"(ID) : "memory");
}
__device__ __forceinline__ void block_fence(int id, uint32_t zero = blockIdx.y) {
  asm volatile("{\n.reg .pred q;\nsetp.eq.u32 q, %0, %1;\nBF_LOOP:\n@q st.volatile.shared.u32 [%0], %0;\n@q bra.uni BF_LOOP;\n}"
               ::"r"(zero), "r"(id) : "memory");
}
__device__ __forceinline__ bool mbar_test(uint32_t bar, uint32_t parity) {
  uint32_t ok;
  asm volatile("{\n.reg .pred p;\nmbarrier.test_wait.parity.shared::cta.b64 p, [%1], %2;\nselp.u32 %0, 1, 0, p;\n}"
               : "=r"(ok) : "r"(bar), "r"(parity) : "memory");
  return ok;
}
__device__ __forceinline__ void mbar_wait(uint32_t bar, uint32_t parity) {
  asm volatile("{\n.reg .pred p, q;\n.reg .u32 n;\nmov.u32 n, 0;\n"
               "WAIT_LOOP:\nmbarrier.try_wait.parity.shared::cta.b64 p, [%0], %1;\n"
               "add.u32 n, n, 1;\nsetp.lt.u32 q, n, 4194304;\nand.pred q, q, !p;\n@q bra WAIT_LOOP;\n}"
               ::"r"(bar), "r"(parity) : "memory");
}
__device__ __forceinline__ uint32_t mapa(uint32_t addr, uint32_t rank) {
  uint32_t r;
  asm volatile("mapa.shared::cluster.u32 %0, %1, %2;" : "=r"(r) : "r"(addr), "r"(rank));
  return r;
}
__device__ __forceinline__ void cluster_arrive() { asm volatile("barrier.cluster.arrive.relaxed.aligned;" ::: "memory"); }
__device__ __forceinline__ bool elect_one() {
  uint32_t p;
  asm volatile("{\n.reg .pred p;\nelect.sync _|p, 0xffffffff;\nselp.u32 %0, 1, 0, p;\n}" : "=r"(p));
  return p;
}
__device__ __forceinline__ int read_lane() { return threadIdx.x & 31; }
__device__ __forceinline__ void cluster_wait() { asm volatile("barrier.cluster.wait.acquire.aligned;" ::: "memory"); }
__device__ __forceinline__ void bar_sync(int id, int n) { asm volatile("barrier.cta.sync %0, %1;" ::"r"(id), "r"(n) : "memory"); }
__device__ __forceinline__ void bar_arrive(int id, int n) { asm volatile("barrier.cta.arrive %0, %1;" ::"r"(id), "r"(n) : "memory"); }

__device__ __forceinline__ uint64_t policy_evict_first() {
  uint64_t p;
  asm("createpolicy.fractional.L2::evict_first.b64 %0, 1.0;" : "=l"(p));
  return p;
}
__device__ __forceinline__ uint64_t policy_evict_normal() {
  uint64_t p;
  asm("createpolicy.fractional.L2::evict_normal.b64 %0, 1.0;" : "=l"(p));
  return p;
}
__device__ __forceinline__ void tma2d_mc(uint32_t dst, const CUtensorMap* tm, int c0, int c1, uint32_t bar, uint64_t pol) {
  asm volatile("cp.async.bulk.tensor.2d.shared::cluster.global.mbarrier::complete_tx::bytes.multicast::cluster.L2::cache_hint"
               " [%0], [%1, {%2, %3}], [%4], %5, %6;"
               ::"r"(dst), "l"(tm), "r"(c0), "r"(c1), "r"(bar), "h"((uint16_t)3), "l"(pol) : "memory");
}
__device__ __forceinline__ void tma3d(uint32_t dst, const CUtensorMap* tm, int c1, int c2, uint32_t bar) {
  asm volatile("cp.async.bulk.tensor.3d.shared::cluster.global.mbarrier::complete_tx::bytes [%0], [%1, {%2, %3, %4}], [%5];"
               ::"r"(dst), "l"(tm), "r"(0), "r"(c1), "r"(c2), "r"(bar) : "memory");
}
__device__ __forceinline__ void tma2d_stream(uint32_t dst, const CUtensorMap* tm, int c0, int c1, uint32_t bar) {
  asm volatile("{\n.reg .b64 pol;\ncreatepolicy.fractional.L2::evict_first.b64 pol, 1.0;\n"
               "cp.async.bulk.tensor.2d.shared::cluster.global.mbarrier::complete_tx::bytes.L2::cache_hint [%0], [%1, {%2, %3}], [%4], pol;\n}"
               ::"r"(dst), "l"(tm), "r"(c0), "r"(c1), "r"(bar) : "memory");
}
__device__ __forceinline__ void tma2d_prefetch(const CUtensorMap* tm, int c0, int c1) {
  asm volatile("cp.async.bulk.prefetch.tensor.2d.L2.global [%0, {%1, %2}];" ::"l"(tm), "r"(c0), "r"(c1) : "memory");
}
__device__ __forceinline__ void prefetch_l2(const void* p, uint32_t bytes) {
  asm volatile("cp.async.bulk.prefetch.L2.global [%0], %1;" ::"l"(p), "r"(bytes) : "memory");
}
__device__ __forceinline__ void prefetch_tmap(const CUtensorMap* tm) {
  asm volatile("prefetch.tensormap [%0];" ::"l"(tm) : "memory");
}

__device__ __forceinline__ void wg_fence() { asm volatile("wgmma.fence.sync.aligned;" ::: "memory"); }
__device__ __forceinline__ void wg_commit() { asm volatile("wgmma.commit_group.sync.aligned;" ::: "memory"); }
template <int N> __device__ __forceinline__ void wg_wait() { asm volatile("wgmma.wait_group.sync.aligned %0;" ::"n"(N) : "memory"); }

__device__ __forceinline__ uint64_t mkdesc(uint32_t addr, uint32_t lbo_bytes) {
  return (uint64_t)(((addr & 0x3FFFF) >> 4) | ((lbo_bytes >> 4) << 16)) | ((uint64_t)0x40000040u << 32);
}
template <int N> __device__ __forceinline__ void pin(float (&a)[N]) {
#pragma unroll
  for (int i = 0; i < N; i++) asm volatile("" : "+f"(a[i])::"memory");
}
template <int N> __device__ __forceinline__ void pin(uint32_t (&a)[N]) {
#pragma unroll
  for (int i = 0; i < N; i++) asm volatile("" : "+r"(a[i])::"memory");
}

#define F8(d, o) "+f"(d[o]), "+f"(d[o + 1]), "+f"(d[o + 2]), "+f"(d[o + 3]), "+f"(d[o + 4]), "+f"(d[o + 5]), "+f"(d[o + 6]), "+f"(d[o + 7])
#define R32A "%0, %1, %2, %3, %4, %5, %6, %7, %8, %9, %10, %11, %12, %13, %14, %15, %16, %17, %18, %19, %20, %21, %22, %23, %24, %25, %26, %27, %28, %29, %30, %31"
#define R32B "%32, %33, %34, %35, %36, %37, %38, %39, %40, %41, %42, %43, %44, %45, %46, %47, %48, %49, %50, %51, %52, %53, %54, %55, %56, %57, %58, %59, %60, %61, %62, %63"

template <int TB>
__device__ __forceinline__ void mma_n128(float (&d)[64], uint32_t a0, uint32_t a1, uint32_t a2, uint32_t a3, uint64_t db, int acc) {
  asm volatile("{\n.reg .pred p;\nsetp.ne.b32 p, %69, 0;\n"
               "wgmma.mma_async.sync.aligned.m64n128k16.f32.bf16.bf16 {" R32A ", " R32B "}, {%64, %65, %66, %67}, %68, p, 1, 1, %70;\n}\n"
               : F8(d, 0), F8(d, 8), F8(d, 16), F8(d, 24), F8(d, 32), F8(d, 40), F8(d, 48), F8(d, 56)
               : "r"(a0), "r"(a1), "r"(a2), "r"(a3), "l"(db), "r"(acc), "n"(TB));
}
__device__ __forceinline__ void mma_n128_ss(float (&d)[64], uint64_t da, uint64_t db, int acc) {
  asm volatile("{\n.reg .pred p;\nsetp.ne.b32 p, %66, 0;\n"
               "wgmma.mma_async.sync.aligned.m64n128k16.f32.bf16.bf16 {" R32A ", " R32B "}, %64, %65, p, 1, 1, 0, 0;\n}\n"
               : F8(d, 0), F8(d, 8), F8(d, 16), F8(d, 24), F8(d, 32), F8(d, 40), F8(d, 48), F8(d, 56)
               : "l"(da), "l"(db), "r"(acc));
}
__device__ __forceinline__ void mma_n64t(float (&d)[32], uint32_t a0, uint32_t a1, uint32_t a2, uint32_t a3, uint64_t db, int acc) {
  asm volatile("{\n.reg .pred p;\nsetp.ne.b32 p, %37, 0;\n"
               "wgmma.mma_async.sync.aligned.m64n64k16.f32.bf16.bf16 {" R32A "}, {%32, %33, %34, %35}, %36, p, 1, 1, 1;\n}\n"
               : F8(d, 0), F8(d, 8), F8(d, 16), F8(d, 24)
               : "r"(a0), "r"(a1), "r"(a2), "r"(a3), "l"(db), "r"(acc));
}
__device__ __forceinline__ void mma_n8(float (&d)[4], uint64_t da, uint64_t db, int acc) {
  asm volatile("{\n.reg .pred p;\nsetp.ne.b32 p, %6, 0;\n"
               "wgmma.mma_async.sync.aligned.m64n8k16.f32.bf16.bf16 {%0, %1, %2, %3}, %4, %5, p, 1, 1, 1, 0;\n}\n"
               : "+f"(d[0]), "+f"(d[1]), "+f"(d[2]), "+f"(d[3])
               : "l"(da), "l"(db), "r"(acc));
}
__device__ __forceinline__ void hmma_k8(float (&d)[4], uint32_t a0, uint32_t a1, uint32_t b0) {
  asm volatile("mma.sync.aligned.m16n8k8.row.col.f32.bf16.bf16.f32 {%0, %1, %2, %3}, {%4, %5}, {%6}, {%0, %1, %2, %3};"
               : "+f"(d[0]), "+f"(d[1]), "+f"(d[2]), "+f"(d[3]) : "r"(a0), "r"(a1), "r"(b0));
}
__device__ __forceinline__ void hmma_k16(float (&d)[4], uint32_t a0, uint32_t a1, uint32_t a2, uint32_t a3, uint32_t b0, uint32_t b1) {
  asm volatile("mma.sync.aligned.m16n8k16.row.col.f32.bf16.bf16.f32 {%0, %1, %2, %3}, {%4, %5, %6, %7}, {%8, %9}, {%0, %1, %2, %3};"
               : "+f"(d[0]), "+f"(d[1]), "+f"(d[2]), "+f"(d[3]) : "r"(a0), "r"(a1), "r"(a2), "r"(a3), "r"(b0), "r"(b1));
}

__device__ __forceinline__ uint32_t pack2(float lo, float hi) {
  uint32_t r;
  asm("cvt.rn.bf16x2.f32 %0, %1, %2;" : "=r"(r) : "f"(hi), "f"(lo));
  return r;
}
__device__ __forceinline__ float bf_lo(uint32_t w) { return __uint_as_float(w << 16); }
__device__ __forceinline__ float bf_hi(uint32_t w) { return __uint_as_float(w & 0xFFFF0000u); }
__device__ __forceinline__ float bfr(float x) { return __bfloat162float(__float2bfloat16_rn(x)); }
__device__ __forceinline__ uint32_t sub2(uint32_t a, uint32_t b) {
  uint32_t r;
  asm("sub.rn.bf16x2 %0, %1, %2;" : "=r"(r) : "r"(a), "r"(b));
  return r;
}
__device__ __forceinline__ uint32_t add2(uint32_t a, uint32_t b) {
  uint32_t r;
  asm("add.rn.bf16x2 %0, %1, %2;" : "=r"(r) : "r"(a), "r"(b));
  return r;
}
__device__ __forceinline__ float ex2(float x) {
  float r;
  asm("ex2.approx.ftz.f32 %0, %1;" : "=f"(r) : "f"(x));
  return r;
}
__device__ __forceinline__ float rcp(float x) {
  float r;
  asm("rcp.approx.ftz.f32 %0, %1;" : "=f"(r) : "f"(x));
  return r;
}
__device__ __forceinline__ float silu_f(float t) { return t * rcp(1.0f + ex2(-1.4426950408889634f * t)); }
__device__ __forceinline__ void sts128(uint32_t a, uint32_t x, uint32_t y, uint32_t z, uint32_t w) {
  asm volatile("st.shared.v4.u32 [%0], {%1, %2, %3, %4};" ::"r"(a), "r"(x), "r"(y), "r"(z), "r"(w) : "memory");
}
__device__ __forceinline__ void lds128(uint32_t a, uint32_t& x, uint32_t& y, uint32_t& z, uint32_t& w) {
  asm volatile("ld.shared.v4.u32 {%0, %1, %2, %3}, [%4];" : "=r"(x), "=r"(y), "=r"(z), "=r"(w) : "r"(a) : "memory");
}
__device__ __forceinline__ void ldsm4(uint32_t a, uint32_t& x, uint32_t& y, uint32_t& z, uint32_t& w) {
  asm volatile("ldmatrix.sync.aligned.m8n8.x4.shared.b16 {%0, %1, %2, %3}, [%4];" : "=r"(x), "=r"(y), "=r"(z), "=r"(w) : "r"(a) : "memory");
}
__device__ __forceinline__ void st_gran(uint4* p, uint32_t x, uint32_t y, uint32_t z, uint32_t w) {
  asm volatile("st.relaxed.gpu.global.v4.b32 [%0], {%1, %2, %3, %4};" ::"l"(p), "r"(x), "r"(y), "r"(z), "r"(w) : "memory");
}
__device__ __forceinline__ void ld_gran(const uint4* p, uint32_t& x, uint32_t& y, uint32_t& z, uint32_t& w) {
  asm volatile("ld.relaxed.gpu.global.v4.b32 {%0, %1, %2, %3}, [%4];" : "=r"(x), "=r"(y), "=r"(z), "=r"(w) : "l"(p) : "memory");
}
__device__ __forceinline__ void stsm4(uint32_t a, uint32_t x, uint32_t y, uint32_t z, uint32_t w) {
  asm volatile("stmatrix.sync.aligned.m8n8.x4.shared.b16 [%0], {%1, %2, %3, %4};" ::"r"(a), "r"(x), "r"(y), "r"(z), "r"(w) : "memory");
}
__device__ __forceinline__ void cp16(uint32_t dst, const void* src) {
  asm volatile("cp.async.cg.shared.global [%0], [%1], 16;" ::"r"(dst), "l"(src) : "memory");
}
template <class T>
__device__ __forceinline__ T* at(const void* base, uint32_t off) {
  uint64_t r;
  asm("{\n.reg .u32 lo, hi;\nmov.b64 {lo, hi}, %1;\nadd.cc.u32 lo, lo, %2;\naddc.u32 hi, hi, 0;\nmov.b64 %0, {lo, hi};\n}"
      : "=l"(r) : "l"(base), "r"(off));
  return (T*)__cvta_global_to_generic(r);
}
__device__ __forceinline__ void cp_wait_all() { asm volatile("cp.async.wait_all;" ::: "memory"); }
__device__ __forceinline__ void add_granules(float (&red)[32], const uint32_t (&g)[16]) {
#pragma unroll
  for (int i = 0; i < 16; i++) { red[2 * i] += bf_lo((i & 3) ? g[i] : g[i] & ~1u); red[2 * i + 1] += bf_hi(g[i]); }
}
__device__ __forceinline__ bool granules_ok(const uint32_t (&g)[16], uint32_t tag) {
  return __all_sync(0xffffffffu, (((g[0] ^ tag) | (g[4] ^ tag) | (g[8] ^ tag) | (g[12] ^ tag)) & 1) == 0);
}
__device__ __forceinline__ unsigned ld_acquire(const unsigned* p) {
  unsigned v;
  asm volatile("ld.acquire.gpu.global.u32 %0, [%1];" : "=r"(v) : "l"(p) : "memory");
  return v;
}
__device__ __forceinline__ unsigned atom_add_acq_rel(unsigned* p) {
  unsigned v;
  asm volatile("atom.acq_rel.gpu.global.add.u32 %0, [%1], 1;" : "=r"(v) : "l"(p) : "memory");
  return v;
}
__device__ __forceinline__ void st_release(unsigned* p, unsigned v) {
  asm volatile("st.release.gpu.global.u32 [%0], %1;" ::"l"(p), "r"(v) : "memory");
}

struct LnAcc {
  float sm[2][4], sq[8][4];
  __device__ __forceinline__ void clear() {
#pragma unroll
    for (int i = 0; i < 4; i++) {
      sm[0][i] = sm[1][i] = 0.f;
#pragma unroll
      for (int j = 0; j < 8; j++) sq[j][i] = 0.f;
    }
  }
};
template <int K0, int K1>
__device__ __forceinline__ void ln_fetch(uint32_t (&xa)[144], uint32_t boxes, uint32_t lo) {
#pragma unroll
  for (int k = K0; k < K1; k++) ldsm4(boxes + (k >> 2) * 8192 + (lo ^ ((k & 3) << 5)), xa[4 * k], xa[4 * k + 1], xa[4 * k + 2], xa[4 * k + 3]);
}
__device__ __forceinline__ void ln_accum1(LnAcc& a, int h, uint32_t x0, uint32_t x1, uint32_t x2, uint32_t x3) {
  const uint32_t ONES = 0x3F803F80u;
  hmma_k16(a.sm[h], x0, x1, x2, x3, ONES, ONES);
  hmma_k8(a.sq[4 * h], x0, x1, x0);
  hmma_k8(a.sq[4 * h + 1], x0, x1, x1);
  hmma_k8(a.sq[4 * h + 2], x2, x3, x2);
  hmma_k8(a.sq[4 * h + 3], x2, x3, x3);
}
template <int K0, int K1>
__device__ __forceinline__ void ln_accum(const uint32_t (&xa)[144], LnAcc& a) {
#pragma unroll
  for (int k = K0; k < K1; k++) ln_accum1(a, k & 1, xa[4 * k], xa[4 * k + 1], xa[4 * k + 2], xa[4 * k + 3]);
}
template <int K0, int K1>
__device__ __forceinline__ void ln_sums(const uint32_t (&xa)[144], float (&sm)[4][4]) {
#pragma unroll
  for (int k = K0; k < K1; k++) hmma_k16(sm[k & 3], xa[4 * k], xa[4 * k + 1], xa[4 * k + 2], xa[4 * k + 3], 0x3F803F80u, 0x3F803F80u);
}
__device__ __forceinline__ uint32_t sq8(const uint32_t* a) {
  uint32_t t, u;
  asm("mul.rn.bf16x2 %0, %1, %1;" : "=r"(t) : "r"(a[0]));
  asm("mul.rn.bf16x2 %0, %1, %1;" : "=r"(u) : "r"(a[2]));
#pragma unroll
  for (int i = 4; i < 16; i += 4) {
    asm("fma.rn.bf16x2 %0, %1, %1, %0;" : "+r"(t) : "r"(a[i]));
    asm("fma.rn.bf16x2 %0, %1, %1, %0;" : "+r"(u) : "r"(a[i + 2]));
  }
  return add2(t, u);
}
__device__ __forceinline__ void ln_centre(uint32_t (&xa)[144], int j0, int j1, uint32_t mm0, uint32_t mm1, float& sq0, float& sq1) {
#pragma unroll
  for (int j = 0; j < 72; j += 8)
    if (j >= j0 && j < j1) {
#pragma unroll
      for (int k = j; k < j + 8; k++) {
        xa[2 * k] = sub2(xa[2 * k], mm0);
        xa[2 * k + 1] = sub2(xa[2 * k + 1], mm1);
      }
      const uint32_t t0 = sq8(xa + 2 * j), t1 = sq8(xa + 2 * j + 1);
      sq0 += bf_lo(t0) + bf_hi(t0);
      sq1 += bf_lo(t1) + bf_hi(t1);
    }
}
__device__ __forceinline__ float ln_rstd(float msq, float d) {
  float sd;
  asm("sqrt.approx.f32 %0, %1;" : "=f"(sd) : "f"(bfr(bfr(fmaxf(msq - d * d, 0.0f)) + 1e-5f)));
  return rcp(bfr(sd));
}
__device__ __forceinline__ void ln_row(float sum, float sq, float& mean_b, float& rstd) {
  const float mean = sum * (1.0f / DM);
  mean_b = bfr(mean);
  rstd = ln_rstd(sq * (1.0f / DM), mean);
}
__device__ __forceinline__ void ln_diag(const LnAcc& a, int lane, float& t0, float& t1) {
  const bool odd = (lane >> 2) & 1;
  t0 = odd ? (a.sq[0][1] + a.sq[2][1]) + (a.sq[4][1] + a.sq[6][1]) : (a.sq[0][0] + a.sq[2][0]) + (a.sq[4][0] + a.sq[6][0]);
  t1 = odd ? (a.sq[1][3] + a.sq[3][3]) + (a.sq[5][3] + a.sq[7][3]) : (a.sq[1][2] + a.sq[3][2]) + (a.sq[5][2] + a.sq[7][2]);
}
__device__ __forceinline__ void ln_stats(const LnAcc& a, int lane, float& mean0, float& rstd0, float& mean1, float& rstd1) {
  float t0, t1;
  ln_diag(a, lane, t0, t1);
  const int src = (lane & ~3) | (lane >> 3);
  t0 = __shfl_sync(0xffffffffu, t0, src);
  t1 = __shfl_sync(0xffffffffu, t1, src);
  ln_row(a.sm[0][0] + a.sm[1][0], t0, mean0, rstd0);
  ln_row(a.sm[0][2] + a.sm[1][2], t1, mean1, rstd1);
}

template <bool ROUTED>
__device__ __forceinline__ uint32_t gate2(uint32_t x2, float mean_b, float rstd, float2 upd = make_float2(0.f, 0.f)) {
  const uint32_t xc = sub2(x2, pack2(mean_b, mean_b));
  uint32_t t = pack2(bf_lo(xc) * rstd, bf_hi(xc) * rstd);
  if (ROUTED) t = pack2(bf_lo(t) + upd.x, bf_hi(t) + upd.y);
  return pack2(silu_f(bf_lo(t)), silu_f(bf_hi(t)));
}

template <int V> struct IC { static constexpr int value = V; };

struct Ctx {
  uint32_t sb;
  uint8_t* sp;
  uint32_t rank;
  Scratch* gs;
};

__device__ __forceinline__ void dly(int) {}
template <int BOXES>
__device__ __forceinline__ void load_stage(uint32_t dst, const CUtensorMap* tm, int c0, int c1, uint32_t bar, uint32_t bytes, uint64_t pol) {
  asm volatile("{\n.reg .pred p;\nelect.sync _|p, 0xffffffff;\n"
               "@p mbarrier.arrive.expect_tx.shared::cta.b64 _, [%4], %7;\n"
               "@p cp.async.bulk.tensor.2d.shared::cluster.global.mbarrier::complete_tx::bytes.multicast::cluster.L2::cache_hint"
               " [%0], [%1, {%2, %3}], [%4], %5, %6;\n}"
               ::"r"(dst), "l"(tm), "r"(c0), "r"(c1), "r"(bar), "h"((uint16_t)3), "l"(pol), "r"(bytes) : "memory");
  if (BOXES == 2)
    asm volatile("{\n.reg .pred p;\nelect.sync _|p, 0xffffffff;\n"
                 "@p cp.async.bulk.tensor.2d.shared::cluster.global.mbarrier::complete_tx::bytes.multicast::cluster.L2::cache_hint"
                 " [%0], [%1, {%2, %3}], [%4], %5, %6;\n}"
                 ::"r"(dst + 8192), "l"(tm), "r"(c0), "r"(c1 + 64), "r"(bar), "h"((uint16_t)3), "l"(pol) : "memory");
}
__device__ __forceinline__ void attn_producer(const Ctx& cx, int qb, int hs, const CUtensorMap* tmX, const CUtensorMap* tmK,
                                              const CUtensorMap* tmV, const CUtensorMap* tmWq, const CUtensorMap* tmWo) {
  const uint32_t full = cx.sb + SM_FULL, empty = cx.sb + SM_EMPTY, ring = cx.sb + SM_RING + cx.rank * 16384;
  const uint64_t keep = policy_evict_normal(), last_use = policy_evict_first();
  auto acquire = [&](int st) {
    mbar_wait(empty + 8 * (st & 3), ((st >> 2) ^ ((st & 3) >> 1) ^ 1) & 1);
    dly(st);
  };
  if (elect_one()) {
#pragma unroll
    for (int j = 0; j < 3; j++) {
      mbar_expect_tx(cx.sb + SM_XFULL + 96 + 8 * j, 24576);
      tma3d(cx.sb + SM_X + 73728 + j * 24576, tmX, qb * 128 + 64, j * 3, cx.sb + SM_XFULL + 96 + 8 * j);
    }
  }
  __syncwarp();
#pragma unroll 1
  for (int p = 0; p < 4; p++) {
    const int n0 = (hs * 4 + ((0x1320 >> (4 * p)) & 3)) * DH + cx.rank * 64;
#pragma unroll
    for (int i = 0; i < 5; i++) {
      const int st = 5 * p + i, sl = st & 3;
      if (i == 4 && p == 3) break;
      acquire(st);
      if (i == 2) load_stage<1>(ring + sl * STAGE, tmWq, n0, 256, full + 8 * sl, 16384, last_use);
      else load_stage<2>(ring + sl * STAGE, tmWq, n0, i < 2 ? 128 * i : 128 * i - 64, full + 8 * sl, 32768, last_use);
      if (i == X_PFQ && p == 0 && elect_one()) {
#pragma unroll 1
        for (int b = 8 + qb; b < 72; b += 16) {
          const int bp = (b * 57) >> 10;
          tma2d_prefetch(tmWq, (hs * 4 + ((0x1320 >> (4 * bp)) & 3)) * DH + (b & 1) * 64, ((b - 18 * bp) >> 1) * 64);
        }
      }
      __syncwarp();
    }
  }
  const int c0 = cx.rank * 64;
  int vrow = 0;
  uint64_t vpol = keep;
#pragma unroll 1
  for (int j = 0; j < 32; j++) {
    const int st = NST_Q - 1 + 4 * j, row = (hs * 2 + (j >> 4)) * SEQ + (j & 7) * 256;
    const uint64_t pol = (j & 8) ? last_use : keep;
    acquire(st);
    load_stage<1>(ring + 3 * STAGE, tmK, c0, row, full + 24, 32768, pol);
    acquire(st + 1);
    if (j) load_stage<1>(ring, tmV, c0, vrow, full, 32768, vpol);
    else load_stage<2>(ring, tmWq, (hs * 4 + 1) * DH + c0, 448, full, 32768, last_use);
    vrow = row + 128;
    vpol = pol;
    acquire(st + 2);
    load_stage<1>(ring + STAGE, tmK, c0, vrow, full + 8, 32768, pol);
    acquire(st + 3);
    load_stage<1>(ring + 2 * STAGE, tmV, c0, row, full + 16, 32768, pol);
  }
  acquire(NST_Q + NST_KV - 1);
  load_stage<1>(ring + 3 * STAGE, tmV, c0, vrow, full + 24, 32768, last_use);
#pragma unroll 1
  for (int u = 0; u < NST_O; u++) {
    const int s = u >> 1, st = NST_Q + NST_KV + u, sl = st & 3;
    const int blk = s == 0 ? 8 : ((hs + s) & 7);
    acquire(st);
    load_stage<1>(ring + sl * STAGE, tmWo, blk * 64, hs * 512 + (((u & 1) * 2 + cx.rank + 3) & 3) * 128, full + 8 * sl, 32768, last_use);
  }
}

__device__ __forceinline__ void attn_gate(const Ctx& cx, int qb, int hs, int t, const __nv_bfloat16* x) {
  const uint32_t base = (qb * 128 * DM + (t & 7) * 8) * 2;
  uint32_t lr = t >> 3, o = base + (lr * DM + hs * 64) * 2;
  uint4 nx = __ldg(at<const uint4>(x, o));
  bar_sync(BAR_GATE, 352);
#pragma unroll 1
  for (uint32_t n = (t >> 3) + 12; n < 156; n += 12) {
    const uint4 v = nx;
    const float2 st = *(const float2*)(cx.sp + SM_STATS + 8 * lr);
    uint4* dst = at<uint4>(cx.gs->gate, o);
    lr = n < 128 ? n : n + hs * 16 - 128;
    o = base + (lr * DM + (n < 128 ? hs * 64 : 512)) * 2;
    if (n < 144) nx = __ldg(at<const uint4>(x, o));
    *dst = make_uint4(gate2<false>(v.x, st.x, st.y), gate2<false>(v.y, st.x, st.y), gate2<false>(v.z, st.x, st.y), gate2<false>(v.w, st.x, st.y));
  }
}

constexpr uint32_t SM_XO = SM_SLOT, SM_GO = SM_SLOT + 128 * 144;
constexpr uint32_t SM_X8 = SM_SLOT + 2 * STAGE + 20480, SM_G8 = SM_X8 + 16 * 144;
__device__ __forceinline__ void attn_stage_xg(const Ctx& cx, int qb, int hs, int t, const __nv_bfloat16* x) {
  bar_sync(BAR_OA, 352);
#pragma unroll 1
  for (uint32_t lr = t >> 3; lr < 128; lr += 8) {
    const uint32_t o = ((qb * 128 + lr) * DM + hs * 64 + (t & 7) * 8) * 2;
    cp16(cx.sb + SM_XO + lr * 144 + (t & 7) * 16, at<const void>(x, o));
    cp16(cx.sb + SM_GO + lr * 144 + (t & 7) * 16, at<const void>(cx.gs->gate, o));
  }
  cp_wait_all();
  mbar_arrive(cx.sb + SM_BAR_XG);
}

__device__ __forceinline__ void attn_helper(const Ctx& cx, int qb, int hs, int lane, const __nv_bfloat16* x, const __nv_bfloat16* wo) {
  unsigned e = 0;
  if (lane == 0) {
    e = cx.gs->launch[blockIdx.x];
    cx.gs->launch[blockIdx.x] = e + 1;
  }
  e = __shfl_sync(0xffffffffu, e, 0);
  bar_sync(BAR_HELPER, 128);
  prefetch_l2(at<const void>(wo, (hs * 512 + qb * 32 + lane) * (DM * 2)), DM * 2);
#pragma unroll 1
  for (int n = 0; n < (1 << 16) && ld_acquire(&cx.gs->ffn_flag) != e + 1; n++) __nanosleep(1000);
  const uint32_t tag = ~e & 1;
  {
#pragma unroll 1
    for (int i = 0; i < 2 * TOPC; i++) {
      const int lr = __ldcg(&cx.gs->idx[i >> 1]) - qb * 128, col = ((i & 1) ? 512 : hs * 64) + 2 * lane;
      if ((i & 1) ? (lr >> 4) == hs : (lr >> 7) == 0) {
        const float2 st = *(const float2*)(cx.sp + SM_STATS + 8 * lr);
        const uint32_t o = ((qb * 128 + lr) * DM + col) * 2;
        *at<uint32_t>(cx.gs->gate, o) =
            gate2<true>(*at<const uint32_t>(x, o), st.x, st.y, __ldcg(at<const float2>(cx.gs->upd, ((i >> 1) * DM + col) * 4)));
      }
    }
  }
  if (lane == 0) *(uint32_t*)(cx.sp + SM_TAG) = tag;
  __syncwarp();
  if (lane == 0) mbar_arrive(cx.sb + SM_BAR_MISC);

  const uint4* src = at<const uint4>(cx.gs->part, (((qb * 64 + 56) * 2 + (hs >> 2)) * 4 * 128 + (hs & 3) * 32 + lane) * 16);
  const uint32_t stg = cx.sb + SM_SLOT + 2 * STAGE + lane * 16;
  bar_sync(BAR_OA, 352);

#pragma unroll 1
  for (int i = 0; i < 4; i++) {
    const int ch = i * 32 + lane;
    const uint32_t o = ((qb * 128 + hs * 16 + (ch >> 3)) * DM + 512 + (ch & 7) * 8) * 2;
    cp16(cx.sb + SM_X8 + (ch >> 3) * 144 + (ch & 7) * 16, at<const void>(x, o));
    cp16(cx.sb + SM_G8 + (ch >> 3) * 144 + (ch & 7) * 16, at<const void>(cx.gs->gate, o));
  }
#pragma unroll 1
  for (int n = 0; n < (1 << 16); n++) {
    __nanosleep(n ? 500 : 2000);
    uint32_t a, b, d, t;
    ld_gran(at<const uint4>(src, ((lane & 7) * (2 * 4 * 128) + 3 * 128 + 31 - lane) * 16), a, b, d, t);
    if (__all_sync(0xffffffffu, (a & 1) == tag)) break;
  }
#pragma unroll 1
  for (int n = 0; n < (1 << 16); n++) {
#pragma unroll 1
    for (int i = 0; i < 8; i++) {
#pragma unroll
      for (int g = 0; g < 4; g++) cp16(stg + (i * 4 + g) * 512, at<const uint4>(src, i * (2 * 4 * 128 * 16)) + g * 128);
    }
    cp_wait_all();
    uint32_t bad = 0;
#pragma unroll 4
    for (int i = 0; i < 32; i++) bad |= *(const volatile uint32_t*)(cx.sp + SM_SLOT + 2 * STAGE + lane * 16 + i * 512) ^ tag;
    if (__all_sync(0xffffffffu, (bad & 1) == 0)) break;
  }

}
__device__ __forceinline__ void attn_finish8(const Ctx& cx, int qb, int hs, int hw, int lane, __nv_bfloat16* out) {
  bar_sync(BAR_GATE, 96);
#pragma unroll 1
  for (int g = hw; g < 4; g += 3) {
    float acc[8] = {0.f, 0.f, 0.f, 0.f, 0.f, 0.f, 0.f, 0.f};
#pragma unroll 2
    for (int sidx = 0; sidx < 8; sidx++) {
      uint32_t a, b, d, t;
      lds128(cx.sb + SM_SLOT + 2 * STAGE + lane * 16 + (sidx * 4 + g) * 512, a, b, d, t);
      acc[0] += bf_lo(a & ~1u); acc[1] += bf_hi(a); acc[2] += bf_lo(b); acc[3] += bf_hi(b);
      acc[4] += bf_lo(d); acc[5] += bf_hi(d); acc[6] += bf_lo(t); acc[7] += bf_hi(t);
    }
#pragma unroll
    for (int j = 0; j < 4; j++) {
      const int o = ((lane >> 2) + (j & 1) * 8) * 144 + (2 * g + (j >> 1)) * 16 + (lane & 3) * 4;
      uint32_t* xp = (uint32_t*)(cx.sp + SM_X8 + o);
      const uint32_t xw = *xp, gw = *(const uint32_t*)(cx.sp + SM_G8 + o);
      *xp = pack2(fmaf(acc[2 * j], bf_lo(gw), bf_lo(xw)), fmaf(acc[2 * j + 1], bf_hi(gw), bf_hi(xw)));
    }
  }
  bar_sync(BAR_GATE, 96);
#pragma unroll 1
  for (int ch = hw * 32 + lane; ch < 128; ch += 96)
    *at<uint4>(out, ((qb * 128 + hs * 16 + (ch >> 3)) * DM + 512 + (ch & 7) * 8) * 2) =
        *(const uint4*)(cx.sp + SM_X8 + (ch >> 3) * 144 + (ch & 7) * 16);
}

constexpr float SUM_HI = 1.8446744e19f, SUM_LO = 9.0949470e-13f;

__device__ __forceinline__ void softmax_shift(float (&s)[64], float n0, float n1) {
#pragma unroll
  for (int i = 0; i < 64; i++) s[i] += (i & 2) ? n1 : n0;
}
template <int LO, int HI>
__device__ __forceinline__ void softmax_exp(float (&s)[64]) {
#pragma unroll
  for (int i = LO; i < HI; i++) s[i] = ex2(s[i]);
}
__device__ __forceinline__ void row_sums(const uint32_t (&pf)[32], float& l0, float& l1) {
  uint32_t t[16];
#pragma unroll
  for (int i = 0; i < 16; i++) t[i] = add2(pf[(i >> 1) * 4 + (i & 1)], pf[(i >> 1) * 4 + 2 + (i & 1)]);
#pragma unroll
  for (int i = 0; i < 8; i++) t[i] = add2(t[(i >> 1) * 4 + (i & 1)], t[(i >> 1) * 4 + 2 + (i & 1)]);
#pragma unroll
  for (int i = 0; i < 4; i++) t[i] = add2(t[(i >> 1) * 4 + (i & 1)], t[(i >> 1) * 4 + 2 + (i & 1)]);
  l0 += (bf_lo(t[0]) + bf_lo(t[2])) + (bf_hi(t[0]) + bf_hi(t[2]));
  l1 += (bf_lo(t[1]) + bf_lo(t[3])) + (bf_hi(t[1]) + bf_hi(t[3]));
}
__device__ __forceinline__ void row_max(const float (&s)[64], float& x0, float& x1) {
  x0 = s[0];
  x1 = s[2];
#pragma unroll
  for (int i = 0; i < 64; i += 4) { x0 = fmaxf(x0, fmaxf(s[i], s[i + 1])); x1 = fmaxf(x1, fmaxf(s[i + 2], s[i + 3])); }
  x0 = fmaxf(x0, __shfl_xor_sync(0xffffffffu, x0, 1));
  x1 = fmaxf(x1, __shfl_xor_sync(0xffffffffu, x1, 1));
  x0 = fmaxf(x0, __shfl_xor_sync(0xffffffffu, x0, 2));
  x1 = fmaxf(x1, __shfl_xor_sync(0xffffffffu, x1, 2));
}
__device__ __forceinline__ void softmax_rebase(float (&s)[64], float& n0, float& n1, float& sc0, float& sc1) {
  float x0, x1;
  row_max(s, x0, x1);
  x0 = fmaxf(x0, 1.f);
  x1 = fmaxf(x1, 1.f);
  n0 -= __log2f(x0);
  n1 -= __log2f(x1);
  sc0 = exp2f(-__log2f(x0));
  sc1 = exp2f(-__log2f(x1));
#pragma unroll
  for (int i = 0; i < 64; i++) s[i] *= (i & 2) ? sc1 : sc0;
}
__device__ __forceinline__ void softmax_redo(float (&s)[64], const uint32_t (&q)[32], const __nv_bfloat16* kblk, int lane, float& n0,
                                             float& n1, float& sc0, float& sc1) {
  const __nv_bfloat16* kp = kblk + (lane >> 2) * DH + (lane & 3) * 2;
#pragma unroll
  for (int nb = 0; nb < 16; nb++) {
    float d[4] = {0.f, 0.f, 0.f, 0.f};
#pragma unroll
    for (int k = 0; k < 8; k++)
      hmma_k16(d, q[4 * k], q[4 * k + 1], q[4 * k + 2], q[4 * k + 3], *(const uint32_t*)(kp + nb * 8 * DH + k * 16),
               *(const uint32_t*)(kp + nb * 8 * DH + k * 16 + 8));
    s[4 * nb] = d[0]; s[4 * nb + 1] = d[1]; s[4 * nb + 2] = d[2]; s[4 * nb + 3] = d[3];
    block_fence(100 + nb);
  }
  float x0, x1;
  row_max(s, x0, x1);
  const float m0 = fminf(n0, -x0), m1 = fminf(n1, -x1);
  sc0 = ex2(m0 - n0);
  sc1 = ex2(m1 - n1);
  n0 = m0; n1 = m1;
  softmax_shift(s, n0, n1);
  softmax_exp<0, 64>(s);
}

__device__ __forceinline__ void attn_consumer(const Ctx& cx, int qb, int hs, int wg, int cw, int lane, const __nv_bfloat16* x,
                                              const __nv_bfloat16* kc, __nv_bfloat16* out) {
  const int r = lane >> 2, c = lane & 3, tw = (cw & 3) * 32 + lane;
  const int lr0 = cw * 16 + r;
  const uint32_t full = cx.sb + SM_FULL;
  const uint32_t ring = cx.sb + SM_RING;
  const uint32_t lo = ((cw & 3) * 16 + (lane & 15)) * 128 + (((lane >> 4) ^ (lane & 7)) << 4);
  const uint32_t slot = cx.sb + SM_SLOT + wg * 16384;
  auto frag = [&](int sl, int k) { return slot + sl * STAGE + (k >> 2) * 8192 + (lo ^ ((k & 3) << 5)); };
  auto park = [&](const float (&a)[64], int sl, int k0, int k1, float f0, float f1) {
#pragma unroll
    for (int k = 0; k < 8; k++)
      if (k >= k0 && k < k1)
        stsm4(frag(sl, k), pack2(a[8 * k] * f0, a[8 * k + 1] * f0), pack2(a[8 * k + 2] * f1, a[8 * k + 3] * f1),
              pack2(a[8 * k + 4] * f0, a[8 * k + 5] * f0), pack2(a[8 * k + 6] * f1, a[8 * k + 7] * f1));
  };
  const bool signaller = lane == 0 && (cw & 3) < 2;
  int my_turn = 1 + wg, other_turn = 2 - wg;

  uint32_t pf[32], empty_c;
  float o[64], l0, l1;
  {
    uint32_t xa[144];
    float rstd0, rstd1, sq0 = 0.f, sq1 = 0.f;
    {
      const uint32_t xb = cx.sb + SM_X + wg * 73728, xf = cx.sb + SM_XFULL + wg * 96;
      float sm[4][4] = {};
      prof(wg, 0);
      empty_c = mapa(cx.sb + SM_EMPTY, cw & 1);
      mbar_wait(xf, 0);
      if ((threadIdx.x & 127) == 0) profc(wg, 30);
      ln_fetch<0, 12>(xa, xb, lo);
      mbar_wait(xf + 8, 0);
      ln_fetch<12, 24>(xa, xb, lo);
      ln_sums<0, 12>(xa, sm);
      mbar_wait(xf + 16, 0);
      if ((threadIdx.x & 127) == 0) profc(wg, 1);
      ln_fetch<24, 36>(xa, xb, lo);
      ln_sums<12, 36>(xa, sm);
      rstd0 = ((sm[0][0] + sm[1][0]) + (sm[2][0] + sm[3][0])) * (1.0f / DM);
      rstd1 = ((sm[0][2] + sm[1][2]) + (sm[2][2] + sm[3][2])) * (1.0f / DM);
    }
    asm volatile("" : "+f"(rstd0), "+f"(rstd1)::"memory");
    if (wg) {
      bar_arrive(other_turn, 256);
    } else {
      bar_sync(4, 128);
      if (signaller) {
        asm volatile("mbarrier.arrive.shared::cluster.b64 _, [%0], 2;" ::"r"(empty_c + 16) : "memory");
        asm volatile("mbarrier.arrive.shared::cluster.b64 _, [%0], 2;" ::"r"(empty_c + 24) : "memory");
      }
    }
    const uint32_t mm0 = pack2(rstd0, rstd0), mm1 = pack2(rstd1, rstd1);
    ln_centre(xa, 0, X_C0, mm0, mm1, sq0, sq1);
    pin(xa);
    if ((threadIdx.x & 127) == 0) profc(wg, 2);

#pragma unroll 1
    for (int p = 0;; p++) {
      const int st0 = p * 5, last = p == 3 ? 3 : 4;
#pragma unroll
      for (int i = 0; i < 5; i++) {
        const int st = st0 + i;
        const uint32_t sl = st & 3;
        mbar_wait(full + 8 * sl, (st >> 2) & 1);
        if (i != (wg ? last : 1)) bar_sync(my_turn, 256);
        wg_fence();
        const uint64_t db = mkdesc(ring + sl * STAGE, 16384);
        const int kb0 = i < 3 ? 8 * i : 8 * i - 4;
#pragma unroll
        for (int k = 0; k < (i == 2 ? 4 : 8); k++) {
          const int kb = kb0 + k;
          mma_n128<1>(o, xa[4 * kb], xa[4 * kb + 1], xa[4 * kb + 2], xa[4 * kb + 3], db + k * 128, kb > 0);
          if (i == 4 && k == X_HO) wg_commit();
        }
        wg_commit();
        if (i == 4 && X_HO < 7) wg_wait<1>();
        if (i != (wg ? last - 1 : 0)) bar_arrive(other_turn, 256);
        if (p == 0 && (i == 1 || i == 2)) {
          ln_centre(xa, i == 1 ? X_C0 : X_C1, i == 1 ? X_C1 : 72, mm0, mm1, sq0, sq1);
          if (i == 2) {
            sq0 += __shfl_xor_sync(0xffffffffu, sq0, 1); sq1 += __shfl_xor_sync(0xffffffffu, sq1, 1);
            sq0 += __shfl_xor_sync(0xffffffffu, sq0, 2); sq1 += __shfl_xor_sync(0xffffffffu, sq1, 2);
            rstd0 = ln_rstd(sq0 * (1.0f / DM), rstd0 - bf_lo(mm0));
            rstd1 = ln_rstd(sq1 * (1.0f / DM), rstd1 - bf_lo(mm1));
            if (c == 0) {
              *(float2*)(cx.sp + SM_STATS + 8 * lr0) = make_float2(bf_lo(mm0), rstd0);
              *(float2*)(cx.sp + SM_STATS + 8 * (lr0 + 8)) = make_float2(bf_lo(mm1), rstd1);
            }
            bar_arrive(BAR_GATE, 352);
            rstd0 *= SM_SCALE_LOG2;
            rstd1 *= SM_SCALE_LOG2;
          }
          pin(xa);
        }
        if (i == 0 || i == 2) {
          if (i ? p != 3 : wg) {
            wg_wait<0>();
            if (signaller) mbar_arrive_cluster(empty_c + 8 * sl);
          }
        } else if (i == 3) {
          if (p == 3) break;
        } else {
          wg_wait<1>();
          if (signaller && (i == 4 || !wg)) mbar_arrive_cluster(empty_c + 8 * ((st - 1) & 3));
          wg_wait<0>();
          if (signaller) mbar_arrive_cluster(empty_c + 8 * sl);
        }
      }
      if (p == 3) break;
      pin(o);
      park(o, p, 0, 8, rstd0, rstd1);
    }
    wg_wait<1>();
    if (signaller) mbar_arrive_cluster(empty_c + 8 * ((NST_Q - 3) & 3));
    wg_wait<0>();
    if (signaller) mbar_arrive_cluster(empty_c + 8 * ((NST_Q - 2) & 3));
    prof(wg, 6);
#pragma unroll
    for (int i = 0; i < 32; i++) pf[i] = xa[112 + i];
    l0 = 0.25f * rcp(rstd0);
    l1 = 0.25f * rcp(rstd1);
  }

  uint32_t oa[96];
  const uint32_t zero = __shfl_sync(0xffffffffu, blockIdx.y, lane);
  my_turn = __shfl_sync(0xffffffffu, my_turn, lane);
  other_turn = __shfl_sync(0xffffffffu, other_turn, lane);
  {
    float s[64], n0, n1;
    uint32_t q[32];
    float lp0, lp1;
    float i0, i1;
    bool redo, shift;
    auto turn = [&](int it, auto kc_) -> bool {
      constexpr int KIND = decltype(kc_)::value;
      constexpr uint32_t slk = KIND == 1 ? 1 : 3, slv = KIND == 1 ? 2 : 0, slkn = KIND == 1 ? 3 : 1;
      constexpr int SPLIT = X_SPLIT, PARK1 = X_PARK;
      const uint32_t par = ((it + 10) >> 1) & 1;
      const int hsl = max((it >> 4) - 1, 0);
      const uint64_t dk = mkdesc(ring + slk * STAGE, 16), dv = mkdesc(ring + slv * STAGE, 16384);
      auto qk = [&]() {
#pragma unroll
        for (int k = 0; k < 8; k++) {
          if (KIND == 3) mma_n128_ss(s, mkdesc(slot + hsl * STAGE, 16) + (k >> 2) * 512 + (k & 3) * 2, dk + (k >> 2) * 1024 + (k & 3) * 2, k > 0);
          else mma_n128<0>(s, q[4 * k], q[4 * k + 1], q[4 * k + 2], q[4 * k + 3], dk + (k >> 2) * 1024 + (k & 3) * 2, k > 0);
        }
        wg_commit();
      };
      auto pv = [&]() {
#pragma unroll
        for (int k = 0; k < 8; k++)
          mma_n128<1>(o, pf[4 * k], pf[4 * k + 1], pf[4 * k + 2], pf[4 * k + 3], dv + k * 128, k > 0 || KIND != 1 || (it & 15) != 1);
        wg_commit();
      };
      lp0 = l0; lp1 = l1;
#define TS(i)
      {
        TS(0)
        if (KIND == 3) {
          asm volatile("fence.proxy.async.shared::cta;" ::: "memory");
          const float t0 = lp0 + __shfl_xor_sync(0xffffffffu, lp0, 1), t1 = lp1 + __shfl_xor_sync(0xffffffffu, lp1, 1);
          i0 = rcp(t0 + __shfl_xor_sync(0xffffffffu, t0, 2));
          i1 = rcp(t1 + __shfl_xor_sync(0xffffffffu, t1, 2));
          asm volatile("" : "+f"(i0), "+f"(i1)::"memory");
          block_fence(31, zero);
#pragma unroll
          for (int k = 0; k < X_N1; k++) ldsm4(frag(hsl, k), q[4 * k], q[4 * k + 1], q[4 * k + 2], q[4 * k + 3]);
        }
        bar_sync(my_turn, 256);
        TS(1)
        if (KIND != 3) pin(q);
        pin(pf); pin(o);
        wg_fence();
        qk();
        TS(2)
        mbar_wait(full + 8 * slv, par);
        if (KIND == 1 && (it & 15) == 1) {
          park(o, hsl, PARK1, 8, i0, i1);
          wg_fence();
        }
        if (KIND == 3) {
#pragma unroll
          for (int k = X_N1; k < 8; k++) ldsm4(frag(hsl, k), q[4 * k], q[4 * k + 1], q[4 * k + 2], q[4 * k + 3]);
          block_fence(32, zero);
        }
        TS(3)
        pv();
        bar_arrive(other_turn, 256);
        TS(4)
        wg_wait<1>();
      }
      pin(s);
      mbar_arrive_cluster_now<10 * KIND + 3>(empty_c + 8 * slk, signaller, zero);
      TS(5)
      if (KIND == 3) {
        shift = false;
        n0 = n1 = l0 = l1 = 0.f;
      } else if (shift) {
        softmax_shift(s, n0, n1);
        pin(s);
      }
      softmax_exp<0, SPLIT>(s);
      pin(s);
      block_fence(10 * KIND + 4, zero);
      TS(6)
      wg_wait<0>();
      pin(o); pin(pf);
      mbar_arrive_cluster_now<10 * KIND + 5>(empty_c + 8 * slv, signaller, zero);
      TS(7)
      const bool kready = mbar_test(full + 8 * slkn, par);
      softmax_exp<SPLIT, 64>(s);
#pragma unroll
      for (int i = 0; i < 32; i++) pf[i] = pack2(s[2 * i], s[2 * i + 1]);
      row_sums(pf, l0, l1);
      if (KIND == 3) {
        park(o, hsl, 0, PARK1, i0, i1);
        if (it) prof(wg, 6 + (it >> 4));
        if (it == 48 && cw == 0) bar_arrive(BAR_HELPER, 128);
      }
      redo = !(l0 + l1 <= SUM_HI) || (KIND == 3 && fminf(l0, l1) < SUM_LO);
      const bool leave = __any_sync(0xffffffffu, redo || !kready);
      return leave;
    };
    int it = -1;
#pragma unroll 1
    while (true) {
      mbar_wait(full + 8 * ((it & 1) ? 3 : 1), ((it + 10) >> 1) & 1);
      it++;
#pragma unroll 1
      while (true) {
        if (it & 1) {
          if (turn(it, IC<1>()) || it == 63) break;
          it++;
        }
        if (it & 15) {
          if (turn(it, IC<2>())) break;
        } else {
          if (turn(it, IC<3>())) break;
        }
        it++;
      }
      if (__any_sync(0xffffffffu, redo)) {
        const int j = it & 15;
        float sc0, sc1;
        if (__all_sync(0xffffffffu, l0 + l1 < 3.0e38f && (j || fminf(l0, l1) >= SUM_LO))) {
          softmax_rebase(s, n0, n1, sc0, sc1);
        } else {
          if (j == 0) n0 = n1 = 3.0e38f;
          softmax_redo(s, q, kc + (size_t)((hs * 2 + (it >> 5)) * SEQ + j * 128) * DH, lane, n0, n1, sc0, sc1);
        }
        l0 = j ? lp0 * sc0 : 0.f;
        l1 = j ? lp1 * sc1 : 0.f;
        shift = true;
        if (j == 0) sc0 = sc1 = 1.f;
#pragma unroll
        for (int i = 0; i < 16; i++) { o[4 * i] *= sc0; o[4 * i + 1] *= sc0; o[4 * i + 2] *= sc1; o[4 * i + 3] *= sc1; }
#pragma unroll
        for (int i = 0; i < 32; i++) pf[i] = pack2(s[2 * i], s[2 * i + 1]);
        row_sums(pf, l0, l1);
      }
      if (it == 63) break;
    }
    {
      const int st = NST_Q + NST_KV - 1;
      const uint32_t sl = st & 3;
      mbar_wait(full + 8 * sl, (st >> 2) & 1);
      bar_sync(my_turn, 256);
      pin(pf); pin(o);
      wg_fence();
      const uint64_t dv = mkdesc(ring + sl * STAGE, 16384);
#pragma unroll
      for (int k = 0; k < 8; k++) mma_n128<1>(o, pf[4 * k], pf[4 * k + 1], pf[4 * k + 2], pf[4 * k + 3], dv + k * 128, 1);
      wg_commit();
      bar_arrive(other_turn, 256);
      l0 += __shfl_xor_sync(0xffffffffu, l0, 1); l1 += __shfl_xor_sync(0xffffffffu, l1, 1);
      l0 += __shfl_xor_sync(0xffffffffu, l0, 2); l1 += __shfl_xor_sync(0xffffffffu, l1, 2);
      float f0 = fmaxf(rcp(l0), 0.f), f1 = fmaxf(rcp(l1), 0.f);
      asm volatile("" : "+f"(f0), "+f"(f1)::"memory");
      block_fence(61, zero);
#pragma unroll
      for (int i = 0; i < 16; i++) ldsm4(frag(i >> 3, i & 7), oa[4 * i], oa[4 * i + 1], oa[4 * i + 2], oa[4 * i + 3]);
      mbar_wait(cx.sb + SM_BAR_MISC, 0);
      mbar_wait(full + 8 * ((st + 1) & 3), ((st + 1) >> 2) & 1);
      wg_wait<0>();
      pin(o); pin(pf);
      if (signaller) mbar_arrive_cluster(empty_c + 8 * sl);
#pragma unroll
      for (int i = 0; i < 16; i++) {
        pf[2 * i] = pack2(o[4 * i] * f0, o[4 * i + 1] * f0);
        pf[2 * i + 1] = pack2(o[4 * i + 2] * f1, o[4 * i + 3] * f1);
      }
    }
  }

  prof(wg, 10);
  {
    float acc[32], red[32];
#pragma unroll
    for (int i = 0; i < 32; i++) red[i] = 0.f;
    const uint32_t tag = *(const uint32_t*)(cx.sp + SM_TAG);
    uint4* const xch = cx.gs->part + (size_t)(qb * 64 * 2 + wg) * 4 * 128 + tw;
    int nrx = 1;
    auto half_step = [&](int s, auto hc, bool arrive) {
      constexpr int h = decltype(hc)::value;
      const int st = NST_Q + NST_KV + 2 * s + h;
      const uint64_t db = mkdesc(ring + (st & 3) * STAGE, 16);
      bar_sync(my_turn, 256);
      if (h == 0) {
        pin(pf);
#pragma unroll
        for (int i = 0; i < 32; i++) asm volatile("" : "+r"(oa[i])::"memory");
      } else {
        pin(oa);
      }
      wg_fence();
#pragma unroll
      for (int k = 0; k < 16; k++) {
        const int kb = h * 16 + k - 8;
        if (kb >= 0) mma_n64t(acc, oa[4 * kb], oa[4 * kb + 1], oa[4 * kb + 2], oa[4 * kb + 3], db + k * 128, 1);
        else mma_n64t(acc, pf[4 * k], pf[4 * k + 1], pf[4 * k + 2], pf[4 * k + 3], db + k * 128, k > 0);
      }
      wg_commit();
      if (arrive) bar_arrive(other_turn, 256);
    };
    auto await = [&](int st) { mbar_wait(full + 8 * (st & 3), (st >> 2) & 1); };
    auto fetch = [&](uint32_t (&g)[16], int n) {
      const uint4* p = xch + (hs * 7 + n - 1) * (2 * 4 * 128);
#pragma unroll
      for (int i = 0; i < 4; i++) ld_gran(p + i * 128, g[4 * i], g[4 * i + 1], g[4 * i + 2], g[4 * i + 3]);
    };
    uint32_t g[16];
    bool pend = false;
#pragma unroll 1
    for (int s = 0; s < 8; s++) {
      const int st = NST_Q + NST_KV + 2 * s;
      half_step(s, IC<0>(), true);
      if (s == 0) {
#pragma unroll
        for (int i = 16; i < 24; i++) ldsm4(frag(2, i & 7), oa[4 * i], oa[4 * i + 1], oa[4 * i + 2], oa[4 * i + 3]);
      }
      await(st + 1);
      if (pend && granules_ok(g, tag)) { add_granules(red, g); nrx++; }
      wg_wait<0>();
      if (signaller && s < 7) mbar_arrive_cluster(empty_c + 8 * (st & 3));
      pend = nrx < s - 1;
      if (pend) fetch(g, nrx);
      half_step(s, IC<1>(), true);
      if (s == 0) bar_arrive(BAR_OA, 352);
      await(st + 2);
      wg_wait<0>();
      if (signaller && s < 7) mbar_arrive_cluster(empty_c + 8 * (st & 3) + 8);
      pin(acc);
      prof(wg, 12 + s);
      uint4* p = xch + (s == 0 ? 56 + hs : ((hs + s) & 7) * 7 + s - 1) * (2 * 4 * 128);
#pragma unroll
      for (int i = 0; i < 4; i++)
        st_gran(p + i * 128, (pack2(acc[8 * i], acc[8 * i + 1]) & ~1u) | tag, pack2(acc[8 * i + 2], acc[8 * i + 3]),
                pack2(acc[8 * i + 4], acc[8 * i + 5]), pack2(acc[8 * i + 6], acc[8 * i + 7]));
    }
    float gf[32], xf[32];
    {
      const int s = 8;
      uint32_t g2[16], xv[16], gt[16];
      half_step(s, IC<0>(), true);
      if (pend && granules_ok(g, tag)) { add_granules(red, g); nrx++; }
      await(NST_Q + NST_KV + NST_O - 1);
      mbar_wait(cx.sb + SM_BAR_XG, 0);
      wg_wait<0>();
      fetch(g, nrx);
#pragma unroll
      for (int i = 0; i < 16; i++) {
        const uint8_t* p = cx.sp + (lr0 + (i & 1) * 8) * 144 + (i >> 1) * 16 + c * 4;
        xv[i] = *(const uint32_t*)(p + SM_XO);
        gt[i] = *(const uint32_t*)(p + SM_GO);
      }
      half_step(s, IC<1>(), wg == 0);
      fetch(g2, 7);
      int last = 8;
      const bool two = nrx < 7;
      if (granules_ok(g, tag)) { add_granules(red, g); nrx++; }
#pragma unroll
      for (int i = 0; i < 16; i++) {
        gf[2 * i] = bf_lo(gt[i]); gf[2 * i + 1] = bf_hi(gt[i]);
        xf[2 * i] = bf_lo(xv[i]); xf[2 * i + 1] = bf_hi(xv[i]);
      }
      wg_wait<0>();
      pin(acc);
#pragma unroll
      for (int i = 0; i < 32; i++) red[i] += acc[i];
      pin(red); pin(gf); pin(xf);
      block_fence(60, zero);
      if (two && granules_ok(g2, tag)) { add_granules(red, g2); last = 7; }
#pragma unroll 1
      for (int spins = 0; nrx < last && spins < (1 << 16); spins++) {
        fetch(g, nrx);
        if (granules_ok(g, tag)) { add_granules(red, g); nrx++; }
      }
    }
    prof(wg, 20);
    const uint32_t ot = ring + 2 * STAGE + cw * (16 * 144);
    uint32_t ow[16];
#pragma unroll
    for (int i = 0; i < 16; i++) ow[i] = pack2(fmaf(red[2 * i], gf[2 * i], xf[2 * i]), fmaf(red[2 * i + 1], gf[2 * i + 1], xf[2 * i + 1]));
#pragma unroll
    for (int i = 0; i < 4; i++)
      stsm4(ot + (lane & 15) * 144 + (2 * i + (lane >> 4)) * 16, ow[4 * i], ow[4 * i + 1], ow[4 * i + 2], ow[4 * i + 3]);
    __syncwarp();
#pragma unroll
    for (int i = 0; i < 4; i++) {
      uint4 v;
      lds128(ot + (i * 4 + (lane >> 3)) * 144 + (lane & 7) * 16, v.x, v.y, v.z, v.w);
      at<uint4>(out, ((qb * 128 + cw * 16 + (lane >> 3)) * DM + hs * 64 + (lane & 7) * 8) * 2)[i * (4 * DM / 8)] = v;
    }
    prof(wg, 22);
  }
}

constexpr int FST_X = 24, FST_END = FST_X + 14 * 12;
__device__ __forceinline__ void ffn_producer(const Ctx& cx, int f, const CUtensorMap* tmX, const CUtensorMap* tmG,
                                             const CUtensorMap* tmU, const CUtensorMap* tmD) {
  const uint32_t full = cx.sb + SM_FULL, empty = cx.sb + SM_EMPTY;
  int pair = -2, u = 0;
#pragma unroll 1
  for (int st = 0; st < FST_END; st++) {
    const uint32_t sl = st & 7;
    const int unit = pair * 2 + (u & 1), k = u >> 1, k3 = k >= 3 ? k - 3 : k;
    if (unit < 27) {
      mbar_wait(empty + 8 * sl, ((st >> 3) & 1) ^ 1);
      mbar_expect_tx(full + 8 * sl, FSTAGE);
      if (pair < 0) tma3d(cx.sb + sl * FSTAGE, tmX, f * 512 + ((pair + 2) * 4 + (k >= 3) * 2 + (u & 1)) * 64, k3 * 3, full + 8 * sl);
      else if (pair < 9) tma2d_stream(cx.sb + sl * FSTAGE, k < 3 ? tmG : tmU, f * 1152 + unit * 64, k3 * 192, full + 8 * sl);
      else tma2d_stream(cx.sb + sl * FSTAGE, tmD, (unit - 18) * 64, f * 1152 + k * 192, full + 8 * sl);
    }
    if (++u == 12) { u = 0; pair++; }
  }
}

__device__ __forceinline__ void ffn_consumer(const Ctx& cx, int f, int wg, int cw, int lane, const __nv_bfloat16* x,
                                             const __nv_bfloat16* w_r) {
  const int r = lane >> 2, c = lane & 3, tid = cw * 32 + lane;
  unsigned e = 0;
  if (tid == 0) {
    e = cx.gs->launch[blockIdx.x];
    cx.gs->launch[blockIdx.x] = e + 1;
    *(unsigned*)(cx.sp + SM_TAG) = e;
  }
  if (tid < 72) *(uint4*)(cx.sp + SM_H + tid * 16) = *(const uint4*)(w_r + tid * 8);
  bar_sync(3, 256);
  prof(wg, 0);
  const uint32_t full = cx.sb + SM_FULL, empty = cx.sb + SM_EMPTY;
  const bool signaller = (tid & 127) == 0;
#pragma unroll 1
  for (int b = wg; b < 8; b += 2) {
    const int row0 = f * 512 + b * 64 + (cw & 3) * 16 + r;
    const uint32_t lo = ((cw & 3) * 16 + (lane & 15)) * 128 + (((lane >> 4) ^ (lane & 7)) << 4);
    LnAcc a;
    a.clear();
#pragma unroll 1
    for (int bx = 0; bx < 9; bx++) {
      const int st = (b >> 1) * 6 + (bx / 3) * 2 + wg;
      if (bx % 3 == 0) mbar_wait(full + 8 * (st & 7), (st >> 3) & 1);
#pragma unroll
      for (int k = 0; k < 4; k++) {
        uint32_t x0, x1, x2, x3;
        ldsm4(cx.sb + (st & 7) * FSTAGE + (bx % 3) * 8192 + (lo ^ (k << 5)), x0, x1, x2, x3);
        ln_accum1(a, k & 1, x0, x1, x2, x3);
      }
    }
    prof(wg, 8 + (b >> 1) * 3);
    float mean0, rstd0, mean1, rstd1;
    ln_stats(a, lane, mean0, rstd0, mean1, rstd1);
    prof(wg, 9 + (b >> 1) * 3);
    const uint32_t mm0 = pack2(mean0, mean0), mm1 = pack2(mean1, mean1);
    float d0[4] = {0, 0, 0, 0}, d1[4] = {0, 0, 0, 0};
#pragma unroll 1
    for (int bx = 0; bx < 9; bx++) {
      const int st = (b >> 1) * 6 + (bx / 3) * 2 + wg;
#pragma unroll
      for (int k = 0; k < 4; k++) {
        uint32_t n[4];
        ldsm4(cx.sb + (st & 7) * FSTAGE + (bx % 3) * 8192 + (lo ^ (k << 5)), n[0], n[1], n[2], n[3]);
        const uint8_t* wp = cx.sp + SM_H + (bx * 4 + k) * 32 + 4 * c;
#pragma unroll
        for (int i = 0; i < 4; i++) {
          const uint32_t t = sub2(n[i], (i & 1) ? mm1 : mm0);
          const float rs = (i & 1) ? rstd1 : rstd0;
          n[i] = pack2(bf_lo(t) * rs, bf_hi(t) * rs);
        }
        if (k & 1) hmma_k16(d1, n[0], n[1], n[2], n[3], *(const uint32_t*)wp, *(const uint32_t*)(wp + 16));
        else hmma_k16(d0, n[0], n[1], n[2], n[3], *(const uint32_t*)wp, *(const uint32_t*)(wp + 16));
      }
    }
    prof(wg, 10 + (b >> 1) * 3);
    bar_sync(4 + wg, 128);
    if (signaller) {
#pragma unroll
      for (int i = 0; i < 3; i++) mbar_arrive(empty + 8 * (((b >> 1) * 6 + i * 2 + wg) & 7));
    }
    if (c == 0) {
      cx.gs->r[row0] = bfr(d0[0] + d1[0]);
      cx.gs->r[row0 + 8] = bfr(d0[2] + d1[2]);
      cx.gs->stats[row0] = make_float2(mean0, rstd0);
      cx.gs->stats[row0 + 8] = make_float2(mean1, rstd1);
    }
  }
  prof(wg, 1);
  bar_sync(3, 256);
  e = *(const unsigned*)(cx.sp + SM_TAG);
  if (tid == 0) {
    atom_add_acq_rel(&cx.gs->rcnt);
#pragma unroll 1
    for (int n = 0; n < (1 << 16) && (int)(ld_acquire(&cx.gs->rcnt) - 4 * (e + 1)) < 0; n++) {}
  }
  bar_sync(3, 256);
  prof(wg, 2);
  uint32_t key[8];
#pragma unroll
  for (int i = 0; i < 8; i++) {
    const int row = i * 256 + tid;
    const uint32_t b = __float_as_uint(__ldcg(&cx.gs->r[row])) >> 16;
    key[i] = (((b & 0x8000u) ? (~b & 0xFFFFu) : (b | 0x8000u)) << 16) | (uint32_t)(0xFFFF - row);
  }
  int mysel = 0;
#pragma unroll 1
  for (int k = 0; k < TOPC; k++) {
    uint32_t m = key[0];
#pragma unroll
    for (int i = 1; i < 8; i++) m = max(m, key[i]);
    m = __reduce_max_sync(0xffffffffu, m);
    uint32_t* tk = (uint32_t*)(cx.sp + SM_TOPK) + (k & 1) * 8;
    if (lane == 0) tk[cw] = m;
    bar_sync(3, 256);
    m = __reduce_max_sync(0xffffffffu, tk[lane & 7]);
#pragma unroll
    for (int i = 0; i < 8; i++) if (key[i] == m) key[i] = 0;
    if (k == cw) mysel = 0xFFFF - (int)(m & 0xFFFF);
  }
  {
    const float2 st = __ldcg(&cx.gs->stats[mysel]);
    const uint32_t mm = pack2(st.x, st.x);
#pragma unroll 3
    for (int i = 0; i < 9; i++) {
      const uint32_t t = sub2(*(const uint32_t*)(x + (size_t)mysel * DM + i * 64 + 2 * lane), mm);
      *(uint32_t*)(cx.sp + SM_XSEL + i * 1024 + cw * 128 + (((lane >> 2) ^ cw) << 4) + (lane & 3) * 4) =
          pack2(bf_lo(t) * st.y, bf_hi(t) * st.y);
    }
    if (lane == 0) *(int*)(cx.sp + SM_IDX + 4 * cw) = mysel;
  }
  asm volatile("fence.proxy.async.shared::cta;" ::: "memory");
  bar_sync(3, 256);
  prof(wg, 3);
  auto run = [&](float (&acc)[4], int st, int n, uint32_t b) {
#pragma unroll 1
    for (int u = 0; u < n; u++, st += 2, b += 3072) {
      const uint32_t sl = st & 7;
      mbar_wait(full + 8 * sl, (st >> 3) & 1);
      wg_fence();
      const uint64_t da = mkdesc(cx.sb + sl * FSTAGE, 16), db = mkdesc(b, 16);
#pragma unroll
      for (int k = 0; k < 12; k++) mma_n8(acc, da + k * 128, db + (k >> 2) * 64 + (k & 3) * 2, u > 0 || k > 0);
      wg_commit();
      wg_wait<0>();
      if (signaller) mbar_arrive(empty + 8 * sl);
    }
    pin(acc);
  };
#pragma unroll 1
  for (int unit = wg; unit < 27; unit += 2) {
    if (unit >> 1 == 9) {
      asm volatile("fence.proxy.async.shared::cta;" ::: "memory");
      bar_sync(3, 256);
      prof(wg, 4);
    }
    const bool gu = unit < 18;
    float a0[4], a1[4];
#pragma unroll 1
    for (int m = 0; m < (gu ? 2 : 1); m++) {
      run(a1, FST_X + (unit >> 1) * 12 + m * 6 + wg, gu ? 3 : 6, cx.sb + (gu ? SM_XSEL : SM_H));
      if (m == 0) { a0[0] = a1[0]; a0[1] = a1[1]; a0[2] = a1[2]; a0[3] = a1[3]; }
    }
#pragma unroll
    for (int i = 0; i < 4; i++) {
      const int fl = (cw & 3) * 16 + r + (i >> 1) * 8, tok = 2 * c + (i & 1);
      if (gu) {
        const float h = bfr(silu_f(bfr(a0[i]))) * bfr(a1[i]);
        *(__nv_bfloat16*)(cx.sp + SM_H + unit * 1024 + tok * 128 + (((fl >> 3) ^ tok) << 4) + (fl & 7) * 2) = __float2bfloat16_rn(h);
      } else {
        cx.gs->ypart[(f * TOPC + tok) * DM + (unit - 18) * 64 + fl] = a1[i];
      }
    }
  }
  prof(wg, 5);
  bar_sync(3, 256);
  if (tid == 0) *(unsigned*)(cx.sp + SM_TOPK) = atom_add_acq_rel(&cx.gs->ycnt) == 4 * e + 3;
  bar_sync(3, 256);
  if (*(const unsigned*)(cx.sp + SM_TOPK)) {
    const int row = *(const int*)(cx.sp + SM_IDX + 4 * cw);
    const float rs = bfr(rcp(1.0f + ex2(-1.4426950408889634f * __ldcg(&cx.gs->r[row]))));
#pragma unroll 1
    for (int d = lane * 2; d < DM; d += 192) {
#pragma unroll
      for (int i = 0; i < 3; i++) {
        const float* p = cx.gs->ypart + cw * DM + d + i * 64;
        const float2 a = __ldcg((const float2*)p), b = __ldcg((const float2*)(p + TOPC * DM)),
                     e2 = __ldcg((const float2*)(p + 2 * TOPC * DM)), h = __ldcg((const float2*)(p + 3 * TOPC * DM));
        const uint32_t y = pack2((a.x + b.x) + (e2.x + h.x), (a.y + b.y) + (e2.y + h.y));
        const uint32_t u = pack2(bf_lo(y) * rs, bf_hi(y) * rs);
        *(float2*)(cx.gs->upd + cw * DM + d + i * 64) = make_float2(bf_lo(u), bf_hi(u));
      }
    }
    if (lane == 0) cx.gs->idx[cw] = row;
    bar_sync(3, 256);
    if (tid == 0) st_release(&cx.gs->ffn_flag, e + 1);
    prof(wg, 6);
  }
}

struct Maps { CUtensorMap m[8]; };
__global__ void __cluster_dims__(2, 1, 1) __launch_bounds__(THREADS, 1)
fused_kernel(const __nv_bfloat16* __restrict__ x, const __nv_bfloat16* __restrict__ w_r, const __nv_bfloat16* __restrict__ wq,
             const __nv_bfloat16* __restrict__ wo, __nv_bfloat16* __restrict__ out, Scratch* gs,
             const __grid_constant__ Maps maps, const __nv_bfloat16* __restrict__ kc) {
  const CUtensorMap &tmX = maps.m[0], &tmWq = maps.m[1], &tmK = maps.m[2], &tmV = maps.m[3], &tmWo = maps.m[4], &tmG = maps.m[5],
                    &tmU = maps.m[6], &tmD = maps.m[7];
  extern __shared__ __align__(1024) uint8_t smem_raw[];
  prof(0, 23, 511);
  Ctx cx;
  cx.sb = smem_u32(smem_raw);
  cx.sp = smem_raw;
  cx.gs = gs;
  cx.rank = blockIdx.x & 1;
  const int warp = __shfl_sync(0xffffffffu, threadIdx.x >> 5, 0);
  const int cluster = blockIdx.x >> 1;
  const bool is_ffn = blockIdx.x >= N_ATT_CTA;
  const int c7 = ((cluster - 36) * 37) >> 8;
  const int hs = cluster < 4 ? 4 + cluster : cluster < 36 ? (cluster - 4) >> 3 : 4 + c7;
  const int qb = (cluster < 4 ? 0 : cluster < 36 ? (cluster - 4) & 7 : cluster - 35 - 7 * c7) * 2 + cx.rank;

  extern __shared__ __align__(1024) uint8_t smem_alias[];
  const uint32_t xf = smem_u32(smem_alias) + SM_MISC + warp * 24;
  if (warp == 4 && elect_one()) prefetch_tmap(&tmX);
  if (warp == 6 && !is_ffn && elect_one()) prefetch_l2(x + (size_t)(qb * 128 + hs * 8) * DM, 8 * DM * 2);
  if (elect_one()) {
    const uint32_t cnt = warp == 3 ? 64 : (warp > 4 && warp < 8 && !is_ffn) ? 4 : 1;
#pragma unroll
    for (int i = 0; i < 3; i++) mbar_init(xf + 8 * i, cnt);
    asm volatile("fence.proxy.async.shared::cta;" ::: "memory");
    asm volatile("fence.mbarrier_init.release.cluster;" ::: "memory");
  }
  __syncwarp();
  cluster_arrive();
  if (warp == 4 && !is_ffn) {
    if (elect_one()) {
      profc(0, 28);
#pragma unroll
      for (int i = 0; i < 3; i++) {
        mbar_expect_tx(xf + 8 * i, 24576);
        tma3d(xf - SM_XFULL + SM_X + i * 24576, &tmX, qb * 128, i * 3, xf + 8 * i);
      }
      profc(0, 29);
    }
  } else if (warp > 8 && elect_one()) {
    prefetch_tmap(&tmX + (is_ffn ? warp - 4 : warp - 8));
  }
  __syncwarp();

  if (warp < 4) {
    asm volatile("setmaxnreg.dec.sync.aligned.u32 24;");
    cluster_wait();
    prof(0, 24, 511);
    if (warp == 0) {
      if (!is_ffn) attn_producer(cx, qb, hs, &tmX, &tmK, &tmV, &tmWq, &tmWo);
      else if (elect_one()) ffn_producer(cx, blockIdx.x - N_ATT_CTA, &tmX, &tmG, &tmU, &tmD);
      prof(0, 25, 511);
    } else if (!is_ffn) {
      attn_gate(cx, qb, hs, threadIdx.x - 32, x);
      if (warp == 1) attn_helper(cx, qb, hs, read_lane(), x, wo);
      else { bar_arrive(BAR_HELPER, 128); attn_stage_xg(cx, qb, hs, threadIdx.x - 64, x); }
      attn_finish8(cx, qb, hs, warp - 1, read_lane(), out);

    }
    __syncwarp();
    cluster_arrive();
    cluster_wait();
  } else {
    asm volatile("setmaxnreg.inc.sync.aligned.u32 240;");
    cluster_wait();
    const int cw = warp - 4, wg = cw >> 2;
    if (is_ffn) ffn_consumer(cx, blockIdx.x - N_ATT_CTA, wg, cw, read_lane(), x, w_r);
    else attn_consumer(cx, qb, hs, wg, cw, read_lane(), x, kc, out);
  }
}

typedef CUresult (*EncodeFn)(CUtensorMap*, CUtensorMapDataType, cuuint32_t, void*, const cuuint64_t*, const cuuint64_t*,
                             const cuuint32_t*, const cuuint32_t*, CUtensorMapInterleave, CUtensorMapSwizzle,
                             CUtensorMapL2promotion, CUtensorMapFloatOOBfill);

void encode(EncodeFn fn, CUtensorMap* m, const void* p, int rank, const cuuint64_t* dims, const cuuint64_t* strides,
            const cuuint32_t* box) {
  const cuuint32_t es[5] = {1, 1, 1, 1, 1};
  fn(m, CU_TENSOR_MAP_DATA_TYPE_BFLOAT16, rank, const_cast<void*>(p), dims, strides, box, es, CU_TENSOR_MAP_INTERLEAVE_NONE,
     CU_TENSOR_MAP_SWIZZLE_128B, CU_TENSOR_MAP_L2_PROMOTION_L2_128B, CU_TENSOR_MAP_FLOAT_OOB_FILL_NONE);
}
void encode2d(EncodeFn fn, CUtensorMap* m, const void* p, uint64_t rows, uint64_t cols, uint32_t box_rows) {
  const cuuint64_t dims[2] = {cols, rows}, strides[1] = {cols * 2};
  const cuuint32_t box[2] = {64, box_rows};
  encode(fn, m, p, 2, dims, strides, box);
}

}

extern "C" void kernel_launch(void* const* d_in, const int* in_sizes, int n_in, void* d_out, int out_size) {
  (void)in_sizes; (void)n_in; (void)out_size;
  void* fnp = nullptr;
  cudaDriverEntryPointQueryResult qr;
  cudaGetDriverEntryPoint("cuTensorMapEncodeTiled", &fnp, cudaEnableDefault, &qr);
  EncodeFn fn = (EncodeFn)fnp;
  Maps maps;
  CUtensorMap &tmX = maps.m[0], &tmWq = maps.m[1], &tmK = maps.m[2], &tmV = maps.m[3], &tmWo = maps.m[4], &tmG = maps.m[5],
              &tmU = maps.m[6], &tmD = maps.m[7];
  encode2d(fn, &tmK, d_in[1], 16 * SEQ, DH, 128);
  encode2d(fn, &tmV, d_in[2], 16 * SEQ, DH, 128);
  encode2d(fn, &tmWq, d_in[3], DM, 4096, 64);
  {
    const cuuint64_t dims[3] = {64, SEQ, 9}, strides[2] = {DM * 2, 128};
    const cuuint32_t box[3] = {64, 64, 3};
    encode(fn, &tmX, d_in[0], 3, dims, strides, box);
  }
  encode2d(fn, &tmWo, d_in[4], 4096, DM, 128);
  encode2d(fn, &tmG, d_in[7], DM, FF, 192);
  encode2d(fn, &tmU, d_in[8], DM, FF, 192);
  encode2d(fn, &tmD, d_in[9], FF, DM, 192);
  cudaFuncSetAttribute(fused_kernel, cudaFuncAttributeMaxDynamicSharedMemorySize, SM_TOTAL);
  void* gs = nullptr;
  cudaGetSymbolAddress(&gs, g_scratch);
  fused_kernel<<<N_CTA, THREADS, SM_TOTAL>>>((const __nv_bfloat16*)d_in[0], (const __nv_bfloat16*)d_in[6], (const __nv_bfloat16*)d_in[3],
                                            (const __nv_bfloat16*)d_in[4], (__nv_bfloat16*)d_out, (Scratch*)gs, maps, (const __nv_bfloat16*)d_in[1]);
}
```

```cpp
#include <cuda_runtime.h>
#include <cuda_bf16.h>
#include <cuda.h>
#include <stdint.h>

namespace {

constexpr int SEQ = 2048, DM = 576, DH = 128, FF = 4608, TOPC = 8;
constexpr int N_ATT_CTA = 128, N_CTA = 132;
constexpr int THREADS = 384;

constexpr uint32_t SM_RING = 0;
constexpr uint32_t STAGE = 32768;
constexpr uint32_t SM_SLOT = 131072;
constexpr uint32_t FSTAGE = 24576;
constexpr uint32_t SM_XSEL = 196608;
constexpr uint32_t SM_H = 205824;
constexpr uint32_t SM_MISC = 229376;
constexpr uint32_t SM_FULL = SM_MISC, SM_BAR_MISC = SM_MISC + 64, SM_BAR_XG = SM_MISC + 72, SM_XFULL = SM_MISC + 96,
                   SM_EMPTY = SM_MISC + 120, SM_TAG = SM_MISC + 288, SM_IDX = SM_MISC + 304, SM_TOPK = SM_MISC + 336,
                   SM_STATS = SM_MISC + 400;
constexpr uint32_t SM_TOTAL = SM_MISC + 1424;
constexpr uint32_t SM_X = SM_MISC - 147456;

constexpr int BAR_GATE = 6, BAR_HELPER = 7, BAR_OA = 8;
constexpr int NST_Q = 20, NST_KV = 128, NST_O = 18;
#define X_ORDER 0
#define X_PF 3
#define X_PFQ 2
#define X_REL 0
#define X_N1 4
#define X_SPLIT 44
#define X_PARK 6
#define X_HO 9
#define X_C0 32
#define X_C1 56
constexpr float SM_SCALE_LOG2 = 0.08838834764831845f * 1.4426950408889634f;

struct Scratch {
  uint4 part[16 * 64 * 2 * 4 * 128];
  uint4 gate[SEQ * DM / 8];
  float r[SEQ];
  float2 stats[SEQ];
  float ypart[4 * TOPC * DM];
  float upd[TOPC * DM];
  int idx[32];
  unsigned launch[160];
  unsigned rcnt, pad0[31], ycnt, pad1[31], ffn_flag, pad2[31];
};
__device__ __align__(1024) Scratch g_scratch;

__device__ __forceinline__ void profq(int) {}
__device__ __forceinline__ void prof(int, int, int = 0) {}
__device__ __forceinline__ void profc(int, int) {}

__device__ __forceinline__ uint32_t smem_u32(const void* p) { return (uint32_t)__cvta_generic_to_shared(p); }
__device__ __forceinline__ void mbar_init(uint32_t bar, uint32_t cnt) {
  asm volatile("mbarrier.init.shared::cta.b64 [%0], %1;" ::"r"(bar), "r"(cnt) : "memory");
}
__device__ __forceinline__ void mbar_expect_tx(uint32_t bar, uint32_t bytes) {
  asm volatile("mbarrier.arrive.expect_tx.shared::cta.b64 _, [%0], %1;" ::"r"(bar), "r"(bytes) : "memory");
}
__device__ __forceinline__ void mbar_arrive(uint32_t bar) {
  asm volatile("mbarrier.arrive.shared::cta.b64 _, [%0];" ::"r"(bar) : "memory");
}
__device__ __forceinline__ void mbar_arrive_cluster(uint32_t bar_cluster_addr) {
  asm volatile("mbarrier.arrive.shared::cluster.b64 _, [%0];" ::"r"(bar_cluster_addr) : "memory");
}
template <int ID>
__device__ __forceinline__ void mbar_arrive_cluster_now(uint32_t bar_cluster_addr, bool pred, uint32_t zero) {
  asm volatile("{\n.reg .pred p, q;\nsetp.ne.u32 p, %1, 0;\nsetp.eq.u32 q, %2, %3;\n"
               "ARR_LOOP:\n@p mbarrier.arrive.shared::cluster.b64 _, [%0];\n@q bra.uni ARR_LOOP;\n}"
               ::"r"(bar_cluster_addr), "r"((uint32_t)pred), "r"(zero), "n"(ID) : "memory");
}
__device__ __forceinline__ void block_fence(int id, uint32_t zero = blockIdx.y) {
  asm volatile("{\n.reg .pred q;\nsetp.eq.u32 q, %0, %1;\nBF_LOOP:\n@q st.volatile.shared.u32 [%0], %0;\n@q bra.uni BF_LOOP;\n}"
               ::"r"(zero), "r"(id) : "memory");
}
__device__ __forceinline__ bool mbar_test(uint32_t bar, uint32_t parity) {
  uint32_t ok;
  asm volatile("{\n.reg .pred p;\nmbarrier.test_wait.parity.shared::cta.b64 p, [%1], %2;\nselp.u32 %0, 1, 0, p;\n}"
               : "=r"(ok) : "r"(bar), "r"(parity) : "memory");
  return ok;
}
__device__ __forceinline__ void mbar_wait(uint32_t bar, uint32_t parity) {
  asm volatile("{\n.reg .pred p, q;\n.reg .u32 n;\nmov.u32 n, 0;\n"
               "WAIT_LOOP:\nmbarrier.try_wait.parity.shared::cta.b64 p, [%0], %1;\n"
               "add.u32 n, n, 1;\nsetp.lt.u32 q, n, 4194304;\nand.pred q, q, !p;\n@q bra WAIT_LOOP;\n}"
               ::"r"(bar), "r"(parity) : "memory");
}
__device__ __forceinline__ uint32_t mapa(uint32_t addr, uint32_t rank) {
  uint32_t r;
  asm volatile("mapa.shared::cluster.u32 %0, %1, %2;" : "=r"(r) : "r"(addr), "r"(rank));
  return r;
}
__device__ __forceinline__ void cluster_arrive() { asm volatile("barrier.cluster.arrive.relaxed.aligned;" ::: "memory"); }
__device__ __forceinline__ bool elect_one() {
  uint32_t p;
  asm volatile("{\n.reg .pred p;\nelect.sync _|p, 0xffffffff;\nselp.u32 %0, 1, 0, p;\n}" : "=r"(p));
  return p;
}
__device__ __forceinline__ int read_lane() { return threadIdx.x & 31; }
__device__ __forceinline__ void cluster_wait() { asm volatile("barrier.cluster.wait.acquire.aligned;" ::: "memory"); }
__device__ __forceinline__ void bar_sync(int id, int n) { asm volatile("barrier.cta.sync %0, %1;" ::"r"(id), "r"(n) : "memory"); }
__device__ __forceinline__ void bar_arrive(int id, int n) { asm volatile("barrier.cta.arrive %0, %1;" ::"r"(id), "r"(n) : "memory"); }

__device__ __forceinline__ uint64_t policy_evict_first() {
  uint64_t p;
  asm("createpolicy.fractional.L2::evict_first.b64 %0, 1.0;" : "=l"(p));
  return p;
}
__device__ __forceinline__ uint64_t policy_evict_normal() {
  uint64_t p;
  asm("createpolicy.fractional.L2::evict_normal.b64 %0, 1.0;" : "=l"(p));
  return p;
}
__device__ __forceinline__ void tma2d_mc(uint32_t dst, const CUtensorMap* tm, int c0, int c1, uint32_t bar, uint64_t pol) {
  asm volatile("cp.async.bulk.tensor.2d.shared::cluster.global.mbarrier::complete_tx::bytes.multicast::cluster.L2::cache_hint"
               " [%0], [%1, {%2, %3}], [%4], %5, %6;"
               ::"r"(dst), "l"(tm), "r"(c0), "r"(c1), "r"(bar), "h"((uint16_t)3), "l"(pol) : "memory");
}
__device__ __forceinline__ void tma3d(uint32_t dst, const CUtensorMap* tm, int c1, int c2, uint32_t bar) {
  asm volatile("cp.async.bulk.tensor.3d.shared::cluster.global.mbarrier::complete_tx::bytes [%0], [%1, {%2, %3, %4}], [%5];"
               ::"r"(dst), "l"(tm), "r"(0), "r"(c1), "r"(c2), "r"(bar) : "memory");
}
__device__ __forceinline__ void tma2d_stream(uint32_t dst, const CUtensorMap* tm, int c0, int c1, uint32_t bar) {
  asm volatile("{\n.reg .b64 pol;\ncreatepolicy.fractional.L2::evict_first.b64 pol, 1.0;\n"
               "cp.async.bulk.tensor.2d.shared::cluster.global.mbarrier::complete_tx::bytes.L2::cache_hint [%0], [%1, {%2, %3}], [%4], pol;\n}"
               ::"r"(dst), "l"(tm), "r"(c0), "r"(c1), "r"(bar) : "memory");
}
__device__ __forceinline__ void tma2d_prefetch(const CUtensorMap* tm, int c0, int c1) {
  asm volatile("cp.async.bulk.prefetch.tensor.2d.L2.global [%0, {%1, %2}];" ::"l"(tm), "r"(c0), "r"(c1) : "memory");
}
__device__ __forceinline__ void prefetch_l2(const void* p, uint32_t bytes) {
  asm volatile("cp.async.bulk.prefetch.L2.global [%0], %1;" ::"l"(p), "r"(bytes) : "memory");
}
__device__ __forceinline__ void prefetch_tmap(const CUtensorMap* tm) {
  asm volatile("prefetch.tensormap [%0];" ::"l"(tm) : "memory");
}

__device__ __forceinline__ void wg_fence() { asm volatile("wgmma.fence.sync.aligned;" ::: "memory"); }
__device__ __forceinline__ void wg_commit() { asm volatile("wgmma.commit_group.sync.aligned;" ::: "memory"); }
template <int N> __device__ __forceinline__ void wg_wait() { asm volatile("wgmma.wait_group.sync.aligned %0;" ::"n"(N) : "memory"); }

__device__ __forceinline__ uint64_t mkdesc(uint32_t addr, uint32_t lbo_bytes) {
  return (uint64_t)(((addr & 0x3FFFF) >> 4) | ((lbo_bytes >> 4) << 16)) | ((uint64_t)0x40000040u << 32);
}
template <int N> __device__ __forceinline__ void pin(float (&a)[N]) {
#pragma unroll
  for (int i = 0; i < N; i++) asm volatile("" : "+f"(a[i])::"memory");
}
template <int N> __device__ __forceinline__ void pin(uint32_t (&a)[N]) {
#pragma unroll
  for (int i = 0; i < N; i++) asm volatile("" : "+r"(a[i])::"memory");
}

#define F8(d, o) "+f"(d[o]), "+f"(d[o + 1]), "+f"(d[o + 2]), "+f"(d[o + 3]), "+f"(d[o + 4]), "+f"(d[o + 5]), "+f"(d[o + 6]), "+f"(d[o + 7])
#define R32A "%0, %1, %2, %3, %4, %5, %6, %7, %8, %9, %10, %11, %12, %13, %14, %15, %16, %17, %18, %19, %20, %21, %22, %23, %24, %25, %26, %27, %28, %29, %30, %31"
#define R32B "%32, %33, %34, %35, %36, %37, %38, %39, %40, %41, %42, %43, %44, %45, %46, %47, %48, %49, %50, %51, %52, %53, %54, %55, %56, %57, %58, %59, %60, %61, %62, %63"

template <int TB>
__device__ __forceinline__ void mma_n128(float (&d)[64], uint32_t a0, uint32_t a1, uint32_t a2, uint32_t a3, uint64_t db, int acc) {
  asm volatile("{\n.reg .pred p;\nsetp.ne.b32 p, %69, 0;\n"
               "wgmma.mma_async.sync.aligned.m64n128k16.f32.bf16.bf16 {" R32A ", " R32B "}, {%64, %65, %66, %67}, %68, p, 1, 1, %70;\n}\n"
               : F8(d, 0), F8(d, 8), F8(d, 16), F8(d, 24), F8(d, 32), F8(d, 40), F8(d, 48), F8(d, 56)
               : "r"(a0), "r"(a1), "r"(a2), "r"(a3), "l"(db), "r"(acc), "n"(TB));
}
template <int TB>
__device__ __forceinline__ void mma_n128_ss(float (&d)[64], uint64_t da, uint64_t db, int acc) {
  asm volatile("{\n.reg .pred p;\nsetp.ne.b32 p, %66, 0;\n"
               "wgmma.mma_async.sync.aligned.m64n128k16.f32.bf16.bf16 {" R32A ", " R32B "}, %64, %65, p, 1, 1, 0, %67;\n}\n"
               : F8(d, 0), F8(d, 8), F8(d, 16), F8(d, 24), F8(d, 32), F8(d, 40), F8(d, 48), F8(d, 56)
               : "l"(da), "l"(db), "r"(acc), "n"(TB));
}
__device__ __forceinline__ void mma_n64t(float (&d)[32], uint32_t a0, uint32_t a1, uint32_t a2, uint32_t a3, uint64_t db, int acc) {
  asm volatile("{\n.reg .pred p;\nsetp.ne.b32 p, %37, 0;\n"
               "wgmma.mma_async.sync.aligned.m64n64k16.f32.bf16.bf16 {" R32A "}, {%32, %33, %34, %35}, %36, p, 1, 1, 1;\n}\n"
               : F8(d, 0), F8(d, 8), F8(d, 16), F8(d, 24)
               : "r"(a0), "r"(a1), "r"(a2), "r"(a3), "l"(db), "r"(acc));
}
__device__ __forceinline__ void mma_n8(float (&d)[4], uint64_t da, uint64_t db, int acc) {
  asm volatile("{\n.reg .pred p;\nsetp.ne.b32 p, %6, 0;\n"
               "wgmma.mma_async.sync.aligned.m64n8k16.f32.bf16.bf16 {%0, %1, %2, %3}, %4, %5, p, 1, 1, 1, 0;\n}\n"
               : "+f"(d[0]), "+f"(d[1]), "+f"(d[2]), "+f"(d[3])
               : "l"(da), "l"(db), "r"(acc));
}
__device__ __forceinline__ void hmma_k8(float (&d)[4], uint32_t a0, uint32_t a1, uint32_t b0) {
  asm volatile("mma.sync.aligned.m16n8k8.row.col.f32.bf16.bf16.f32 {%0, %1, %2, %3}, {%4, %5}, {%6}, {%0, %1, %2, %3};"
               : "+f"(d[0]), "+f"(d[1]), "+f"(d[2]), "+f"(d[3]) : "r"(a0), "r"(a1), "r"(b0));
}
__device__ __forceinline__ void hmma_k16(float (&d)[4], uint32_t a0, uint32_t a1, uint32_t a2, uint32_t a3, uint32_t b0, uint32_t b1) {
  asm volatile("mma.sync.aligned.m16n8k16.row.col.f32.bf16.bf16.f32 {%0, %1, %2, %3}, {%4, %5, %6, %7}, {%8, %9}, {%0, %1, %2, %3};"
               : "+f"(d[0]), "+f"(d[1]), "+f"(d[2]), "+f"(d[3]) : "r"(a0), "r"(a1), "r"(a2), "r"(a3), "r"(b0), "r"(b1));
}

__device__ __forceinline__ uint32_t pack2(float lo, float hi) {
  uint32_t r;
  asm("cvt.rn.bf16x2.f32 %0, %1, %2;" : "=r"(r) : "f"(hi), "f"(lo));
  return r;
}
__device__ __forceinline__ float bf_lo(uint32_t w) { return __uint_as_float(w << 16); }
__device__ __forceinline__ float bf_hi(uint32_t w) { return __uint_as_float(w & 0xFFFF0000u); }
__device__ __forceinline__ float bfr(float x) { return __bfloat162float(__float2bfloat16_rn(x)); }
__device__ __forceinline__ uint32_t sub2(uint32_t a, uint32_t b) {
  uint32_t r;
  asm("sub.rn.bf16x2 %0, %1, %2;" : "=r"(r) : "r"(a), "r"(b));
  return r;
}
__device__ __forceinline__ uint32_t add2(uint32_t a, uint32_t b) {
  uint32_t r;
  asm("add.rn.bf16x2 %0, %1, %2;" : "=r"(r) : "r"(a), "r"(b));
  return r;
}
__device__ __forceinline__ float ex2(float x) {
  float r;
  asm("ex2.approx.ftz.f32 %0, %1;" : "=f"(r) : "f"(x));
  return r;
}
__device__ __forceinline__ float rcp(float x) {
  float r;
  asm("rcp.approx.ftz.f32 %0, %1;" : "=f"(r) : "f"(x));
  return r;
}
__device__ __forceinline__ float silu_f(float t) { return t * rcp(1.0f + ex2(-1.4426950408889634f * t)); }
__device__ __forceinline__ void sts128(uint32_t a, uint32_t x, uint32_t y, uint32_t z, uint32_t w) {
  asm volatile("st.shared.v4.u32 [%0], {%1, %2, %3, %4};" ::"r"(a), "r"(x), "r"(y), "r"(z), "r"(w) : "memory");
}
__device__ __forceinline__ void lds128(uint32_t a, uint32_t& x, uint32_t& y, uint32_t& z, uint32_t& w) {
  asm volatile("ld.shared.v4.u32 {%0, %1, %2, %3}, [%4];" : "=r"(x), "=r"(y), "=r"(z), "=r"(w) : "r"(a) : "memory");
}
__device__ __forceinline__ void ldsm4(uint32_t a, uint32_t& x, uint32_t& y, uint32_t& z, uint32_t& w) {
  asm volatile("ldmatrix.sync.aligned.m8n8.x4.shared.b16 {%0, %1, %2, %3}, [%4];" : "=r"(x), "=r"(y), "=r"(z), "=r"(w) : "r"(a) : "memory");
}
__device__ __forceinline__ void st_gran(uint4* p, uint32_t x, uint32_t y, uint32_t z, uint32_t w) {
  asm volatile("st.relaxed.gpu.global.v4.b32 [%0], {%1, %2, %3, %4};" ::"l"(p), "r"(x), "r"(y), "r"(z), "r"(w) : "memory");
}
__device__ __forceinline__ void ld_gran(const uint4* p, uint32_t& x, uint32_t& y, uint32_t& z, uint32_t& w) {
  asm volatile("ld.relaxed.gpu.global.v4.b32 {%0, %1, %2, %3}, [%4];" : "=r"(x), "=r"(y), "=r"(z), "=r"(w) : "l"(p) : "memory");
}
__device__ __forceinline__ void stsm4(uint32_t a, uint32_t x, uint32_t y, uint32_t z, uint32_t w) {
  asm volatile("stmatrix.sync.aligned.m8n8.x4.shared.b16 [%0], {%1, %2, %3, %4};" ::"r"(a), "r"(x), "r"(y), "r"(z), "r"(w) : "memory");
}
__device__ __forceinline__ void cp16(uint32_t dst, const void* src) {
  asm volatile("cp.async.cg.shared.global [%0], [%1], 16;" ::"r"(dst), "l"(src) : "memory");
}
template <class T>
__device__ __forceinline__ T* at(const void* base, uint32_t off) {
  uint64_t r;
  asm("{\n.reg .u32 lo, hi;\nmov.b64 {lo, hi}, %1;\nadd.cc.u32 lo, lo, %2;\naddc.u32 hi, hi, 0;\nmov.b64 %0, {lo, hi};\n}"
      : "=l"(r) : "l"(base), "r"(off));
  return (T*)__cvta_global_to_generic(r);
}
__device__ __forceinline__ void cp_wait_all() { asm volatile("cp.async.wait_all;" ::: "memory"); }
__device__ __forceinline__ void add_granules(float (&red)[32], const uint32_t (&g)[16]) {
#pragma unroll
  for (int i = 0; i < 16; i++) { red[2 * i] += bf_lo((i & 3) ? g[i] : g[i] & ~1u); red[2 * i + 1] += bf_hi(g[i]); }
}
__device__ __forceinline__ bool granules_ok(const uint32_t (&g)[16], uint32_t tag) {
  return __all_sync(0xffffffffu, (((g[0] ^ tag) | (g[4] ^ tag) | (g[8] ^ tag) | (g[12] ^ tag)) & 1) == 0);
}
__device__ __forceinline__ unsigned ld_acquire(const unsigned* p) {
  unsigned v;
  asm volatile("ld.acquire.gpu.global.u32 %0, [%1];" : "=r"(v) : "l"(p) : "memory");
  return v;
}
__device__ __forceinline__ unsigned atom_add_acq_rel(unsigned* p) {
  unsigned v;
  asm volatile("atom.acq_rel.gpu.global.add.u32 %0, [%1], 1;" : "=r"(v) : "l"(p) : "memory");
  return v;
}
__device__ __forceinline__ void st_release(unsigned* p, unsigned v) {
  asm volatile("st.release.gpu.global.u32 [%0], %1;" ::"l"(p), "r"(v) : "memory");
}

struct LnAcc {
  float sm[2][4], sq[8][4];
  __device__ __forceinline__ void clear() {
#pragma unroll
    for (int i = 0; i < 4; i++) {
      sm[0][i] = sm[1][i] = 0.f;
#pragma unroll
      for (int j = 0; j < 8; j++) sq[j][i] = 0.f;
    }
  }
};
template <int K0, int K1>
__device__ __forceinline__ void ln_fetch(uint32_t (&xa)[144], uint32_t boxes, uint32_t lo) {
#pragma unroll
  for (int k = K0; k < K1; k++) ldsm4(boxes + (k >> 2) * 8192 + (lo ^ ((k & 3) << 5)), xa[4 * k], xa[4 * k + 1], xa[4 * k + 2], xa[4 * k + 3]);
}
__device__ __forceinline__ void ln_accum1(LnAcc& a, int h, uint32_t x0, uint32_t x1, uint32_t x2, uint32_t x3) {
  const uint32_t ONES = 0x3F803F80u;
  hmma_k16(a.sm[h], x0, x1, x2, x3, ONES, ONES);
  hmma_k8(a.sq[4 * h], x0, x1, x0);
  hmma_k8(a.sq[4 * h + 1], x0, x1, x1);
  hmma_k8(a.sq[4 * h + 2], x2, x3, x2);
  hmma_k8(a.sq[4 * h + 3], x2, x3, x3);
}
template <int K0, int K1>
__device__ __forceinline__ void ln_accum(const uint32_t (&xa)[144], LnAcc& a) {
#pragma unroll
  for (int k = K0; k < K1; k++) ln_accum1(a, k & 1, xa[4 * k], xa[4 * k + 1], xa[4 * k + 2], xa[4 * k + 3]);
}
template <int K0, int K1>
__device__ __forceinline__ void ln_sums(const uint32_t (&xa)[144], float (&sm)[4][4]) {
#pragma unroll
  for (int k = K0; k < K1; k++) hmma_k16(sm[k & 3], xa[4 * k], xa[4 * k + 1], xa[4 * k + 2], xa[4 * k + 3], 0x3F803F80u, 0x3F803F80u);
}
__device__ __forceinline__ uint32_t sq8(const uint32_t* a) {
  uint32_t t, u;
  asm("mul.rn.bf16x2 %0, %1, %1;" : "=r"(t) : "r"(a[0]));
  asm("mul.rn.bf16x2 %0, %1, %1;" : "=r"(u) : "r"(a[2]));
#pragma unroll
  for (int i = 4; i < 16; i += 4) {
    asm("fma.rn.bf16x2 %0, %1, %1, %0;" : "+r"(t) : "r"(a[i]));
    asm("fma.rn.bf16x2 %0, %1, %1, %0;" : "+r"(u) : "r"(a[i + 2]));
  }
  return add2(t, u);
}
__device__ __forceinline__ void ln_centre(uint32_t (&xa)[144], int j0, int j1, uint32_t mm0, uint32_t mm1, float& sq0, float& sq1) {
#pragma unroll
  for (int j = 0; j < 72; j += 8)
    if (j >= j0 && j < j1) {
#pragma unroll
      for (int k = j; k < j + 8; k++) {
        xa[2 * k] = sub2(xa[2 * k], mm0);
        xa[2 * k + 1] = sub2(xa[2 * k + 1], mm1);
      }
      const uint32_t t0 = sq8(xa + 2 * j), t1 = sq8(xa + 2 * j + 1);
      sq0 += bf_lo(t0) + bf_hi(t0);
      sq1 += bf_lo(t1) + bf_hi(t1);
    }
}
__device__ __forceinline__ float ln_rstd(float msq, float d) {
  float sd;
  asm("sqrt.approx.f32 %0, %1;" : "=f"(sd) : "f"(bfr(bfr(fmaxf(msq - d * d, 0.0f)) + 1e-5f)));
  return rcp(bfr(sd));
}
__device__ __forceinline__ void ln_row(float sum, float sq, float& mean_b, float& rstd) {
  const float mean = sum * (1.0f / DM);
  mean_b = bfr(mean);
  rstd = ln_rstd(sq * (1.0f / DM), mean);
}
__device__ __forceinline__ void ln_diag(const LnAcc& a, int lane, float& t0, float& t1) {
  const bool odd = (lane >> 2) & 1;
  t0 = odd ? (a.sq[0][1] + a.sq[2][1]) + (a.sq[4][1] + a.sq[6][1]) : (a.sq[0][0] + a.sq[2][0]) + (a.sq[4][0] + a.sq[6][0]);
  t1 = odd ? (a.sq[1][3] + a.sq[3][3]) + (a.sq[5][3] + a.sq[7][3]) : (a.sq[1][2] + a.sq[3][2]) + (a.sq[5][2] + a.sq[7][2]);
}
__device__ __forceinline__ void ln_stats(const LnAcc& a, int lane, float& mean0, float& rstd0, float& mean1, float& rstd1) {
  float t0, t1;
  ln_diag(a, lane, t0, t1);
  const int src = (lane & ~3) | (lane >> 3);
  t0 = __shfl_sync(0xffffffffu, t0, src);
  t1 = __shfl_sync(0xffffffffu, t1, src);
  ln_row(a.sm[0][0] + a.sm[1][0], t0, mean0, rstd0);
  ln_row(a.sm[0][2] + a.sm[1][2], t1, mean1, rstd1);
}

template <bool ROUTED>
__device__ __forceinline__ uint32_t gate2(uint32_t x2, float mean_b, float rstd, float2 upd = make_float2(0.f, 0.f)) {
  const uint32_t xc = sub2(x2, pack2(mean_b, mean_b));
  uint32_t t = pack2(bf_lo(xc) * rstd, bf_hi(xc) * rstd);
  if (ROUTED) t = pack2(bf_lo(t) + upd.x, bf_hi(t) + upd.y);
  return pack2(silu_f(bf_lo(t)), silu_f(bf_hi(t)));
}

template <int V> struct IC { static constexpr int value = V; };

struct Ctx {
  uint32_t sb;
  uint8_t* sp;
  uint32_t rank;
  Scratch* gs;
};

__device__ __forceinline__ void dly(int) {}
template <int BOXES>
__device__ __forceinline__ void load_stage(uint32_t dst, const CUtensorMap* tm, int c0, int c1, uint32_t bar, uint32_t bytes, uint64_t pol) {
  asm volatile("{\n.reg .pred p;\nelect.sync _|p, 0xffffffff;\n"
               "@p mbarrier.arrive.expect_tx.shared::cta.b64 _, [%4], %7;\n"
               "@p cp.async.bulk.tensor.2d.shared::cluster.global.mbarrier::complete_tx::bytes.multicast::cluster.L2::cache_hint"
               " [%0], [%1, {%2, %3}], [%4], %5, %6;\n}"
               ::"r"(dst), "l"(tm), "r"(c0), "r"(c1), "r"(bar), "h"((uint16_t)3), "l"(pol), "r"(bytes) : "memory");
  if (BOXES == 2)
    asm volatile("{\n.reg .pred p;\nelect.sync _|p, 0xffffffff;\n"
                 "@p cp.async.bulk.tensor.2d.shared::cluster.global.mbarrier::complete_tx::bytes.multicast::cluster.L2::cache_hint"
                 " [%0], [%1, {%2, %3}], [%4], %5, %6;\n}"
                 ::"r"(dst + 8192), "l"(tm), "r"(c0), "r"(c1 + 64), "r"(bar), "h"((uint16_t)3), "l"(pol) : "memory");
}
__device__ __forceinline__ void attn_producer(const Ctx& cx, int qb, int hs, const CUtensorMap* tmX, const CUtensorMap* tmK,
                                              const CUtensorMap* tmV, const CUtensorMap* tmWq, const CUtensorMap* tmWo) {
  const uint32_t full = cx.sb + SM_FULL, empty = cx.sb + SM_EMPTY, ring = cx.sb + SM_RING + cx.rank * 16384;
  const uint64_t keep = policy_evict_normal(), last_use = policy_evict_first();
  auto acquire = [&](int st) {
    mbar_wait(empty + 8 * (st & 3), ((st >> 2) ^ ((st & 3) >> 1) ^ 1) & 1);
    dly(st);
  };
  if (elect_one()) {
#pragma unroll
    for (int j = 0; j < 3; j++) {
      mbar_expect_tx(cx.sb + SM_XFULL + 96 + 8 * j, 24576);
      tma3d(cx.sb + SM_X + 73728 + j * 24576, tmX, qb * 128 + 64, j * 3, cx.sb + SM_XFULL + 96 + 8 * j);
    }
  }
  __syncwarp();
#pragma unroll 1
  for (int p = 0; p < 4; p++) {
    const int n0 = (hs * 4 + ((0x1320 >> (4 * p)) & 3)) * DH + cx.rank * 64;
#pragma unroll
    for (int i = 0; i < 5; i++) {
      const int st = 5 * p + i, sl = st & 3;
      if (i == 4 && p == 3) break;
      acquire(st);
      if (i == 2) load_stage<1>(ring + sl * STAGE, tmWq, n0, 256, full + 8 * sl, 16384, last_use);
      else load_stage<2>(ring + sl * STAGE, tmWq, n0, i < 2 ? 128 * i : 128 * i - 64, full + 8 * sl, 32768, last_use);
      if (i == X_PFQ && p == 0 && elect_one()) {
#pragma unroll 1
        for (int b = 8 + qb; b < 72; b += 16) {
          const int bp = (b * 57) >> 10;
          tma2d_prefetch(tmWq, (hs * 4 + ((0x1320 >> (4 * bp)) & 3)) * DH + (b & 1) * 64, ((b - 18 * bp) >> 1) * 64);
        }
      }
      __syncwarp();
    }
  }
  const int c0 = cx.rank * 64;
  int vrow = 0;
  uint64_t vpol = keep;
#pragma unroll 1
  for (int j = 0; j < 32; j++) {
    const int st = NST_Q - 1 + 4 * j, row = (hs * 2 + (j >> 4)) * SEQ + (j & 7) * 256;
    const uint64_t pol = (j & 8) ? last_use : keep;
    acquire(st);
    load_stage<1>(ring + 3 * STAGE, tmK, c0, row, full + 24, 32768, pol);
    acquire(st + 1);
    if (j) load_stage<1>(ring, tmV, c0, vrow, full, 32768, vpol);
    else load_stage<2>(ring, tmWq, (hs * 4 + 1) * DH + c0, 448, full, 32768, last_use);
    vrow = row + 128;
    vpol = pol;
    acquire(st + 2);
    load_stage<1>(ring + STAGE, tmK, c0, vrow, full + 8, 32768, pol);
    acquire(st + 3);
    load_stage<1>(ring + 2 * STAGE, tmV, c0, row, full + 16, 32768, pol);
  }
  acquire(NST_Q + NST_KV - 1);
  load_stage<1>(ring + 3 * STAGE, tmV, c0, vrow, full + 24, 32768, last_use);
#pragma unroll 1
  for (int u = 0; u < NST_O; u++) {
    const int st = NST_Q + NST_KV + u, sl = st & 3;
    const int blk = u < 4 && cx.rank ? 8 : ((hs + max(u >> 1, 1)) & 7);
    const int head = u < 4 ? u ^ (u >> 1) : ((u & 1) * 2 + cx.rank + 3) & 3;
    acquire(st);
    load_stage<1>(ring + sl * STAGE, tmWo, blk * 64, hs * 512 + head * 128, full + 8 * sl, 32768, last_use);
  }
}

__device__ __forceinline__ void attn_gate(const Ctx& cx, int qb, int hs, int t, const __nv_bfloat16* x) {
  const uint32_t base = (qb * 128 * DM + (t & 7) * 8) * 2;
  uint32_t lr = t >> 3, o = base + (lr * DM + hs * 64) * 2;
  uint4 nx = __ldg(at<const uint4>(x, o));
  bar_sync(BAR_GATE, 352);
#pragma unroll 1
  for (uint32_t n = (t >> 3) + 12; n < 156; n += 12) {
    const uint4 v = nx;
    const float2 st = *(const float2*)(cx.sp + SM_STATS + 8 * lr);
    uint4* dst = at<uint4>(cx.gs->gate, o);
    lr = n < 128 ? n : n + hs * 16 - 128;
    o = base + (lr * DM + (n < 128 ? hs * 64 : 512)) * 2;
    if (n < 144) nx = __ldg(at<const uint4>(x, o));
    *dst = make_uint4(gate2<false>(v.x, st.x, st.y), gate2<false>(v.y, st.x, st.y), gate2<false>(v.z, st.x, st.y), gate2<false>(v.w, st.x, st.y));
  }
}

constexpr uint32_t SM_XO = SM_SLOT, SM_GO = SM_SLOT + 128 * 144;
constexpr uint32_t SM_X8 = SM_SLOT + 2 * STAGE + 20480, SM_G8 = SM_X8 + 16 * 144;
__device__ __forceinline__ void attn_stage_xg(const Ctx& cx, int qb, int hs, int t, const __nv_bfloat16* x) {
  bar_sync(BAR_OA, 352);
#pragma unroll 1
  for (uint32_t lr = t >> 3; lr < 128; lr += 8) {
    const uint32_t o = ((qb * 128 + lr) * DM + hs * 64 + (t & 7) * 8) * 2;
    cp16(cx.sb + SM_XO + lr * 144 + (t & 7) * 16, at<const void>(x, o));
    cp16(cx.sb + SM_GO + lr * 144 + (t & 7) * 16, at<const void>(cx.gs->gate, o));
  }
  cp_wait_all();
  mbar_arrive(cx.sb + SM_BAR_XG);
}

__device__ __forceinline__ void attn_helper(const Ctx& cx, int qb, int hs, int lane, const __nv_bfloat16* x, const __nv_bfloat16* wo) {
  unsigned e = 0;
  if (lane == 0) {
    e = cx.gs->launch[blockIdx.x];
    cx.gs->launch[blockIdx.x] = e + 1;
  }
  e = __shfl_sync(0xffffffffu, e, 0);
  bar_sync(BAR_HELPER, 128);
  prefetch_l2(at<const void>(wo, (hs * 512 + qb * 32 + lane) * (DM * 2)), DM * 2);
#pragma unroll 1
  for (int n = 0; n < (1 << 16) && ld_acquire(&cx.gs->ffn_flag) != e + 1; n++) __nanosleep(1000);
  const uint32_t tag = ~e & 1;
  {
#pragma unroll 1
    for (int i = 0; i < 2 * TOPC; i++) {
      const int lr = __ldcg(&cx.gs->idx[i >> 1]) - qb * 128, col = ((i & 1) ? 512 : hs * 64) + 2 * lane;
      if ((i & 1) ? (lr >> 4) == hs : (lr >> 7) == 0) {
        const float2 st = *(const float2*)(cx.sp + SM_STATS + 8 * lr);
        const uint32_t o = ((qb * 128 + lr) * DM + col) * 2;
        *at<uint32_t>(cx.gs->gate, o) =
            gate2<true>(*at<const uint32_t>(x, o), st.x, st.y, __ldcg(at<const float2>(cx.gs->upd, ((i >> 1) * DM + col) * 4)));
      }
    }
  }
  if (lane == 0) *(uint32_t*)(cx.sp + SM_TAG) = tag;
  __syncwarp();
  if (lane == 0) mbar_arrive(cx.sb + SM_BAR_MISC);

  const uint4* src = at<const uint4>(cx.gs->part, (((qb * 64 + 56) * 2 + (hs >> 2)) * 4 * 128 + (hs & 3) * 32 + lane) * 16);
  const uint32_t stg = cx.sb + SM_SLOT + 2 * STAGE + lane * 16;
  bar_sync(BAR_OA, 352);

#pragma unroll 1
  for (int i = 0; i < 4; i++) {
    const int ch = i * 32 + lane;
    const uint32_t o = ((qb * 128 + hs * 16 + (ch >> 3)) * DM + 512 + (ch & 7) * 8) * 2;
    cp16(cx.sb + SM_X8 + (ch >> 3) * 144 + (ch & 7) * 16, at<const void>(x, o));
    cp16(cx.sb + SM_G8 + (ch >> 3) * 144 + (ch & 7) * 16, at<const void>(cx.gs->gate, o));
  }
#pragma unroll 1
  for (int n = 0; n < (1 << 16); n++) {
    __nanosleep(n ? 500 : 1000);
    uint32_t a, b, d, t;
    ld_gran(at<const uint4>(src, ((lane & 7) * (2 * 4 * 128) + 3 * 128 + 31 - lane) * 16), a, b, d, t);
    if (__all_sync(0xffffffffu, (a & 1) == tag)) break;
  }
#pragma unroll 1
  for (int n = 0; n < (1 << 16); n++) {
#pragma unroll 1
    for (int i = 0; i < 8; i++) {
#pragma unroll
      for (int g = 0; g < 4; g++) cp16(stg + (i * 4 + g) * 512, at<const uint4>(src, i * (2 * 4 * 128 * 16)) + g * 128);
    }
    cp_wait_all();
    uint32_t bad = 0;
#pragma unroll 4
    for (int i = 0; i < 32; i++) bad |= *(const volatile uint32_t*)(cx.sp + SM_SLOT + 2 * STAGE + lane * 16 + i * 512) ^ tag;
    if (__all_sync(0xffffffffu, (bad & 1) == 0)) break;
  }

}
__device__ __forceinline__ void attn_finish8(const Ctx& cx, int qb, int hs, int hw, int lane, __nv_bfloat16* out) {
  bar_sync(BAR_GATE, 96);
#pragma unroll 1
  for (int g = hw; g < 4; g += 3) {
    float acc[8] = {0.f, 0.f, 0.f, 0.f, 0.f, 0.f, 0.f, 0.f};
#pragma unroll 2
    for (int sidx = 0; sidx < 8; sidx++) {
      uint32_t a, b, d, t;
      lds128(cx.sb + SM_SLOT + 2 * STAGE + lane * 16 + (sidx * 4 + g) * 512, a, b, d, t);
      acc[0] += bf_lo(a & ~1u); acc[1] += bf_hi(a); acc[2] += bf_lo(b); acc[3] += bf_hi(b);
      acc[4] += bf_lo(d); acc[5] += bf_hi(d); acc[6] += bf_lo(t); acc[7] += bf_hi(t);
    }
#pragma unroll
    for (int j = 0; j < 4; j++) {
      const int o = ((lane >> 2) + (j & 1) * 8) * 144 + (2 * g + (j >> 1)) * 16 + (lane & 3) * 4;
      uint32_t* xp = (uint32_t*)(cx.sp + SM_X8 + o);
      const uint32_t xw = *xp, gw = *(const uint32_t*)(cx.sp + SM_G8 + o);
      *xp = pack2(fmaf(acc[2 * j], bf_lo(gw), bf_lo(xw)), fmaf(acc[2 * j + 1], bf_hi(gw), bf_hi(xw)));
    }
  }
  bar_sync(BAR_GATE, 96);
#pragma unroll 1
  for (int ch = hw * 32 + lane; ch < 128; ch += 96)
    *at<uint4>(out, ((qb * 128 + hs * 16 + (ch >> 3)) * DM + 512 + (ch & 7) * 8) * 2) =
        *(const uint4*)(cx.sp + SM_X8 + (ch >> 3) * 144 + (ch & 7) * 16);
}

constexpr float SUM_HI = 1.8446744e19f, SUM_LO = 9.0949470e-13f;

__device__ __forceinline__ void softmax_shift(float (&s)[64], float n0, float n1) {
#pragma unroll
  for (int i = 0; i < 64; i++) s[i] += (i & 2) ? n1 : n0;
}
template <int LO, int HI>
__device__ __forceinline__ void softmax_exp(float (&s)[64]) {
#pragma unroll
  for (int i = LO; i < HI; i++) s[i] = ex2(s[i]);
}
__device__ __forceinline__ void row_sums(const uint32_t (&pf)[32], float& l0, float& l1) {
  uint32_t t[16];
#pragma unroll
  for (int i = 0; i < 16; i++) t[i] = add2(pf[(i >> 1) * 4 + (i & 1)], pf[(i >> 1) * 4 + 2 + (i & 1)]);
#pragma unroll
  for (int i = 0; i < 8; i++) t[i] = add2(t[(i >> 1) * 4 + (i & 1)], t[(i >> 1) * 4 + 2 + (i & 1)]);
#pragma unroll
  for (int i = 0; i < 4; i++) t[i] = add2(t[(i >> 1) * 4 + (i & 1)], t[(i >> 1) * 4 + 2 + (i & 1)]);
  l0 += (bf_lo(t[0]) + bf_lo(t[2])) + (bf_hi(t[0]) + bf_hi(t[2]));
  l1 += (bf_lo(t[1]) + bf_lo(t[3])) + (bf_hi(t[1]) + bf_hi(t[3]));
}
__device__ __forceinline__ void row_max(const float (&s)[64], float& x0, float& x1) {
  x0 = s[0];
  x1 = s[2];
#pragma unroll
  for (int i = 0; i < 64; i += 4) { x0 = fmaxf(x0, fmaxf(s[i], s[i + 1])); x1 = fmaxf(x1, fmaxf(s[i + 2], s[i + 3])); }
  x0 = fmaxf(x0, __shfl_xor_sync(0xffffffffu, x0, 1));
  x1 = fmaxf(x1, __shfl_xor_sync(0xffffffffu, x1, 1));
  x0 = fmaxf(x0, __shfl_xor_sync(0xffffffffu, x0, 2));
  x1 = fmaxf(x1, __shfl_xor_sync(0xffffffffu, x1, 2));
}
__device__ __forceinline__ void softmax_rebase(float (&s)[64], float& n0, float& n1, float& sc0, float& sc1) {
  float x0, x1;
  row_max(s, x0, x1);
  x0 = fmaxf(x0, 1.f);
  x1 = fmaxf(x1, 1.f);
  n0 -= __log2f(x0);
  n1 -= __log2f(x1);
  sc0 = exp2f(-__log2f(x0));
  sc1 = exp2f(-__log2f(x1));
#pragma unroll
  for (int i = 0; i < 64; i++) s[i] *= (i & 2) ? sc1 : sc0;
}
__device__ __forceinline__ void softmax_redo(float (&s)[64], const uint32_t (&q)[32], const __nv_bfloat16* kblk, int lane, float& n0,
                                             float& n1, float& sc0, float& sc1) {
  const __nv_bfloat16* kp = kblk + (lane >> 2) * DH + (lane & 3) * 2;
#pragma unroll
  for (int nb = 0; nb < 16; nb++) {
    float d[4] = {0.f, 0.f, 0.f, 0.f};
#pragma unroll
    for (int k = 0; k < 8; k++)
      hmma_k16(d, q[4 * k], q[4 * k + 1], q[4 * k + 2], q[4 * k + 3], *(const uint32_t*)(kp + nb * 8 * DH + k * 16),
               *(const uint32_t*)(kp + nb * 8 * DH + k * 16 + 8));
    s[4 * nb] = d[0]; s[4 * nb + 1] = d[1]; s[4 * nb + 2] = d[2]; s[4 * nb + 3] = d[3];
    block_fence(100 + nb);
  }
  float x0, x1;
  row_max(s, x0, x1);
  const float m0 = fminf(n0, -x0), m1 = fminf(n1, -x1);
  sc0 = ex2(m0 - n0);
  sc1 = ex2(m1 - n1);
  n0 = m0; n1 = m1;
  softmax_shift(s, n0, n1);
  softmax_exp<0, 64>(s);
}

__device__ __forceinline__ void attn_consumer(const Ctx& cx, int qb, int hs, int wg, int cw, int lane, const __nv_bfloat16* x,
                                              const __nv_bfloat16* kc, __nv_bfloat16* out) {
  const int r = lane >> 2, c = lane & 3, tw = (cw & 3) * 32 + lane;
  const int lr0 = cw * 16 + r;
  const uint32_t full = cx.sb + SM_FULL;
  const uint32_t ring = cx.sb + SM_RING;
  const uint32_t lo = ((cw & 3) * 16 + (lane & 15)) * 128 + (((lane >> 4) ^ (lane & 7)) << 4);
  const uint32_t slot = cx.sb + SM_SLOT + wg * 16384;
  auto frag = [&](int sl, int k) { return slot + sl * STAGE + (k >> 2) * 8192 + (lo ^ ((k & 3) << 5)); };
  auto park = [&](const float (&a)[64], int sl, int k0, int k1, float f0, float f1) {
#pragma unroll
    for (int k = 0; k < 8; k++)
      if (k >= k0 && k < k1)
        stsm4(frag(sl, k), pack2(a[8 * k] * f0, a[8 * k + 1] * f0), pack2(a[8 * k + 2] * f1, a[8 * k + 3] * f1),
              pack2(a[8 * k + 4] * f0, a[8 * k + 5] * f0), pack2(a[8 * k + 6] * f1, a[8 * k + 7] * f1));
  };
  const bool signaller = lane == 0 && (cw & 3) < 2;
  int my_turn = 1 + wg, other_turn = 2 - wg;

  uint32_t pf[32], empty_c;
  float o[64], l0, l1;
  {
    uint32_t xa[144];
    float rstd0, rstd1, sq0 = 0.f, sq1 = 0.f;
    {
      const uint32_t xb = cx.sb + SM_X + wg * 73728, xf = cx.sb + SM_XFULL + wg * 96;
      float sm[4][4] = {};
      prof(wg, 0);
      empty_c = mapa(cx.sb + SM_EMPTY, cw & 1);
      mbar_wait(xf, 0);
      if ((threadIdx.x & 127) == 0) profc(wg, 30);
      ln_fetch<0, 12>(xa, xb, lo);
      mbar_wait(xf + 8, 0);
      ln_fetch<12, 24>(xa, xb, lo);
      ln_sums<0, 12>(xa, sm);
      mbar_wait(xf + 16, 0);
      if ((threadIdx.x & 127) == 0) profc(wg, 1);
      ln_fetch<24, 36>(xa, xb, lo);
      ln_sums<12, 36>(xa, sm);
      rstd0 = ((sm[0][0] + sm[1][0]) + (sm[2][0] + sm[3][0])) * (1.0f / DM);
      rstd1 = ((sm[0][2] + sm[1][2]) + (sm[2][2] + sm[3][2])) * (1.0f / DM);
    }
    asm volatile("" : "+f"(rstd0), "+f"(rstd1)::"memory");
    if (wg) {
      bar_arrive(other_turn, 256);
    } else {
      bar_sync(4, 128);
      if (signaller) {
        asm volatile("mbarrier.arrive.shared::cluster.b64 _, [%0], 2;" ::"r"(empty_c + 16) : "memory");
        asm volatile("mbarrier.arrive.shared::cluster.b64 _, [%0], 2;" ::"r"(empty_c + 24) : "memory");
      }
    }
    const uint32_t mm0 = pack2(rstd0, rstd0), mm1 = pack2(rstd1, rstd1);
    ln_centre(xa, 0, X_C0, mm0, mm1, sq0, sq1);
    pin(xa);
    if ((threadIdx.x & 127) == 0) profc(wg, 2);

#pragma unroll 1
    for (int p = 0;; p++) {
      const int st0 = p * 5, last = p == 3 ? 3 : 4;
#pragma unroll
      for (int i = 0; i < 5; i++) {
        const int st = st0 + i;
        const uint32_t sl = st & 3;
        mbar_wait(full + 8 * sl, (st >> 2) & 1);
        if (i != (wg ? last : 1)) bar_sync(my_turn, 256);
        wg_fence();
        const uint64_t db = mkdesc(ring + sl * STAGE, 16384);
        const int kb0 = i < 3 ? 8 * i : 8 * i - 4;
#pragma unroll
        for (int k = 0; k < (i == 2 ? 4 : 8); k++) {
          const int kb = kb0 + k;
          mma_n128<1>(o, xa[4 * kb], xa[4 * kb + 1], xa[4 * kb + 2], xa[4 * kb + 3], db + k * 128, kb > 0);
          if (i == 4 && k == X_HO) wg_commit();
        }
        wg_commit();
        if (i == 4 && X_HO < 7) wg_wait<1>();
        if (i != (wg ? last - 1 : 0)) bar_arrive(other_turn, 256);
        if (p == 0 && (i == 1 || i == 2)) {
          ln_centre(xa, i == 1 ? X_C0 : X_C1, i == 1 ? X_C1 : 72, mm0, mm1, sq0, sq1);
          if (i == 2) {
            sq0 += __shfl_xor_sync(0xffffffffu, sq0, 1); sq1 += __shfl_xor_sync(0xffffffffu, sq1, 1);
            sq0 += __shfl_xor_sync(0xffffffffu, sq0, 2); sq1 += __shfl_xor_sync(0xffffffffu, sq1, 2);
            rstd0 = ln_rstd(sq0 * (1.0f / DM), rstd0 - bf_lo(mm0));
            rstd1 = ln_rstd(sq1 * (1.0f / DM), rstd1 - bf_lo(mm1));
            if (c == 0) {
              *(float2*)(cx.sp + SM_STATS + 8 * lr0) = make_float2(bf_lo(mm0), rstd0);
              *(float2*)(cx.sp + SM_STATS + 8 * (lr0 + 8)) = make_float2(bf_lo(mm1), rstd1);
            }
            bar_arrive(BAR_GATE, 352);
            rstd0 *= SM_SCALE_LOG2;
            rstd1 *= SM_SCALE_LOG2;
          }
          pin(xa);
        }
        if (i == 0 || i == 2) {
          if (i ? p != 3 : wg) {
            wg_wait<0>();
            if (signaller) mbar_arrive_cluster(empty_c + 8 * sl);
          }
        } else if (i == 3) {
          if (p == 3) break;
        } else {
          wg_wait<1>();
          if (signaller && (i == 4 || !wg)) mbar_arrive_cluster(empty_c + 8 * ((st - 1) & 3));
          wg_wait<0>();
          if (signaller) mbar_arrive_cluster(empty_c + 8 * sl);
        }
      }
      if (p == 3) break;
      pin(o);
      park(o, p, 0, 8, rstd0, rstd1);
    }
    wg_wait<1>();
    if (signaller) mbar_arrive_cluster(empty_c + 8 * ((NST_Q - 3) & 3));
    wg_wait<0>();
    if (signaller) mbar_arrive_cluster(empty_c + 8 * ((NST_Q - 2) & 3));
    prof(wg, 6);
#pragma unroll
    for (int i = 0; i < 32; i++) pf[i] = xa[112 + i];
    l0 = 0.25f * rcp(rstd0);
    l1 = 0.25f * rcp(rstd1);
  }

  uint32_t oa[96];
  const uint32_t zero = __shfl_sync(0xffffffffu, blockIdx.y, lane);
  my_turn = __shfl_sync(0xffffffffu, my_turn, lane);
  other_turn = __shfl_sync(0xffffffffu, other_turn, lane);
  {
    float s[64], n0, n1;
    uint32_t q[32];
    float lp0, lp1;
    float i0, i1;
    bool redo, shift;
    auto turn = [&](int it, auto kc_) -> bool {
      constexpr int KIND = decltype(kc_)::value;
      constexpr uint32_t slk = KIND == 1 ? 1 : 3, slv = KIND == 1 ? 2 : 0, slkn = KIND == 1 ? 3 : 1;
      constexpr int SPLIT = X_SPLIT, PARK1 = X_PARK;
      const uint32_t par = ((it + 10) >> 1) & 1;
      const int hsl = max((it >> 4) - 1, 0);
      const uint64_t dk = mkdesc(ring + slk * STAGE, 16), dv = mkdesc(ring + slv * STAGE, 16384);
      auto qk = [&]() {
#pragma unroll
        for (int k = 0; k < 8; k++) {
          if (KIND == 3) mma_n128_ss<0>(s, mkdesc(slot + hsl * STAGE, 16) + (k >> 2) * 512 + (k & 3) * 2, dk + (k >> 2) * 1024 + (k & 3) * 2, k > 0);
          else mma_n128<0>(s, q[4 * k], q[4 * k + 1], q[4 * k + 2], q[4 * k + 3], dk + (k >> 2) * 1024 + (k & 3) * 2, k > 0);
        }
        wg_commit();
      };
      auto pv = [&]() {
#pragma unroll
        for (int k = 0; k < 8; k++)
          mma_n128<1>(o, pf[4 * k], pf[4 * k + 1], pf[4 * k + 2], pf[4 * k + 3], dv + k * 128, k > 0 || KIND != 1 || (it & 15) != 1);
        wg_commit();
      };
      lp0 = l0; lp1 = l1;
#define TS(i)
      {
        TS(0)
        if (KIND == 3) {
          asm volatile("fence.proxy.async.shared::cta;" ::: "memory");
          const float t0 = lp0 + __shfl_xor_sync(0xffffffffu, lp0, 1), t1 = lp1 + __shfl_xor_sync(0xffffffffu, lp1, 1);
          i0 = rcp(t0 + __shfl_xor_sync(0xffffffffu, t0, 2));
          i1 = rcp(t1 + __shfl_xor_sync(0xffffffffu, t1, 2));
          asm volatile("" : "+f"(i0), "+f"(i1)::"memory");
          block_fence(31, zero);
#pragma unroll
          for (int k = 0; k < X_N1; k++) ldsm4(frag(hsl, k), q[4 * k], q[4 * k + 1], q[4 * k + 2], q[4 * k + 3]);
        }
        bar_sync(my_turn, 256);
        TS(1)
        if (KIND != 3) pin(q);
        pin(pf); pin(o);
        wg_fence();
        qk();
        TS(2)
        mbar_wait(full + 8 * slv, par);
        if (KIND == 1 && (it & 15) == 1) {
          park(o, hsl, PARK1, 8, i0, i1);
          wg_fence();
        }
        if (KIND == 3) {
#pragma unroll
          for (int k = X_N1; k < 8; k++) ldsm4(frag(hsl, k), q[4 * k], q[4 * k + 1], q[4 * k + 2], q[4 * k + 3]);
          block_fence(32, zero);
        }
        TS(3)
        pv();
        bar_arrive(other_turn, 256);
        TS(4)
        wg_wait<1>();
      }
      pin(s);
      mbar_arrive_cluster_now<10 * KIND + 3>(empty_c + 8 * slk, signaller, zero);
      TS(5)
      if (KIND == 3) {
        shift = false;
        n0 = n1 = l0 = l1 = 0.f;
      } else if (shift) {
        softmax_shift(s, n0, n1);
        pin(s);
      }
      softmax_exp<0, SPLIT>(s);
      pin(s);
      block_fence(10 * KIND + 4, zero);
      TS(6)
      wg_wait<0>();
      pin(o); pin(pf);
      mbar_arrive_cluster_now<10 * KIND + 5>(empty_c + 8 * slv, signaller, zero);
      TS(7)
      const bool kready = mbar_test(full + 8 * slkn, par);
      softmax_exp<SPLIT, 64>(s);
#pragma unroll
      for (int i = 0; i < 32; i++) pf[i] = pack2(s[2 * i], s[2 * i + 1]);
      row_sums(pf, l0, l1);
      if (KIND == 3) {
        park(o, hsl, 0, PARK1, i0, i1);
        if (it) prof(wg, 6 + (it >> 4));
        if (it == 48 && cw == 0) bar_arrive(BAR_HELPER, 128);
      }
      redo = !(l0 + l1 <= SUM_HI) || (KIND == 3 && fminf(l0, l1) < SUM_LO);
      const bool leave = __any_sync(0xffffffffu, redo || !kready);
      return leave;
    };
    int it = -1;
#pragma unroll 1
    while (true) {
      mbar_wait(full + 8 * ((it & 1) ? 3 : 1), ((it + 10) >> 1) & 1);
      it++;
#pragma unroll 1
      while (true) {
        if (it & 1) {
          if (turn(it, IC<1>()) || it == 63) break;
          it++;
        }
        if (it & 15) {
          if (turn(it, IC<2>())) break;
        } else {
          if (turn(it, IC<3>())) break;
        }
        it++;
      }
      if (__any_sync(0xffffffffu, redo)) {
        const int j = it & 15;
        float sc0, sc1;
        if (__all_sync(0xffffffffu, l0 + l1 < 3.0e38f && (j || fminf(l0, l1) >= SUM_LO))) {
          softmax_rebase(s, n0, n1, sc0, sc1);
        } else {
          if (j == 0) n0 = n1 = 3.0e38f;
          softmax_redo(s, q, kc + (size_t)((hs * 2 + (it >> 5)) * SEQ + j * 128) * DH, lane, n0, n1, sc0, sc1);
        }
        l0 = j ? lp0 * sc0 : 0.f;
        l1 = j ? lp1 * sc1 : 0.f;
        shift = true;
        if (j == 0) sc0 = sc1 = 1.f;
#pragma unroll
        for (int i = 0; i < 16; i++) { o[4 * i] *= sc0; o[4 * i + 1] *= sc0; o[4 * i + 2] *= sc1; o[4 * i + 3] *= sc1; }
#pragma unroll
        for (int i = 0; i < 32; i++) pf[i] = pack2(s[2 * i], s[2 * i + 1]);
        row_sums(pf, l0, l1);
      }
      if (it == 63) break;
    }
  }

  {
    constexpr int ST0 = NST_Q + NST_KV;
    float acc[32], red[32];
    auto await = [&](int st) { mbar_wait(full + 8 * (st & 3), (st >> 2) & 1); };
    auto release = [&](int st) { if (signaller) mbar_arrive_cluster(empty_c + 8 * (st & 3)); };
    auto unpark = [&](int h, int k0, int k1) {
#pragma unroll
      for (int k = 0; k < 8; k++)
        if (k >= k0 && k < k1) ldsm4(frag(h, k), oa[32 * h + 4 * k], oa[32 * h + 4 * k + 1], oa[32 * h + 4 * k + 2], oa[32 * h + 4 * k + 3]);
    };
    {
      float ar[64];
      asm volatile("fence.proxy.async.shared::cta;" ::: "memory");
      l0 += __shfl_xor_sync(0xffffffffu, l0, 1); l1 += __shfl_xor_sync(0xffffffffu, l1, 1);
      l0 += __shfl_xor_sync(0xffffffffu, l0, 2); l1 += __shfl_xor_sync(0xffffffffu, l1, 2);
      float f0 = rcp(l0), f1 = rcp(l1);
      asm volatile("" : "+f"(f0), "+f"(f1)::"memory");
      await(ST0 - 1);
      unpark(1, 0, 4);
      bar_sync(my_turn, 256);
      pin(pf); pin(o);
      wg_fence();
#pragma unroll
      for (int k = 0; k < 8; k++)
        mma_n128<1>(o, pf[4 * k], pf[4 * k + 1], pf[4 * k + 2], pf[4 * k + 3], mkdesc(ring + 3 * STAGE, 16384) + k * 128, 1);
      wg_commit();
      await(ST0);
      unpark(1, 4, 8);
      block_fence(61, zero);
#pragma unroll
      for (int k = 0; k < 8; k++) mma_n128_ss<1>(ar, mkdesc(slot, 16) + (k >> 2) * 512 + (k & 3) * 2, mkdesc(ring, 16384) + k * 128, k > 0);
      wg_commit();
      bar_arrive(other_turn, 256);
      wg_wait<1>();
      pin(o); pin(pf);
      mbar_arrive_cluster_now<62>(empty_c + 24, signaller, zero);
#pragma unroll
      for (int i = 0; i < 16; i++) {
        pf[2 * i] = pack2(o[4 * i] * f0, o[4 * i + 1] * f0);
        pf[2 * i + 1] = pack2(o[4 * i + 2] * f1, o[4 * i + 3] * f1);
      }
      pin(pf);
      prof(wg, 10);
#pragma unroll
      for (int u = 1; u < 4; u++) {
        await(ST0 + u);
        wg_wait<0>();
        release(ST0 + u - 1);
        bar_sync(my_turn, 256);
        wg_fence();
#pragma unroll
        for (int k = 0; k < 8; k++) {
          const uint32_t* a = (u == 1 ? oa + 32 : u == 2 ? pf : oa + 64) + 4 * k;
          mma_n128<1>(ar, a[0], a[1], a[2], a[3], mkdesc(ring + u * STAGE, 16384) + k * 128, 1);
        }
        wg_commit();
        bar_arrive(other_turn, 256);
        if (u < 3) {
          block_fence(62 + u, zero);
          unpark(u == 1 ? 2 : 0, 0, 8);
        }
      }
      mbar_wait(cx.sb + SM_BAR_MISC, 0);
      await(ST0 + 4);
      wg_wait<0>();
      release(ST0 + 3);
      pin(ar);
#pragma unroll
      for (int i = 0; i < 32; i++) { acc[i] = ar[i]; red[i] = ar[32 + i]; }
    }
    const uint32_t tag = *(const uint32_t*)(cx.sp + SM_TAG);
    uint4* const xch = at<uint4>(cx.gs->part, ((qb * 64 * 2 + wg) * 4 * 128 + tw) * 16);
    auto send = [&](const float (&v)[32], int dst) {
      uint4* p = at<uint4>(xch, dst * (2 * 4 * 128 * 16));
#pragma unroll
      for (int i = 0; i < 4; i++)
        st_gran(p + i * 128, (pack2(v[8 * i], v[8 * i + 1]) & ~1u) | tag, pack2(v[8 * i + 2], v[8 * i + 3]),
                pack2(v[8 * i + 4], v[8 * i + 5]), pack2(v[8 * i + 6], v[8 * i + 7]));
    };
    send(acc, ((hs + 1) & 7) * 7);
    int nrx = 1;
    auto half_step = [&](int s, auto hc, bool arrive) {
      constexpr int h = decltype(hc)::value;
      const int st = ST0 + 2 * s + h;
      const uint64_t db = mkdesc(ring + (st & 3) * STAGE, 16);
      bar_sync(my_turn, 256);
      pin(pf); pin(oa);
      wg_fence();
#pragma unroll
      for (int k = 0; k < 16; k++) {
        const int kb = h * 16 + k - 8;
        if (kb >= 0) mma_n64t(acc, oa[4 * kb], oa[4 * kb + 1], oa[4 * kb + 2], oa[4 * kb + 3], db + k * 128, 1);
        else mma_n64t(acc, pf[4 * k], pf[4 * k + 1], pf[4 * k + 2], pf[4 * k + 3], db + k * 128, k > 0);
      }
      wg_commit();
      if (arrive) bar_arrive(other_turn, 256);
    };
    auto fetch = [&](uint32_t (&g)[16], int n) {
      const uint4* p = at<const uint4>(xch, (hs * 7 + n - 1) * (2 * 4 * 128 * 16));
#pragma unroll
      for (int i = 0; i < 4; i++) ld_gran(p + i * 128, g[4 * i], g[4 * i + 1], g[4 * i + 2], g[4 * i + 3]);
    };
    uint32_t g[16];
    bool pend = false;
#pragma unroll 1
    for (int s = 2; s < 8; s++) {
      const int st = ST0 + 2 * s;
      half_step(s, IC<0>(), true);
      if (s == 2) {
        bar_arrive(BAR_OA, 352);
        send(red, 56 + hs);
#pragma unroll
        for (int i = 0; i < 32; i++) red[i] = 0.f;
      }
      await(st + 1);
      if (pend && granules_ok(g, tag)) { add_granules(red, g); nrx++; }
      wg_wait<0>();
      if (s < 7) release(st);
      pend = nrx < s - 1;
      if (pend) fetch(g, nrx);
      half_step(s, IC<1>(), true);
      await(st + 2);
      wg_wait<0>();
      if (s < 7) release(st + 1);
      pin(acc);
      if (s == 7) prof(wg, 19);
      send(acc, ((hs + s) & 7) * 7 + s - 1);
    }
    float gf[32], xf[32];
    {
      const int s = 8;
      uint32_t g2[16], xv[16], gt[16];
      half_step(s, IC<0>(), true);
      if (pend && granules_ok(g, tag)) { add_granules(red, g); nrx++; }
      await(NST_Q + NST_KV + NST_O - 1);
      mbar_wait(cx.sb + SM_BAR_XG, 0);
      wg_wait<0>();
      fetch(g, nrx);
#pragma unroll
      for (int i = 0; i < 16; i++) {
        const uint8_t* p = cx.sp + (lr0 + (i & 1) * 8) * 144 + (i >> 1) * 16 + c * 4;
        xv[i] = *(const uint32_t*)(p + SM_XO);
        gt[i] = *(const uint32_t*)(p + SM_GO);
      }
      half_step(s, IC<1>(), wg == 0);
      fetch(g2, 7);
      int last = 8;
      const bool two = nrx < 7;
      if (granules_ok(g, tag)) { add_granules(red, g); nrx++; }
#pragma unroll
      for (int i = 0; i < 16; i++) {
        gf[2 * i] = bf_lo(gt[i]); gf[2 * i + 1] = bf_hi(gt[i]);
        xf[2 * i] = bf_lo(xv[i]); xf[2 * i + 1] = bf_hi(xv[i]);
      }
      wg_wait<0>();
      pin(acc);
#pragma unroll
      for (int i = 0; i < 32; i++) red[i] += acc[i];
      pin(red); pin(gf); pin(xf);
      block_fence(60, zero);
      if (two && granules_ok(g2, tag)) { add_granules(red, g2); last = 7; }
#pragma unroll 1
      for (int spins = 0; nrx < last && spins < (1 << 16); spins++) {
        fetch(g, nrx);
        if (granules_ok(g, tag)) { add_granules(red, g); nrx++; }
      }
    }
    prof(wg, 20);
    const uint32_t ot = ring + 2 * STAGE + cw * (16 * 144);
    uint32_t ow[16];
#pragma unroll
    for (int i = 0; i < 16; i++) ow[i] = pack2(fmaf(red[2 * i], gf[2 * i], xf[2 * i]), fmaf(red[2 * i + 1], gf[2 * i + 1], xf[2 * i + 1]));
#pragma unroll
    for (int i = 0; i < 4; i++)
      stsm4(ot + (lane & 15) * 144 + (2 * i + (lane >> 4)) * 16, ow[4 * i], ow[4 * i + 1], ow[4 * i + 2], ow[4 * i + 3]);
    __syncwarp();
#pragma unroll
    for (int i = 0; i < 4; i++) {
      uint4 v;
      lds128(ot + (i * 4 + (lane >> 3)) * 144 + (lane & 7) * 16, v.x, v.y, v.z, v.w);
      at<uint4>(out, ((qb * 128 + cw * 16 + (lane >> 3)) * DM + hs * 64 + (lane & 7) * 8) * 2)[i * (4 * DM / 8)] = v;
    }
    prof(wg, 22);
  }
}

constexpr int FST_X = 24, FST_END = FST_X + 14 * 12;
__device__ __forceinline__ void ffn_producer(const Ctx& cx, int f, const CUtensorMap* tmX, const CUtensorMap* tmG,
                                             const CUtensorMap* tmU, const CUtensorMap* tmD) {
  const uint32_t full = cx.sb + SM_FULL, empty = cx.sb + SM_EMPTY;
  int pair = -2, u = 0;
#pragma unroll 1
  for (int st = 0; st < FST_END; st++) {
    const uint32_t sl = st & 7;
    const int unit = pair * 2 + (u & 1), k = u >> 1, k3 = k >= 3 ? k - 3 : k;
    if (unit < 27) {
      mbar_wait(empty + 8 * sl, ((st >> 3) & 1) ^ 1);
      mbar_expect_tx(full + 8 * sl, FSTAGE);
      if (pair < 0) tma3d(cx.sb + sl * FSTAGE, tmX, f * 512 + ((pair + 2) * 4 + (k >= 3) * 2 + (u & 1)) * 64, k3 * 3, full + 8 * sl);
      else if (pair < 9) tma2d_stream(cx.sb + sl * FSTAGE, k < 3 ? tmG : tmU, f * 1152 + unit * 64, k3 * 192, full + 8 * sl);
      else tma2d_stream(cx.sb + sl * FSTAGE, tmD, (unit - 18) * 64, f * 1152 + k * 192, full + 8 * sl);
    }
    if (++u == 12) { u = 0; pair++; }
  }
}

__device__ __forceinline__ void ffn_consumer(const Ctx& cx, int f, int wg, int cw, int lane, const __nv_bfloat16* x,
                                             const __nv_bfloat16* w_r) {
  const int r = lane >> 2, c = lane & 3, tid = cw * 32 + lane;
  unsigned e = 0;
  if (tid == 0) {
    e = cx.gs->launch[blockIdx.x];
    cx.gs->launch[blockIdx.x] = e + 1;
    *(unsigned*)(cx.sp + SM_TAG) = e;
  }
  if (tid < 72) *(uint4*)(cx.sp + SM_H + tid * 16) = *(const uint4*)(w_r + tid * 8);
  bar_sync(3, 256);
  prof(wg, 0);
  const uint32_t full = cx.sb + SM_FULL, empty = cx.sb + SM_EMPTY;
  const bool signaller = (tid & 127) == 0;
#pragma unroll 1
  for (int b = wg; b < 8; b += 2) {
    const int row0 = f * 512 + b * 64 + (cw & 3) * 16 + r;
    const uint32_t lo = ((cw & 3) * 16 + (lane & 15)) * 128 + (((lane >> 4) ^ (lane & 7)) << 4);
    LnAcc a;
    a.clear();
#pragma unroll 1
    for (int bx = 0; bx < 9; bx++) {
      const int st = (b >> 1) * 6 + (bx / 3) * 2 + wg;
      if (bx % 3 == 0) mbar_wait(full + 8 * (st & 7), (st >> 3) & 1);
#pragma unroll
      for (int k = 0; k < 4; k++) {
        uint32_t x0, x1, x2, x3;
        ldsm4(cx.sb + (st & 7) * FSTAGE + (bx % 3) * 8192 + (lo ^ (k << 5)), x0, x1, x2, x3);
        ln_accum1(a, k & 1, x0, x1, x2, x3);
      }
    }
    prof(wg, 8 + (b >> 1) * 3);
    float mean0, rstd0, mean1, rstd1;
    ln_stats(a, lane, mean0, rstd0, mean1, rstd1);
    prof(wg, 9 + (b >> 1) * 3);
    const uint32_t mm0 = pack2(mean0, mean0), mm1 = pack2(mean1, mean1);
    float d0[4] = {0, 0, 0, 0}, d1[4] = {0, 0, 0, 0};
#pragma unroll 1
    for (int bx = 0; bx < 9; bx++) {
      const int st = (b >> 1) * 6 + (bx / 3) * 2 + wg;
#pragma unroll
      for (int k = 0; k < 4; k++) {
        uint32_t n[4];
        ldsm4(cx.sb + (st & 7) * FSTAGE + (bx % 3) * 8192 + (lo ^ (k << 5)), n[0], n[1], n[2], n[3]);
        const uint8_t* wp = cx.sp + SM_H + (bx * 4 + k) * 32 + 4 * c;
#pragma unroll
        for (int i = 0; i < 4; i++) {
          const uint32_t t = sub2(n[i], (i & 1) ? mm1 : mm0);
          const float rs = (i & 1) ? rstd1 : rstd0;
          n[i] = pack2(bf_lo(t) * rs, bf_hi(t) * rs);
        }
        if (k & 1) hmma_k16(d1, n[0], n[1], n[2], n[3], *(const uint32_t*)wp, *(const uint32_t*)(wp + 16));
        else hmma_k16(d0, n[0], n[1], n[2], n[3], *(const uint32_t*)wp, *(const uint32_t*)(wp + 16));
      }
    }
    prof(wg, 10 + (b >> 1) * 3);
    bar_sync(4 + wg, 128);
    if (signaller) {
#pragma unroll
      for (int i = 0; i < 3; i++) mbar_arrive(empty + 8 * (((b >> 1) * 6 + i * 2 + wg) & 7));
    }
    if (c == 0) {
      cx.gs->r[row0] = bfr(d0[0] + d1[0]);
      cx.gs->r[row0 + 8] = bfr(d0[2] + d1[2]);
      cx.gs->stats[row0] = make_float2(mean0, rstd0);
      cx.gs->stats[row0 + 8] = make_float2(mean1, rstd1);
    }
  }
  prof(wg, 1);
  bar_sync(3, 256);
  e = *(const unsigned*)(cx.sp + SM_TAG);
  if (tid == 0) {
    atom_add_acq_rel(&cx.gs->rcnt);
#pragma unroll 1
    for (int n = 0; n < (1 << 16) && (int)(ld_acquire(&cx.gs->rcnt) - 4 * (e + 1)) < 0; n++) {}
  }
  bar_sync(3, 256);
  prof(wg, 2);
  uint32_t key[8];
#pragma unroll
  for (int i = 0; i < 8; i++) {
    const int row = i * 256 + tid;
    const uint32_t b = __float_as_uint(__ldcg(&cx.gs->r[row])) >> 16;
    key[i] = (((b & 0x8000u) ? (~b & 0xFFFFu) : (b | 0x8000u)) << 16) | (uint32_t)(0xFFFF - row);
  }
  int mysel = 0;
#pragma unroll 1
  for (int k = 0; k < TOPC; k++) {
    uint32_t m = key[0];
#pragma unroll
    for (int i = 1; i < 8; i++) m = max(m, key[i]);
    m = __reduce_max_sync(0xffffffffu, m);
    uint32_t* tk = (uint32_t*)(cx.sp + SM_TOPK) + (k & 1) * 8;
    if (lane == 0) tk[cw] = m;
    bar_sync(3, 256);
    m = __reduce_max_sync(0xffffffffu, tk[lane & 7]);
#pragma unroll
    for (int i = 0; i < 8; i++) if (key[i] == m) key[i] = 0;
    if (k == cw) mysel = 0xFFFF - (int)(m & 0xFFFF);
  }
  {
    const float2 st = __ldcg(&cx.gs->stats[mysel]);
    const uint32_t mm = pack2(st.x, st.x);
#pragma unroll 3
    for (int i = 0; i < 9; i++) {
      const uint32_t t = sub2(*(const uint32_t*)(x + (size_t)mysel * DM + i * 64 + 2 * lane), mm);
      *(uint32_t*)(cx.sp + SM_XSEL + i * 1024 + cw * 128 + (((lane >> 2) ^ cw) << 4) + (lane & 3) * 4) =
          pack2(bf_lo(t) * st.y, bf_hi(t) * st.y);
    }
    if (lane == 0) *(int*)(cx.sp + SM_IDX + 4 * cw) = mysel;
  }
  asm volatile("fence.proxy.async.shared::cta;" ::: "memory");
  bar_sync(3, 256);
  prof(wg, 3);
  auto run = [&](float (&acc)[4], int st, int n, uint32_t b) {
#pragma unroll 1
    for (int u = 0; u < n; u++, st += 2, b += 3072) {
      const uint32_t sl = st & 7;
      mbar_wait(full + 8 * sl, (st >> 3) & 1);
      wg_fence();
      const uint64_t da = mkdesc(cx.sb + sl * FSTAGE, 16), db = mkdesc(b, 16);
#pragma unroll
      for (int k = 0; k < 12; k++) mma_n8(acc, da + k * 128, db + (k >> 2) * 64 + (k & 3) * 2, u > 0 || k > 0);
      wg_commit();
      wg_wait<0>();
      if (signaller) mbar_arrive(empty + 8 * sl);
    }
    pin(acc);
  };
#pragma unroll 1
  for (int unit = wg; unit < 27; unit += 2) {
    if (unit >> 1 == 9) {
      asm volatile("fence.proxy.async.shared::cta;" ::: "memory");
      bar_sync(3, 256);
      prof(wg, 4);
    }
    const bool gu = unit < 18;
    float a0[4], a1[4];
#pragma unroll 1
    for (int m = 0; m < (gu ? 2 : 1); m++) {
      run(a1, FST_X + (unit >> 1) * 12 + m * 6 + wg, gu ? 3 : 6, cx.sb + (gu ? SM_XSEL : SM_H));
      if (m == 0) { a0[0] = a1[0]; a0[1] = a1[1]; a0[2] = a1[2]; a0[3] = a1[3]; }
    }
#pragma unroll
    for (int i = 0; i < 4; i++) {
      const int fl = (cw & 3) * 16 + r + (i >> 1) * 8, tok = 2 * c + (i & 1);
      if (gu) {
        const float h = bfr(silu_f(bfr(a0[i]))) * bfr(a1[i]);
        *(__nv_bfloat16*)(cx.sp + SM_H + unit * 1024 + tok * 128 + (((fl >> 3) ^ tok) << 4) + (fl & 7) * 2) = __float2bfloat16_rn(h);
      } else {
        cx.gs->ypart[(f * TOPC + tok) * DM + (unit - 18) * 64 + fl] = a1[i];
      }
    }
  }
  prof(wg, 5);
  bar_sync(3, 256);
  if (tid == 0) *(unsigned*)(cx.sp + SM_TOPK) = atom_add_acq_rel(&cx.gs->ycnt) == 4 * e + 3;
  bar_sync(3, 256);
  if (*(const unsigned*)(cx.sp + SM_TOPK)) {
    const int row = *(const int*)(cx.sp + SM_IDX + 4 * cw);
    const float rs = bfr(rcp(1.0f + ex2(-1.4426950408889634f * __ldcg(&cx.gs->r[row]))));
#pragma unroll 1
    for (int d = lane * 2; d < DM; d += 192) {
#pragma unroll
      for (int i = 0; i < 3; i++) {
        const float* p = cx.gs->ypart + cw * DM + d + i * 64;
        const float2 a = __ldcg((const float2*)p), b = __ldcg((const float2*)(p + TOPC * DM)),
                     e2 = __ldcg((const float2*)(p + 2 * TOPC * DM)), h = __ldcg((const float2*)(p + 3 * TOPC * DM));
        const uint32_t y = pack2((a.x + b.x) + (e2.x + h.x), (a.y + b.y) + (e2.y + h.y));
        const uint32_t u = pack2(bf_lo(y) * rs, bf_hi(y) * rs);
        *(float2*)(cx.gs->upd + cw * DM + d + i * 64) = make_float2(bf_lo(u), bf_hi(u));
      }
    }
    if (lane == 0) cx.gs->idx[cw] = row;
    bar_sync(3, 256);
    if (tid == 0) st_release(&cx.gs->ffn_flag, e + 1);
    prof(wg, 6);
  }
}

struct Maps { CUtensorMap m[8]; };
__global__ void __cluster_dims__(2, 1, 1) __launch_bounds__(THREADS, 1)
fused_kernel(const __nv_bfloat16* __restrict__ x, const __nv_bfloat16* __restrict__ w_r, const __nv_bfloat16* __restrict__ wq,
             const __nv_bfloat16* __restrict__ wo, __nv_bfloat16* __restrict__ out, Scratch* gs,
             const __grid_constant__ Maps maps, const __nv_bfloat16* __restrict__ kc) {
  const CUtensorMap &tmX = maps.m[0], &tmWq = maps.m[1], &tmK = maps.m[2], &tmV = maps.m[3], &tmWo = maps.m[4], &tmG = maps.m[5],
                    &tmU = maps.m[6], &tmD = maps.m[7];
  extern __shared__ __align__(1024) uint8_t smem_raw[];
  prof(0, 23, 511);
  Ctx cx;
  cx.sb = smem_u32(smem_raw);
  cx.sp = smem_raw;
  cx.gs = gs;
  cx.rank = blockIdx.x & 1;
  const int warp = __shfl_sync(0xffffffffu, threadIdx.x >> 5, 0);
  const int cluster = blockIdx.x >> 1;
  const bool is_ffn = blockIdx.x >= N_ATT_CTA;
  const int c7 = ((cluster - 36) * 37) >> 8;
  const int hs = cluster < 4 ? 4 + cluster : cluster < 36 ? (cluster - 4) >> 3 : 4 + c7;
  const int qb = (cluster < 4 ? 0 : cluster < 36 ? (cluster - 4) & 7 : cluster - 35 - 7 * c7) * 2 + cx.rank;

  extern __shared__ __align__(1024) uint8_t smem_alias[];
  const uint32_t xf = smem_u32(smem_alias) + SM_MISC + warp * 24;
  if (warp == 4 && elect_one()) prefetch_tmap(&tmX);
  if (warp == 6 && !is_ffn && elect_one()) prefetch_l2(x + (size_t)(qb * 128 + hs * 8) * DM, 8 * DM * 2);
  if (elect_one()) {
    const uint32_t cnt = warp == 3 ? 64 : (warp > 4 && warp < 8 && !is_ffn) ? 4 : 1;
#pragma unroll
    for (int i = 0; i < 3; i++) mbar_init(xf + 8 * i, cnt);
    asm volatile("fence.proxy.async.shared::cta;" ::: "memory");
    asm volatile("fence.mbarrier_init.release.cluster;" ::: "memory");
  }
  __syncwarp();
  cluster_arrive();
  if (warp == 4 && !is_ffn) {
    if (elect_one()) {
      profc(0, 28);
#pragma unroll
      for (int i = 0; i < 3; i++) {
        mbar_expect_tx(xf + 8 * i, 24576);
        tma3d(xf - SM_XFULL + SM_X + i * 24576, &tmX, qb * 128, i * 3, xf + 8 * i);
      }
      profc(0, 29);
    }
  } else if (warp > 8 && elect_one()) {
    prefetch_tmap(&tmX + (is_ffn ? warp - 4 : warp - 8));
  }
  __syncwarp();

  if (warp < 4) {
    asm volatile("setmaxnreg.dec.sync.aligned.u32 24;");
    cluster_wait();
    prof(0, 24, 511);
    if (warp == 0) {
      if (!is_ffn) attn_producer(cx, qb, hs, &tmX, &tmK, &tmV, &tmWq, &tmWo);
      else if (elect_one()) ffn_producer(cx, blockIdx.x - N_ATT_CTA, &tmX, &tmG, &tmU, &tmD);
      prof(0, 25, 511);
    } else if (!is_ffn) {
      attn_gate(cx, qb, hs, threadIdx.x - 32, x);
      if (warp == 1) attn_helper(cx, qb, hs, read_lane(), x, wo);
      else { bar_arrive(BAR_HELPER, 128); attn_stage_xg(cx, qb, hs, threadIdx.x - 64, x); }
      attn_finish8(cx, qb, hs, warp - 1, read_lane(), out);

    }
    __syncwarp();
    cluster_arrive();
    cluster_wait();
  } else {
    asm volatile("setmaxnreg.inc.sync.aligned.u32 240;");
    cluster_wait();
    const int cw = warp - 4, wg = cw >> 2;
    if (is_ffn) ffn_consumer(cx, blockIdx.x - N_ATT_CTA, wg, cw, read_lane(), x, w_r);
    else attn_consumer(cx, qb, hs, wg, cw, read_lane(), x, kc, out);
  }
}

typedef CUresult (*EncodeFn)(CUtensorMap*, CUtensorMapDataType, cuuint32_t, void*, const cuuint64_t*, const cuuint64_t*,
                             const cuuint32_t*, const cuuint32_t*, CUtensorMapInterleave, CUtensorMapSwizzle,
                             CUtensorMapL2promotion, CUtensorMapFloatOOBfill);

void encode(EncodeFn fn, CUtensorMap* m, const void* p, int rank, const cuuint64_t* dims, const cuuint64_t* strides,
            const cuuint32_t* box) {
  const cuuint32_t es[5] = {1, 1, 1, 1, 1};
  fn(m, CU_TENSOR_MAP_DATA_TYPE_BFLOAT16, rank, const_cast<void*>(p), dims, strides, box, es, CU_TENSOR_MAP_INTERLEAVE_NONE,
     CU_TENSOR_MAP_SWIZZLE_128B, CU_TENSOR_MAP_L2_PROMOTION_L2_128B, CU_TENSOR_MAP_FLOAT_OOB_FILL_NONE);
}
void encode2d(EncodeFn fn, CUtensorMap* m, const void* p, uint64_t rows, uint64_t cols, uint32_t box_rows) {
  const cuuint64_t dims[2] = {cols, rows}, strides[1] = {cols * 2};
  const cuuint32_t box[2] = {64, box_rows};
  encode(fn, m, p, 2, dims, strides, box);
}

}

extern "C" void kernel_launch(void* const* d_in, const int* in_sizes, int n_in, void* d_out, int out_size) {
  (void)in_sizes; (void)n_in; (void)out_size;
  void* fnp = nullptr;
  cudaDriverEntryPointQueryResult qr;
  cudaGetDriverEntryPoint("cuTensorMapEncodeTiled", &fnp, cudaEnableDefault, &qr);
  EncodeFn fn = (EncodeFn)fnp;
  Maps maps;
  CUtensorMap &tmX = maps.m[0], &tmWq = maps.m[1], &tmK = maps.m[2], &tmV = maps.m[3], &tmWo = maps.m[4], &tmG = maps.m[5],
              &tmU = maps.m[6], &tmD = maps.m[7];
  encode2d(fn, &tmK, d_in[1], 16 * SEQ, DH, 128);
  encode2d(fn, &tmV, d_in[2], 16 * SEQ, DH, 128);
  encode2d(fn, &tmWq, d_in[3], DM, 4096, 64);
  {
    const cuuint64_t dims[3] = {64, SEQ, 9}, strides[2] = {DM * 2, 128};
    const cuuint32_t box[3] = {64, 64, 3};
    encode(fn, &tmX, d_in[0], 3, dims, strides, box);
  }
  encode2d(fn, &tmWo, d_in[4], 4096, DM, 128);
  encode2d(fn, &tmG, d_in[7], DM, FF, 192);
  encode2d(fn, &tmU, d_in[8], DM, FF, 192);
  encode2d(fn, &tmD, d_in[9], FF, DM, 192);
  cudaFuncSetAttribute(fused_kernel, cudaFuncAttributeMaxDynamicSharedMemorySize, SM_TOTAL);
  void* gs = nullptr;
  cudaGetSymbolAddress(&gs, g_scratch);
  fused_kernel<<<N_CTA, THREADS, SM_TOTAL>>>((const __nv_bfloat16*)d_in[0], (const __nv_bfloat16*)d_in[6], (const __nv_bfloat16*)d_in[3],
                                            (const __nv_bfloat16*)d_in[4], (__nv_bfloat16*)d_out, (Scratch*)gs, maps, (const __nv_bfloat16*)d_in[1]);
}
```

```cpp
#include <cuda_runtime.h>
#include <cuda_bf16.h>
#include <cuda.h>
#include <stdint.h>

namespace {

constexpr int SEQ = 2048, DM = 576, DH = 128, FF = 4608, TOPC = 8;
constexpr int N_ATT_CTA = 128, N_CTA = 132;
constexpr int THREADS = 384;

constexpr uint32_t SM_RING = 0;
constexpr uint32_t STAGE = 32768;
constexpr uint32_t SM_SLOT = 131072;
constexpr uint32_t FSTAGE = 24576;
constexpr uint32_t SM_XSEL = 196608;
constexpr uint32_t SM_H = 205824;
constexpr uint32_t SM_MISC = 229376;
constexpr uint32_t SM_FULL = SM_MISC, SM_BAR_MISC = SM_MISC + 64, SM_BAR_XG = SM_MISC + 72, SM_BAR_P8 = SM_MISC + 80, SM_XFULL = SM_MISC + 96,
                   SM_EMPTY = SM_MISC + 120, SM_TAG = SM_MISC + 288, SM_IDX = SM_MISC + 304, SM_TOPK = SM_MISC + 336,
                   SM_STATS = SM_MISC + 400;
constexpr uint32_t SM_TOTAL = SM_MISC + 1424;
constexpr uint32_t SM_X = SM_MISC - 147456;

constexpr int BAR_GATE = 6, BAR_HELPER = 7, BAR_OA = 8;
constexpr int NST_Q = 20, NST_KV = 128, NST_O = 18;
#define X_ORDER 0
#define X_PF 3
#define X_PFQ 2
#define X_REL 0
#define X_SLEEP8 700
#define X_N1 4
#define X_SPLIT 44
#define X_PARK 5
#define X_HO 9
#define X_C0 32
#define X_C1 56
constexpr float SM_SCALE_LOG2 = 0.08838834764831845f * 1.4426950408889634f;

struct Scratch {
  uint4 part[16 * 64 * 2 * 4 * 128];
  uint4 gate[N_ATT_CTA * 144 * 8];
  float r[SEQ];
  float2 stats[SEQ];
  float ypart[4 * TOPC * DM];
  float upd[TOPC * DM];
  int idx[32];
  unsigned launch[160];
  unsigned rcnt, pad0[31], ycnt, pad1[31], ffn_flag, pad2[31];
};
__device__ __align__(1024) Scratch g_scratch;

__device__ __forceinline__ void profq(int) {}
__device__ __forceinline__ void prof(int, int, int = 0) {}
__device__ __forceinline__ void profc(int, int) {}

__device__ __forceinline__ uint32_t smem_u32(const void* p) { return (uint32_t)__cvta_generic_to_shared(p); }
__device__ __forceinline__ void mbar_init(uint32_t bar, uint32_t cnt) {
  asm volatile("mbarrier.init.shared::cta.b64 [%0], %1;" ::"r"(bar), "r"(cnt) : "memory");
}
__device__ __forceinline__ void mbar_expect_tx(uint32_t bar, uint32_t bytes) {
  asm volatile("mbarrier.arrive.expect_tx.shared::cta.b64 _, [%0], %1;" ::"r"(bar), "r"(bytes) : "memory");
}
__device__ __forceinline__ void mbar_arrive(uint32_t bar) {
  asm volatile("mbarrier.arrive.shared::cta.b64 _, [%0];" ::"r"(bar) : "memory");
}
__device__ __forceinline__ void mbar_arrive_cluster(uint32_t bar_cluster_addr) {
  asm volatile("mbarrier.arrive.shared::cluster.b64 _, [%0];" ::"r"(bar_cluster_addr) : "memory");
}
template <int ID>
__device__ __forceinline__ void mbar_arrive_cluster_now(uint32_t bar_cluster_addr, bool pred, uint32_t zero) {
  asm volatile("{\n.reg .pred p, q;\nsetp.ne.u32 p, %1, 0;\nsetp.eq.u32 q, %2, %3;\n"
               "ARR_LOOP:\n@p mbarrier.arrive.shared::cluster.b64 _, [%0];\n@q bra.uni ARR_LOOP;\n}"
               ::"r"(bar_cluster_addr), "r"((uint32_t)pred), "r"(zero), "n"(ID) : "memory");
}
__device__ __forceinline__ void block_fence(int id, uint32_t zero = blockIdx.y) {
  asm volatile("{\n.reg .pred q;\nsetp.eq.u32 q, %0, %1;\nBF_LOOP:\n@q st.volatile.shared.u32 [%0], %0;\n@q bra.uni BF_LOOP;\n}"
               ::"r"(zero), "r"(id) : "memory");
}
__device__ __forceinline__ bool mbar_test(uint32_t bar, uint32_t parity) {
  uint32_t ok;
  asm volatile("{\n.reg .pred p;\nmbarrier.test_wait.parity.shared::cta.b64 p, [%1], %2;\nselp.u32 %0, 1, 0, p;\n}"
               : "=r"(ok) : "r"(bar), "r"(parity) : "memory");
  return ok;
}
__device__ __forceinline__ void mbar_wait(uint32_t bar, uint32_t parity) {
  asm volatile("{\n.reg .pred p, q;\n.reg .u32 n;\nmov.u32 n, 0;\n"
               "WAIT_LOOP:\nmbarrier.try_wait.parity.shared::cta.b64 p, [%0], %1;\n"
               "add.u32 n, n, 1;\nsetp.lt.u32 q, n, 4194304;\nand.pred q, q, !p;\n@q bra WAIT_LOOP;\n}"
               ::"r"(bar), "r"(parity) : "memory");
}
__device__ __forceinline__ uint32_t mapa(uint32_t addr, uint32_t rank) {
  uint32_t r;
  asm volatile("mapa.shared::cluster.u32 %0, %1, %2;" : "=r"(r) : "r"(addr), "r"(rank));
  return r;
}
__device__ __forceinline__ void cluster_arrive() { asm volatile("barrier.cluster.arrive.relaxed.aligned;" ::: "memory"); }
__device__ __forceinline__ bool elect_one() {
  uint32_t p;
  asm volatile("{\n.reg .pred p;\nelect.sync _|p, 0xffffffff;\nselp.u32 %0, 1, 0, p;\n}" : "=r"(p));
  return p;
}
__device__ __forceinline__ int read_lane() { return threadIdx.x & 31; }
__device__ __forceinline__ void cluster_wait() { asm volatile("barrier.cluster.wait.acquire.aligned;" ::: "memory"); }
__device__ __forceinline__ void bar_sync(int id, int n) { asm volatile("barrier.cta.sync %0, %1;" ::"r"(id), "r"(n) : "memory"); }
__device__ __forceinline__ void bar_arrive(int id, int n) { asm volatile("barrier.cta.arrive %0, %1;" ::"r"(id), "r"(n) : "memory"); }

__device__ __forceinline__ uint64_t policy_evict_first() {
  uint64_t p;
  asm("createpolicy.fractional.L2::evict_first.b64 %0, 1.0;" : "=l"(p));
  return p;
}
__device__ __forceinline__ uint64_t policy_evict_normal() {
  uint64_t p;
  asm("createpolicy.fractional.L2::evict_normal.b64 %0, 1.0;" : "=l"(p));
  return p;
}
__device__ __forceinline__ void tma2d_mc(uint32_t dst, const CUtensorMap* tm, int c0, int c1, uint32_t bar, uint64_t pol) {
  asm volatile("cp.async.bulk.tensor.2d.shared::cluster.global.mbarrier::complete_tx::bytes.multicast::cluster.L2::cache_hint"
               " [%0], [%1, {%2, %3}], [%4], %5, %6;"
               ::"r"(dst), "l"(tm), "r"(c0), "r"(c1), "r"(bar), "h"((uint16_t)3), "l"(pol) : "memory");
}
__device__ __forceinline__ void tma3d(uint32_t dst, const CUtensorMap* tm, int c1, int c2, uint32_t bar) {
  asm volatile("cp.async.bulk.tensor.3d.shared::cluster.global.mbarrier::complete_tx::bytes [%0], [%1, {%2, %3, %4}], [%5];"
               ::"r"(dst), "l"(tm), "r"(0), "r"(c1), "r"(c2), "r"(bar) : "memory");
}
__device__ __forceinline__ void tma2d_stream(uint32_t dst, const CUtensorMap* tm, int c0, int c1, uint32_t bar) {
  asm volatile("{\n.reg .b64 pol;\ncreatepolicy.fractional.L2::evict_first.b64 pol, 1.0;\n"
               "cp.async.bulk.tensor.2d.shared::cluster.global.mbarrier::complete_tx::bytes.L2::cache_hint [%0], [%1, {%2, %3}], [%4], pol;\n}"
               ::"r"(dst), "l"(tm), "r"(c0), "r"(c1), "r"(bar) : "memory");
}
__device__ __forceinline__ void tma2d_prefetch(const CUtensorMap* tm, int c0, int c1) {
  asm volatile("cp.async.bulk.prefetch.tensor.2d.L2.global [%0, {%1, %2}];" ::"l"(tm), "r"(c0), "r"(c1) : "memory");
}
__device__ __forceinline__ void prefetch_l2(const void* p, uint32_t bytes) {
  asm volatile("cp.async.bulk.prefetch.L2.global [%0], %1;" ::"l"(p), "r"(bytes) : "memory");
}
__device__ __forceinline__ void prefetch_tmap(const CUtensorMap* tm) {
  asm volatile("prefetch.tensormap [%0];" ::"l"(tm) : "memory");
}

__device__ __forceinline__ void wg_fence() { asm volatile("wgmma.fence.sync.aligned;" ::: "memory"); }
__device__ __forceinline__ void wg_commit() { asm volatile("wgmma.commit_group.sync.aligned;" ::: "memory"); }
template <int N> __device__ __forceinline__ void wg_wait() { asm volatile("wgmma.wait_group.sync.aligned %0;" ::"n"(N) : "memory"); }

__device__ __forceinline__ uint64_t mkdesc(uint32_t addr, uint32_t lbo_bytes) {
  return (uint64_t)(((addr & 0x3FFFF) >> 4) | ((lbo_bytes >> 4) << 16)) | ((uint64_t)0x40000040u << 32);
}
template <int N> __device__ __forceinline__ void pin(float (&a)[N]) {
#pragma unroll
  for (int i = 0; i < N; i++) asm volatile("" : "+f"(a[i])::"memory");
}
template <int N> __device__ __forceinline__ void pin(uint32_t (&a)[N]) {
#pragma unroll
  for (int i = 0; i < N; i++) asm volatile("" : "+r"(a[i])::"memory");
}

#define F8(d, o) "+f"(d[o]), "+f"(d[o + 1]), "+f"(d[o + 2]), "+f"(d[o + 3]), "+f"(d[o + 4]), "+f"(d[o + 5]), "+f"(d[o + 6]), "+f"(d[o + 7])
#define R32A "%0, %1, %2, %3, %4, %5, %6, %7, %8, %9, %10, %11, %12, %13, %14, %15, %16, %17, %18, %19, %20, %21, %22, %23, %24, %25, %26, %27, %28, %29, %30, %31"
#define R32B "%32, %33, %34, %35, %36, %37, %38, %39, %40, %41, %42, %43, %44, %45, %46, %47, %48, %49, %50, %51, %52, %53, %54, %55, %56, %57, %58, %59, %60, %61, %62, %63"

template <int TB>
__device__ __forceinline__ void mma_n128(float (&d)[64], uint32_t a0, uint32_t a1, uint32_t a2, uint32_t a3, uint64_t db, int acc) {
  asm volatile("{\n.reg .pred p;\nsetp.ne.b32 p, %69, 0;\n"
               "wgmma.mma_async.sync.aligned.m64n128k16.f32.bf16.bf16 {" R32A ", " R32B "}, {%64, %65, %66, %67}, %68, p, 1, 1, %70;\n}\n"
               : F8(d, 0), F8(d, 8), F8(d, 16), F8(d, 24), F8(d, 32), F8(d, 40), F8(d, 48), F8(d, 56)
               : "r"(a0), "r"(a1), "r"(a2), "r"(a3), "l"(db), "r"(acc), "n"(TB));
}
template <int TB>
__device__ __forceinline__ void mma_n128_ss(float (&d)[64], uint64_t da, uint64_t db, int acc) {
  asm volatile("{\n.reg .pred p;\nsetp.ne.b32 p, %66, 0;\n"
               "wgmma.mma_async.sync.aligned.m64n128k16.f32.bf16.bf16 {" R32A ", " R32B "}, %64, %65, p, 1, 1, 0, %67;\n}\n"
               : F8(d, 0), F8(d, 8), F8(d, 16), F8(d, 24), F8(d, 32), F8(d, 40), F8(d, 48), F8(d, 56)
               : "l"(da), "l"(db), "r"(acc), "n"(TB));
}
__device__ __forceinline__ void mma_n64t(float (&d)[32], uint32_t a0, uint32_t a1, uint32_t a2, uint32_t a3, uint64_t db, int acc) {
  asm volatile("{\n.reg .pred p;\nsetp.ne.b32 p, %37, 0;\n"
               "wgmma.mma_async.sync.aligned.m64n64k16.f32.bf16.bf16 {" R32A "}, {%32, %33, %34, %35}, %36, p, 1, 1, 1;\n}\n"
               : F8(d, 0), F8(d, 8), F8(d, 16), F8(d, 24)
               : "r"(a0), "r"(a1), "r"(a2), "r"(a3), "l"(db), "r"(acc));
}
__device__ __forceinline__ void mma_n8(float (&d)[4], uint64_t da, uint64_t db, int acc) {
  asm volatile("{\n.reg .pred p;\nsetp.ne.b32 p, %6, 0;\n"
               "wgmma.mma_async.sync.aligned.m64n8k16.f32.bf16.bf16 {%0, %1, %2, %3}, %4, %5, p, 1, 1, 1, 0;\n}\n"
               : "+f"(d[0]), "+f"(d[1]), "+f"(d[2]), "+f"(d[3])
               : "l"(da), "l"(db), "r"(acc));
}
__device__ __forceinline__ void hmma_k8(float (&d)[4], uint32_t a0, uint32_t a1, uint32_t b0) {
  asm volatile("mma.sync.aligned.m16n8k8.row.col.f32.bf16.bf16.f32 {%0, %1, %2, %3}, {%4, %5}, {%6}, {%0, %1, %2, %3};"
               : "+f"(d[0]), "+f"(d[1]), "+f"(d[2]), "+f"(d[3]) : "r"(a0), "r"(a1), "r"(b0));
}
__device__ __forceinline__ void hmma_k16(float (&d)[4], uint32_t a0, uint32_t a1, uint32_t a2, uint32_t a3, uint32_t b0, uint32_t b1) {
  asm volatile("mma.sync.aligned.m16n8k16.row.col.f32.bf16.bf16.f32 {%0, %1, %2, %3}, {%4, %5, %6, %7}, {%8, %9}, {%0, %1, %2, %3};"
               : "+f"(d[0]), "+f"(d[1]), "+f"(d[2]), "+f"(d[3]) : "r"(a0), "r"(a1), "r"(a2), "r"(a3), "r"(b0), "r"(b1));
}

__device__ __forceinline__ uint32_t pack2(float lo, float hi) {
  uint32_t r;
  asm("cvt.rn.bf16x2.f32 %0, %1, %2;" : "=r"(r) : "f"(hi), "f"(lo));
  return r;
}
__device__ __forceinline__ float bf_lo(uint32_t w) { return __uint_as_float(w << 16); }
__device__ __forceinline__ float bf_hi(uint32_t w) { return __uint_as_float(w & 0xFFFF0000u); }
__device__ __forceinline__ float bfr(float x) { return __bfloat162float(__float2bfloat16_rn(x)); }
__device__ __forceinline__ uint32_t sub2(uint32_t a, uint32_t b) {
  uint32_t r;
  asm("sub.rn.bf16x2 %0, %1, %2;" : "=r"(r) : "r"(a), "r"(b));
  return r;
}
__device__ __forceinline__ uint32_t add2(uint32_t a, uint32_t b) {
  uint32_t r;
  asm("add.rn.bf16x2 %0, %1, %2;" : "=r"(r) : "r"(a), "r"(b));
  return r;
}
__device__ __forceinline__ float ex2(float x) {
  float r;
  asm("ex2.approx.ftz.f32 %0, %1;" : "=f"(r) : "f"(x));
  return r;
}
__device__ __forceinline__ float rcp(float x) {
  float r;
  asm("rcp.approx.ftz.f32 %0, %1;" : "=f"(r) : "f"(x));
  return r;
}
__device__ __forceinline__ float silu_f(float t) { return t * rcp(1.0f + ex2(-1.4426950408889634f * t)); }
__device__ __forceinline__ void sts128(uint32_t a, uint32_t x, uint32_t y, uint32_t z, uint32_t w) {
  asm volatile("st.shared.v4.u32 [%0], {%1, %2, %3, %4};" ::"r"(a), "r"(x), "r"(y), "r"(z), "r"(w) : "memory");
}
__device__ __forceinline__ void lds128(uint32_t a, uint32_t& x, uint32_t& y, uint32_t& z, uint32_t& w) {
  asm volatile("ld.shared.v4.u32 {%0, %1, %2, %3}, [%4];" : "=r"(x), "=r"(y), "=r"(z), "=r"(w) : "r"(a) : "memory");
}
__device__ __forceinline__ void ldsm4(uint32_t a, uint32_t& x, uint32_t& y, uint32_t& z, uint32_t& w) {
  asm volatile("ldmatrix.sync.aligned.m8n8.x4.shared.b16 {%0, %1, %2, %3}, [%4];" : "=r"(x), "=r"(y), "=r"(z), "=r"(w) : "r"(a) : "memory");
}
__device__ __forceinline__ void st_gran(uint4* p, uint32_t x, uint32_t y, uint32_t z, uint32_t w) {
  asm volatile("st.relaxed.gpu.global.v4.b32 [%0], {%1, %2, %3, %4};" ::"l"(p), "r"(x), "r"(y), "r"(z), "r"(w) : "memory");
}
__device__ __forceinline__ void ld_gran(const uint4* p, uint32_t& x, uint32_t& y, uint32_t& z, uint32_t& w) {
  asm volatile("ld.relaxed.gpu.global.v4.b32 {%0, %1, %2, %3}, [%4];" : "=r"(x), "=r"(y), "=r"(z), "=r"(w) : "l"(p) : "memory");
}
__device__ __forceinline__ void stsm4(uint32_t a, uint32_t x, uint32_t y, uint32_t z, uint32_t w) {
  asm volatile("stmatrix.sync.aligned.m8n8.x4.shared.b16 [%0], {%1, %2, %3, %4};" ::"r"(a), "r"(x), "r"(y), "r"(z), "r"(w) : "memory");
}
__device__ __forceinline__ void cp16(uint32_t dst, const void* src) {
  asm volatile("cp.async.cg.shared.global [%0], [%1], 16;" ::"r"(dst), "l"(src) : "memory");
}
template <class T>
__device__ __forceinline__ T* at(const void* base, uint32_t off) {
  uint64_t r;
  asm("{\n.reg .u32 lo, hi;\nmov.b64 {lo, hi}, %1;\nadd.cc.u32 lo, lo, %2;\naddc.u32 hi, hi, 0;\nmov.b64 %0, {lo, hi};\n}"
      : "=l"(r) : "l"(base), "r"(off));
  return (T*)__cvta_global_to_generic(r);
}
__device__ __forceinline__ void cp_wait_all() { asm volatile("cp.async.wait_all;" ::: "memory"); }
__device__ __forceinline__ void add_granules(float (&red)[32], const uint32_t (&g)[16]) {
#pragma unroll
  for (int i = 0; i < 16; i++) { red[2 * i] += bf_lo((i & 3) ? g[i] : g[i] & ~1u); red[2 * i + 1] += bf_hi(g[i]); }
}
__device__ __forceinline__ bool granules_ok(const uint32_t (&g)[16], uint32_t tag) {
  return __all_sync(0xffffffffu, (((g[0] ^ tag) | (g[4] ^ tag) | (g[8] ^ tag) | (g[12] ^ tag)) & 1) == 0);
}
__device__ __forceinline__ unsigned ld_acquire(const unsigned* p) {
  unsigned v;
  asm volatile("ld.acquire.gpu.global.u32 %0, [%1];" : "=r"(v) : "l"(p) : "memory");
  return v;
}
__device__ __forceinline__ unsigned atom_add_acq_rel(unsigned* p) {
  unsigned v;
  asm volatile("atom.acq_rel.gpu.global.add.u32 %0, [%1], 1;" : "=r"(v) : "l"(p) : "memory");
  return v;
}
__device__ __forceinline__ void st_release(unsigned* p, unsigned v) {
  asm volatile("st.release.gpu.global.u32 [%0], %1;" ::"l"(p), "r"(v) : "memory");
}

struct LnAcc {
  float sm[2][4], sq[8][4];
  __device__ __forceinline__ void clear() {
#pragma unroll
    for (int i = 0; i < 4; i++) {
      sm[0][i] = sm[1][i] = 0.f;
#pragma unroll
      for (int j = 0; j < 8; j++) sq[j][i] = 0.f;
    }
  }
};
template <int K0, int K1>
__device__ __forceinline__ void ln_fetch(uint32_t (&xa)[144], uint32_t boxes, uint32_t lo) {
#pragma unroll
  for (int k = K0; k < K1; k++) ldsm4(boxes + (k >> 2) * 8192 + (lo ^ ((k & 3) << 5)), xa[4 * k], xa[4 * k + 1], xa[4 * k + 2], xa[4 * k + 3]);
}
__device__ __forceinline__ void ln_accum1(LnAcc& a, int h, uint32_t x0, uint32_t x1, uint32_t x2, uint32_t x3) {
  const uint32_t ONES = 0x3F803F80u;
  hmma_k16(a.sm[h], x0, x1, x2, x3, ONES, ONES);
  hmma_k8(a.sq[4 * h], x0, x1, x0);
  hmma_k8(a.sq[4 * h + 1], x0, x1, x1);
  hmma_k8(a.sq[4 * h + 2], x2, x3, x2);
  hmma_k8(a.sq[4 * h + 3], x2, x3, x3);
}
template <int K0, int K1>
__device__ __forceinline__ void ln_accum(const uint32_t (&xa)[144], LnAcc& a) {
#pragma unroll
  for (int k = K0; k < K1; k++) ln_accum1(a, k & 1, xa[4 * k], xa[4 * k + 1], xa[4 * k + 2], xa[4 * k + 3]);
}
template <int K0, int K1>
__device__ __forceinline__ void ln_sums(const uint32_t (&xa)[144], float (&sm)[4][4]) {
#pragma unroll
  for (int k = K0; k < K1; k++) hmma_k16(sm[k & 3], xa[4 * k], xa[4 * k + 1], xa[4 * k + 2], xa[4 * k + 3], 0x3F803F80u, 0x3F803F80u);
}
__device__ __forceinline__ uint32_t sq8(const uint32_t* a) {
  uint32_t t, u;
  asm("mul.rn.bf16x2 %0, %1, %1;" : "=r"(t) : "r"(a[0]));
  asm("mul.rn.bf16x2 %0, %1, %1;" : "=r"(u) : "r"(a[2]));
#pragma unroll
  for (int i = 4; i < 16; i += 4) {
    asm("fma.rn.bf16x2 %0, %1, %1, %0;" : "+r"(t) : "r"(a[i]));
    asm("fma.rn.bf16x2 %0, %1, %1, %0;" : "+r"(u) : "r"(a[i + 2]));
  }
  return add2(t, u);
}
__device__ __forceinline__ void ln_centre(uint32_t (&xa)[144], int j0, int j1, uint32_t mm0, uint32_t mm1, float& sq0, float& sq1) {
#pragma unroll
  for (int j = 0; j < 72; j += 8)
    if (j >= j0 && j < j1) {
#pragma unroll
      for (int k = j; k < j + 8; k++) {
        xa[2 * k] = sub2(xa[2 * k], mm0);
        xa[2 * k + 1] = sub2(xa[2 * k + 1], mm1);
      }
      const uint32_t t0 = sq8(xa + 2 * j), t1 = sq8(xa + 2 * j + 1);
      sq0 += bf_lo(t0) + bf_hi(t0);
      sq1 += bf_lo(t1) + bf_hi(t1);
    }
}
__device__ __forceinline__ float ln_rstd(float msq, float d) {
  float sd;
  asm("sqrt.approx.f32 %0, %1;" : "=f"(sd) : "f"(bfr(bfr(fmaxf(msq - d * d, 0.0f)) + 1e-5f)));
  return rcp(bfr(sd));
}
__device__ __forceinline__ void ln_row(float sum, float sq, float& mean_b, float& rstd) {
  const float mean = sum * (1.0f / DM);
  mean_b = bfr(mean);
  rstd = ln_rstd(sq * (1.0f / DM), mean);
}
__device__ __forceinline__ void ln_diag(const LnAcc& a, int lane, float& t0, float& t1) {
  const bool odd = (lane >> 2) & 1;
  t0 = odd ? (a.sq[0][1] + a.sq[2][1]) + (a.sq[4][1] + a.sq[6][1]) : (a.sq[0][0] + a.sq[2][0]) + (a.sq[4][0] + a.sq[6][0]);
  t1 = odd ? (a.sq[1][3] + a.sq[3][3]) + (a.sq[5][3] + a.sq[7][3]) : (a.sq[1][2] + a.sq[3][2]) + (a.sq[5][2] + a.sq[7][2]);
}
__device__ __forceinline__ void ln_stats(const LnAcc& a, int lane, float& mean0, float& rstd0, float& mean1, float& rstd1) {
  float t0, t1;
  ln_diag(a, lane, t0, t1);
  const int src = (lane & ~3) | (lane >> 3);
  t0 = __shfl_sync(0xffffffffu, t0, src);
  t1 = __shfl_sync(0xffffffffu, t1, src);
  ln_row(a.sm[0][0] + a.sm[1][0], t0, mean0, rstd0);
  ln_row(a.sm[0][2] + a.sm[1][2], t1, mean1, rstd1);
}

template <bool ROUTED>
__device__ __forceinline__ uint32_t gate2(uint32_t x2, float mean_b, float rstd, float2 upd = make_float2(0.f, 0.f)) {
  const uint32_t xc = sub2(x2, pack2(mean_b, mean_b));
  uint32_t t = pack2(bf_lo(xc) * rstd, bf_hi(xc) * rstd);
  if (ROUTED) t = pack2(bf_lo(t) + upd.x, bf_hi(t) + upd.y);
  return pack2(silu_f(bf_lo(t)), silu_f(bf_hi(t)));
}

template <int V> struct IC { static constexpr int value = V; };

struct Ctx {
  uint32_t sb;
  uint8_t* sp;
  uint32_t rank;
  Scratch* gs;
};

__device__ __forceinline__ void dly(int) {}
template <int BOXES>
__device__ __forceinline__ void load_stage(uint32_t dst, const CUtensorMap* tm, int c0, int c1, uint32_t bar, uint32_t bytes, uint64_t pol) {
  asm volatile("{\n.reg .pred p;\nelect.sync _|p, 0xffffffff;\n"
               "@p mbarrier.arrive.expect_tx.shared::cta.b64 _, [%4], %7;\n"
               "@p cp.async.bulk.tensor.2d.shared::cluster.global.mbarrier::complete_tx::bytes.multicast::cluster.L2::cache_hint"
               " [%0], [%1, {%2, %3}], [%4], %5, %6;\n}"
               ::"r"(dst), "l"(tm), "r"(c0), "r"(c1), "r"(bar), "h"((uint16_t)3), "l"(pol), "r"(bytes) : "memory");
  if (BOXES == 2)
    asm volatile("{\n.reg .pred p;\nelect.sync _|p, 0xffffffff;\n"
                 "@p cp.async.bulk.tensor.2d.shared::cluster.global.mbarrier::complete_tx::bytes.multicast::cluster.L2::cache_hint"
                 " [%0], [%1, {%2, %3}], [%4], %5, %6;\n}"
                 ::"r"(dst + 8192), "l"(tm), "r"(c0), "r"(c1 + 64), "r"(bar), "h"((uint16_t)3), "l"(pol) : "memory");
}
__device__ __forceinline__ void attn_producer(const Ctx& cx, int qb, int hs, const CUtensorMap* tmX, const CUtensorMap* tmK,
                                              const CUtensorMap* tmV, const CUtensorMap* tmWq, const CUtensorMap* tmWo) {
  const uint32_t full = cx.sb + SM_FULL, empty = cx.sb + SM_EMPTY, ring = cx.sb + SM_RING + cx.rank * 16384;
  const uint64_t keep = policy_evict_normal(), last_use = policy_evict_first();
  auto acquire = [&](int st) {
    mbar_wait(empty + 8 * (st & 3), ((st >> 2) ^ ((st & 3) >> 1) ^ 1) & 1);
    dly(st);
  };
  if (elect_one()) {
#pragma unroll
    for (int j = 0; j < 3; j++) {
      mbar_expect_tx(cx.sb + SM_XFULL + 96 + 8 * j, 24576);
      tma3d(cx.sb + SM_X + 73728 + j * 24576, tmX, qb * 128 + 64, j * 3, cx.sb + SM_XFULL + 96 + 8 * j);
    }
  }
  __syncwarp();
#pragma unroll 1
  for (int p = 0; p < 4; p++) {
    const int n0 = (hs * 4 + ((0x1320 >> (4 * p)) & 3)) * DH + cx.rank * 64;
#pragma unroll
    for (int i = 0; i < 5; i++) {
      const int st = 5 * p + i, sl = st & 3;
      if (i == 4 && p == 3) break;
      acquire(st);
      if (i == 2) load_stage<1>(ring + sl * STAGE, tmWq, n0, 256, full + 8 * sl, 16384, last_use);
      else load_stage<2>(ring + sl * STAGE, tmWq, n0, i < 2 ? 128 * i : 128 * i - 64, full + 8 * sl, 32768, last_use);
      if (i == X_PFQ && p == 0 && elect_one()) {
#pragma unroll 1
        for (int b = 8 + qb; b < 72; b += 16) {
          const int bp = (b * 57) >> 10;
          tma2d_prefetch(tmWq, (hs * 4 + ((0x1320 >> (4 * bp)) & 3)) * DH + (b & 1) * 64, ((b - 18 * bp) >> 1) * 64);
        }
      }
      __syncwarp();
    }
  }
  const int c0 = cx.rank * 64;
  int vrow = 0;
  uint64_t vpol = keep;
#pragma unroll 1
  for (int j = 0; j < 32; j++) {
    const int st = NST_Q - 1 + 4 * j, row = (hs * 2 + (j >> 4)) * SEQ + (j & 7) * 256;
    const uint64_t pol = (j & 8) ? last_use : keep;
    acquire(st);
    load_stage<1>(ring + 3 * STAGE, tmK, c0, row, full + 24, 32768, pol);
    acquire(st + 1);
    if (j) load_stage<1>(ring, tmV, c0, vrow, full, 32768, vpol);
    else load_stage<2>(ring, tmWq, (hs * 4 + 1) * DH + c0, 448, full, 32768, last_use);
    vrow = row + 128;
    vpol = pol;
    acquire(st + 2);
    load_stage<1>(ring + STAGE, tmK, c0, vrow, full + 8, 32768, pol);
    acquire(st + 3);
    load_stage<1>(ring + 2 * STAGE, tmV, c0, row, full + 16, 32768, pol);
  }
  acquire(NST_Q + NST_KV - 1);
  load_stage<1>(ring + 3 * STAGE, tmV, c0, vrow, full + 24, 32768, last_use);
#pragma unroll 1
  for (int u = 0; u < NST_O; u++) {
    const int st = NST_Q + NST_KV + u, sl = st & 3;
    const int blk = u < 4 && cx.rank ? 8 : ((hs + max(u >> 1, 1)) & 7);
    const int head = u < 4 ? u ^ (u >> 1) : ((u & 1) * 2 + cx.rank + 3) & 3;
    acquire(st);
    load_stage<1>(ring + sl * STAGE, tmWo, blk * 64, hs * 512 + head * 128, full + 8 * sl, 32768, last_use);
  }
}

__device__ __forceinline__ void attn_gate(const Ctx& cx, int qb, int hs, int t, const __nv_bfloat16* x) {
  const uint32_t base = (qb * 128 * DM + (t & 7) * 8) * 2;
  uint32_t lr = t >> 3;
  uint4 nx = __ldg(at<const uint4>(x, base + (lr * DM + hs * 64) * 2));
  bar_sync(BAR_GATE, 352);
#pragma unroll 1
  for (uint32_t n = t >> 3; n < 144;) {
    const uint4 v = nx;
    const float2 st = *(const float2*)(cx.sp + SM_STATS + 8 * lr);
    uint4* dst = at<uint4>(cx.gs->gate, (blockIdx.x * 144 + n) * 128 + (((t ^ n) & 7) << 4));
    n += 12;
    lr = n < 128 ? n : n + hs * 16 - 128;
    if (n < 144) nx = __ldg(at<const uint4>(x, base + (lr * DM + (n < 128 ? hs * 64 : 512)) * 2));
    *dst = make_uint4(gate2<false>(v.x, st.x, st.y), gate2<false>(v.y, st.x, st.y), gate2<false>(v.z, st.x, st.y), gate2<false>(v.w, st.x, st.y));
  }
  asm volatile("fence.proxy.async;" ::: "memory");
}

constexpr uint32_t SM_XO = SM_SLOT, SM_GO = SM_SLOT + STAGE, SM_P8 = SM_SLOT + 2 * STAGE;
__device__ __forceinline__ void attn_helper(const Ctx& cx, int qb, int hs, int lane, const __nv_bfloat16* x, const __nv_bfloat16* wo,
                                            const CUtensorMap* tmX16) {
  unsigned e = 0;
  if (lane == 0) {
    e = cx.gs->launch[blockIdx.x];
    cx.gs->launch[blockIdx.x] = e + 1;
  }
  e = __shfl_sync(0xffffffffu, e, 0);
  if (lane == 0) {
    *(uint32_t*)(cx.sp + SM_TAG) = ~e & 1;
    mbar_arrive(cx.sb + SM_BAR_MISC);
  }
  bar_sync(BAR_HELPER, 128);
  prefetch_l2(at<const void>(wo, (hs * 512 + qb * 32 + lane) * (DM * 2)), DM * 2);
#pragma unroll 1
  for (int n = 0; n < (1 << 16) && ld_acquire(&cx.gs->ffn_flag) != e + 1; n++) __nanosleep(1000);
#pragma unroll 1
  for (int i = 0; i < 2 * TOPC; i++) {
    const int lr = __ldcg(&cx.gs->idx[i >> 1]) - qb * 128, col = ((i & 1) ? 512 : hs * 64) + 2 * lane;
    if ((i & 1) ? (lr >> 4) == hs : (lr >> 7) == 0) {
      const float2 st = *(const float2*)(cx.sp + SM_STATS + 8 * lr);
      *at<uint32_t>(cx.gs->gate, (blockIdx.x * 144 + ((i & 1) ? 128 + (lr & 15) : lr)) * 128 + ((((lane >> 2) ^ lr) & 7) << 4) + (lane & 3) * 4) =
          gate2<true>(*at<const uint32_t>(x, ((qb * 128 + lr) * DM + col) * 2), st.x, st.y,
                      __ldcg(at<const float2>(cx.gs->upd, ((i >> 1) * DM + col) * 4)));
    }
  }
  asm volatile("fence.proxy.async;" ::: "memory");
  bar_sync(BAR_OA, 352);
  if (elect_one()) {
    const uint32_t bar = cx.sb + SM_BAR_XG;
    mbar_expect_tx(bar, 2 * 144 * 128);
    asm volatile("cp.async.bulk.shared::cluster.global.mbarrier::complete_tx::bytes [%0], [%1], %2, [%3];"
                 ::"r"(cx.sb + SM_GO), "l"(cx.gs->gate + blockIdx.x * (144 * 8)), "n"(144 * 128), "r"(bar) : "memory");
#pragma unroll 1
    for (int i = 0; i < 9; i++) tma2d_stream(cx.sb + SM_XO + i * 2048, tmX16, i < 8 ? hs * 64 : 512, qb * 128 + (i < 8 ? i : hs) * 16, bar);
  }
  __syncwarp();
  const uint4* src = cx.gs->part + (qb * 64 + 56 + hs) * 1024;
#pragma unroll 1
  for (int n = 0; n < (1 << 16); n++) {
    __nanosleep(n ? 400 : X_SLEEP8);
    uint32_t a, b, d, t;
    ld_gran(at<const uint4>(src, (lane & 7) * 2048 + 2032), a, b, d, t);
    if (__all_sync(0xffffffffu, (a ^ e) & 1)) break;
  }
  if (elect_one()) {
    mbar_expect_tx(cx.sb + SM_BAR_P8, 16384);
    asm volatile("cp.async.bulk.shared::cluster.global.mbarrier::complete_tx::bytes [%0], [%1], 16384, [%2];"
                 ::"r"(cx.sb + SM_P8), "l"(src), "r"(cx.sb + SM_BAR_P8) : "memory");
  }
  __syncwarp();
}
__device__ __forceinline__ void attn_finish8(const Ctx& cx, int qb, int hs, int hw, int lane, __nv_bfloat16* out) {
  const uint32_t tag = *(const uint32_t*)(cx.sp + SM_TAG);
  mbar_wait(cx.sb + SM_BAR_P8, 0);
  mbar_wait(cx.sb + SM_BAR_XG, 0);
#pragma unroll 1
  for (int g = 2 - hw; g < 4; g += 3) {
    float acc[8] = {0.f, 0.f, 0.f, 0.f, 0.f, 0.f, 0.f, 0.f};
    uint32_t a[4];
#pragma unroll 1
    for (uint32_t o = g * 512 + lane * 16; o < 16384; o += 2048) {
      lds128(cx.sb + SM_P8 + o, a[0], a[1], a[2], a[3]);
#pragma unroll 1
      for (int n = 0; n < (1 << 16) && __any_sync(0xffffffffu, (a[0] & 1) != tag); n++)
        ld_gran(at<const uint4>(cx.gs->part, (qb * 64 + 56 + hs) * 16384 + o), a[0], a[1], a[2], a[3]);
      a[0] &= ~1u;
#pragma unroll
      for (int j = 0; j < 4; j++) { acc[2 * j] += bf_lo(a[j]); acc[2 * j + 1] += bf_hi(a[j]); }
    }
    asm volatile("" : "+r"(lane));
    const uint32_t tile = cx.sb + SM_XO + (128 + (lane & 15)) * 128 + (((lane >> 4) ^ (lane & 7)) << 4);
    ldsm4((tile ^ (g << 5)) + STAGE, a[0], a[1], a[2], a[3]);
#pragma unroll
    for (int j = 0; j < 4; j++) { acc[2 * j] *= bf_lo(a[j]); acc[2 * j + 1] *= bf_hi(a[j]); }
    ldsm4(tile ^ (g << 5), a[0], a[1], a[2], a[3]);
    stsm4(tile ^ (g << 5), pack2(acc[0] + bf_lo(a[0]), acc[1] + bf_hi(a[0])), pack2(acc[2] + bf_lo(a[1]), acc[3] + bf_hi(a[1])),
          pack2(acc[4] + bf_lo(a[2]), acc[5] + bf_hi(a[2])), pack2(acc[6] + bf_lo(a[3]), acc[7] + bf_hi(a[3])));
  }
  bar_sync(BAR_GATE, 96);
#pragma unroll 1
  for (int ch = hw * 32 + lane; ch < 128; ch += 96)
    *at<uint4>(out, ((qb * 128 + hs * 16 + (ch >> 3)) * DM + 512 + (ch & 7) * 8) * 2) =
        *(const uint4*)(cx.sp + SM_XO + (128 + (ch >> 3)) * 128 + (((ch ^ (ch >> 3)) & 7) << 4));
}

constexpr float SUM_HI = 1.8446744e19f, SUM_LO = 9.0949470e-13f;

__device__ __forceinline__ void softmax_shift(float (&s)[64], float n0, float n1) {
#pragma unroll
  for (int i = 0; i < 64; i++) s[i] += (i & 2) ? n1 : n0;
}
template <int LO, int HI>
__device__ __forceinline__ void softmax_exp(float (&s)[64]) {
#pragma unroll
  for (int i = LO; i < HI; i++) s[i] = ex2(s[i]);
}
__device__ __forceinline__ void row_sums(const uint32_t (&pf)[32], float& l0, float& l1) {
  uint32_t t[16];
#pragma unroll
  for (int i = 0; i < 16; i++) t[i] = add2(pf[(i >> 1) * 4 + (i & 1)], pf[(i >> 1) * 4 + 2 + (i & 1)]);
#pragma unroll
  for (int i = 0; i < 8; i++) t[i] = add2(t[(i >> 1) * 4 + (i & 1)], t[(i >> 1) * 4 + 2 + (i & 1)]);
#pragma unroll
  for (int i = 0; i < 4; i++) t[i] = add2(t[(i >> 1) * 4 + (i & 1)], t[(i >> 1) * 4 + 2 + (i & 1)]);
  l0 += (bf_lo(t[0]) + bf_lo(t[2])) + (bf_hi(t[0]) + bf_hi(t[2]));
  l1 += (bf_lo(t[1]) + bf_lo(t[3])) + (bf_hi(t[1]) + bf_hi(t[3]));
}
__device__ __forceinline__ void row_max(const float (&s)[64], float& x0, float& x1) {
  x0 = s[0];
  x1 = s[2];
#pragma unroll
  for (int i = 0; i < 64; i += 4) { x0 = fmaxf(x0, fmaxf(s[i], s[i + 1])); x1 = fmaxf(x1, fmaxf(s[i + 2], s[i + 3])); }
  x0 = fmaxf(x0, __shfl_xor_sync(0xffffffffu, x0, 1));
  x1 = fmaxf(x1, __shfl_xor_sync(0xffffffffu, x1, 1));
  x0 = fmaxf(x0, __shfl_xor_sync(0xffffffffu, x0, 2));
  x1 = fmaxf(x1, __shfl_xor_sync(0xffffffffu, x1, 2));
}
__device__ __forceinline__ void softmax_rebase(float (&s)[64], float& n0, float& n1, float& sc0, float& sc1) {
  float x0, x1;
  row_max(s, x0, x1);
  x0 = fmaxf(x0, 1.f);
  x1 = fmaxf(x1, 1.f);
  n0 -= __log2f(x0);
  n1 -= __log2f(x1);
  sc0 = exp2f(-__log2f(x0));
  sc1 = exp2f(-__log2f(x1));
#pragma unroll
  for (int i = 0; i < 64; i++) s[i] *= (i & 2) ? sc1 : sc0;
}
__device__ __forceinline__ void softmax_redo(float (&s)[64], const uint32_t (&q)[32], const __nv_bfloat16* kblk, int lane, float& n0,
                                             float& n1, float& sc0, float& sc1) {
  const __nv_bfloat16* kp = kblk + (lane >> 2) * DH + (lane & 3) * 2;
#pragma unroll
  for (int nb = 0; nb < 16; nb++) {
    float d[4] = {0.f, 0.f, 0.f, 0.f};
#pragma unroll
    for (int k = 0; k < 8; k++)
      hmma_k16(d, q[4 * k], q[4 * k + 1], q[4 * k + 2], q[4 * k + 3], *(const uint32_t*)(kp + nb * 8 * DH + k * 16),
               *(const uint32_t*)(kp + nb * 8 * DH + k * 16 + 8));
    s[4 * nb] = d[0]; s[4 * nb + 1] = d[1]; s[4 * nb + 2] = d[2]; s[4 * nb + 3] = d[3];
    block_fence(100 + nb);
  }
  float x0, x1;
  row_max(s, x0, x1);
  const float m0 = fminf(n0, -x0), m1 = fminf(n1, -x1);
  sc0 = ex2(m0 - n0);
  sc1 = ex2(m1 - n1);
  n0 = m0; n1 = m1;
  softmax_shift(s, n0, n1);
  softmax_exp<0, 64>(s);
}

__device__ __forceinline__ void attn_consumer(const Ctx& cx, int qb, int hs, int wg, int cw, int lane, const __nv_bfloat16* x,
                                              const __nv_bfloat16* kc, __nv_bfloat16* out) {
  const int r = lane >> 2, c = lane & 3;
  const int lr0 = cw * 16 + r;
  const uint32_t full = cx.sb + SM_FULL;
  const uint32_t ring = cx.sb + SM_RING;
  uint32_t lo = ((cw & 3) * 16 + (lane & 15)) * 128 + (((lane >> 4) ^ (lane & 7)) << 4);
  const uint32_t slot = cx.sb + SM_SLOT + wg * 16384;
  auto frag = [&](int sl, int k) { return slot + sl * STAGE + (k >> 2) * 8192 + (lo ^ ((k & 3) << 5)); };
  auto park = [&](const float (&a)[64], int sl, int k0, int k1, float f0, float f1) {
#pragma unroll
    for (int k = 0; k < 8; k++)
      if (k >= k0 && k < k1)
        stsm4(frag(sl, k), pack2(a[8 * k] * f0, a[8 * k + 1] * f0), pack2(a[8 * k + 2] * f1, a[8 * k + 3] * f1),
              pack2(a[8 * k + 4] * f0, a[8 * k + 5] * f0), pack2(a[8 * k + 6] * f1, a[8 * k + 7] * f1));
  };
  const bool signaller = lane == 0 && (cw & 3) < 2;
  int my_turn = 1 + wg, other_turn = 2 - wg;

  uint32_t pf[32], empty_c;
  float o[64], l0, l1;
  {
    uint32_t xa[144];
    float rstd0, rstd1, sq0 = 0.f, sq1 = 0.f;
    {
      const uint32_t xb = cx.sb + SM_X + wg * 73728, xf = cx.sb + SM_XFULL + wg * 96;
      float sm[4][4] = {};
      prof(wg, 0);
      empty_c = mapa(cx.sb + SM_EMPTY, cw & 1);
      mbar_wait(xf, 0);
      if ((threadIdx.x & 127) == 0) profc(wg, 30);
      ln_fetch<0, 12>(xa, xb, lo);
      mbar_wait(xf + 8, 0);
      ln_fetch<12, 24>(xa, xb, lo);
      ln_sums<0, 12>(xa, sm);
      mbar_wait(xf + 16, 0);
      if ((threadIdx.x & 127) == 0) profc(wg, 1);
      ln_fetch<24, 36>(xa, xb, lo);
      ln_sums<12, 36>(xa, sm);
      rstd0 = ((sm[0][0] + sm[1][0]) + (sm[2][0] + sm[3][0])) * (1.0f / DM);
      rstd1 = ((sm[0][2] + sm[1][2]) + (sm[2][2] + sm[3][2])) * (1.0f / DM);
    }
    asm volatile("" : "+f"(rstd0), "+f"(rstd1)::"memory");
    if (wg) {
      bar_arrive(other_turn, 256);
    } else {
      bar_sync(4, 128);
      if (signaller) {
        asm volatile("mbarrier.arrive.shared::cluster.b64 _, [%0], 2;" ::"r"(empty_c + 16) : "memory");
        asm volatile("mbarrier.arrive.shared::cluster.b64 _, [%0], 2;" ::"r"(empty_c + 24) : "memory");
      }
    }
    const uint32_t mm0 = pack2(rstd0, rstd0), mm1 = pack2(rstd1, rstd1);
    ln_centre(xa, 0, X_C0, mm0, mm1, sq0, sq1);
    pin(xa);
    if ((threadIdx.x & 127) == 0) profc(wg, 2);

#pragma unroll 1
    for (int p = 0;; p++) {
      const int st0 = p * 5, last = p == 3 ? 3 : 4;
#pragma unroll
      for (int i = 0; i < 5; i++) {
        const int st = st0 + i;
        const uint32_t sl = st & 3;
        mbar_wait(full + 8 * sl, (st >> 2) & 1);
        if (i != (wg ? last : 1)) bar_sync(my_turn, 256);
        wg_fence();
        const uint64_t db = mkdesc(ring + sl * STAGE, 16384);
        const int kb0 = i < 3 ? 8 * i : 8 * i - 4;
#pragma unroll
        for (int k = 0; k < (i == 2 ? 4 : 8); k++) {
          const int kb = kb0 + k;
          mma_n128<1>(o, xa[4 * kb], xa[4 * kb + 1], xa[4 * kb + 2], xa[4 * kb + 3], db + k * 128, kb > 0);
          if (i == 4 && k == X_HO) wg_commit();
        }
        wg_commit();
        if (i == 4 && X_HO < 7) wg_wait<1>();
        if (i != (wg ? last - 1 : 0)) bar_arrive(other_turn, 256);
        if (p == 0 && (i == 1 || i == 2)) {
          ln_centre(xa, i == 1 ? X_C0 : X_C1, i == 1 ? X_C1 : 72, mm0, mm1, sq0, sq1);
          if (i == 2) {
            sq0 += __shfl_xor_sync(0xffffffffu, sq0, 1); sq1 += __shfl_xor_sync(0xffffffffu, sq1, 1);
            sq0 += __shfl_xor_sync(0xffffffffu, sq0, 2); sq1 += __shfl_xor_sync(0xffffffffu, sq1, 2);
            rstd0 = ln_rstd(sq0 * (1.0f / DM), rstd0 - bf_lo(mm0));
            rstd1 = ln_rstd(sq1 * (1.0f / DM), rstd1 - bf_lo(mm1));
            if (c == 0) {
              *(float2*)(cx.sp + SM_STATS + 8 * lr0) = make_float2(bf_lo(mm0), rstd0);
              *(float2*)(cx.sp + SM_STATS + 8 * (lr0 + 8)) = make_float2(bf_lo(mm1), rstd1);
            }
            bar_arrive(BAR_GATE, 352);
            rstd0 *= SM_SCALE_LOG2;
            rstd1 *= SM_SCALE_LOG2;
          }
          pin(xa);
        }
        if (i == 0 || i == 2) {
          if (i ? p != 3 : wg) {
            wg_wait<0>();
            if (signaller) mbar_arrive_cluster(empty_c + 8 * sl);
          }
        } else if (i == 3) {
          if (p == 3) break;
        } else {
          wg_wait<1>();
          if (signaller && (i == 4 || !wg)) mbar_arrive_cluster(empty_c + 8 * ((st - 1) & 3));
          wg_wait<0>();
          if (signaller) mbar_arrive_cluster(empty_c + 8 * sl);
        }
      }
      if (p == 3) break;
      pin(o);
      park(o, p, 0, 8, rstd0, rstd1);
    }
    wg_wait<1>();
    if (signaller) mbar_arrive_cluster(empty_c + 8 * ((NST_Q - 3) & 3));
    wg_wait<0>();
    if (signaller) mbar_arrive_cluster(empty_c + 8 * ((NST_Q - 2) & 3));
    prof(wg, 6);
#pragma unroll
    for (int i = 0; i < 32; i++) pf[i] = xa[112 + i];
    l0 = 0.25f * rcp(rstd0);
    l1 = 0.25f * rcp(rstd1);
  }

  uint32_t oa[96];
  const uint32_t zero = __shfl_sync(0xffffffffu, blockIdx.y, lane);
  my_turn = __shfl_sync(0xffffffffu, my_turn, lane);
  other_turn = __shfl_sync(0xffffffffu, other_turn, lane);
  lo = __shfl_sync(0xffffffffu, lo, lane);
  {
    float s[64], n0, n1;
    uint32_t q[32];
    float lp0, lp1;
    float i0, i1;
    bool redo, shift;
    auto turn = [&](int it, auto kc_) -> bool {
      constexpr int KIND = decltype(kc_)::value;
      constexpr uint32_t slk = KIND == 1 ? 1 : 3, slv = KIND == 1 ? 2 : 0, slkn = KIND == 1 ? 3 : 1;
      constexpr int SPLIT = X_SPLIT, PARK1 = X_PARK;
      const uint32_t par = ((it + 10) >> 1) & 1;
      const int hsl = max((it >> 4) - 1, 0);
      const uint64_t dk = mkdesc(ring + slk * STAGE, 16), dv = mkdesc(ring + slv * STAGE, 16384);
      auto qk = [&]() {
#pragma unroll
        for (int k = 0; k < 8; k++) {
          if (KIND == 3) mma_n128_ss<0>(s, mkdesc(slot + hsl * STAGE, 16) + (k >> 2) * 512 + (k & 3) * 2, dk + (k >> 2) * 1024 + (k & 3) * 2, k > 0);
          else mma_n128<0>(s, q[4 * k], q[4 * k + 1], q[4 * k + 2], q[4 * k + 3], dk + (k >> 2) * 1024 + (k & 3) * 2, k > 0);
        }
        wg_commit();
      };
      auto pv = [&]() {
#pragma unroll
        for (int k = 0; k < 8; k++)
          mma_n128<1>(o, pf[4 * k], pf[4 * k + 1], pf[4 * k + 2], pf[4 * k + 3], dv + k * 128, k > 0 || KIND != 1 || (it & 15) != 1);
        wg_commit();
      };
      lp0 = l0; lp1 = l1;
#define TS(i)
      {
        TS(0)
        if (KIND == 3) {
          asm volatile("fence.proxy.async.shared::cta;" ::: "memory");
          const float t0 = lp0 + __shfl_xor_sync(0xffffffffu, lp0, 1), t1 = lp1 + __shfl_xor_sync(0xffffffffu, lp1, 1);
          i0 = rcp(t0 + __shfl_xor_sync(0xffffffffu, t0, 2));
          i1 = rcp(t1 + __shfl_xor_sync(0xffffffffu, t1, 2));
          asm volatile("" : "+f"(i0), "+f"(i1)::"memory");
          block_fence(31, zero);
#pragma unroll
          for (int k = 0; k < X_N1; k++) ldsm4(frag(hsl, k), q[4 * k], q[4 * k + 1], q[4 * k + 2], q[4 * k + 3]);
        }
        bar_sync(my_turn, 256);
        TS(1)
        if (KIND != 3) pin(q);
        pin(pf); pin(o);
        wg_fence();
        qk();
        TS(2)
        mbar_wait(full + 8 * slv, par);
        if (KIND == 1 && (it & 15) == 1) {
          park(o, hsl, PARK1, 8, i0, i1);
          wg_fence();
        }
        if (KIND == 3) {
#pragma unroll
          for (int k = X_N1; k < 8; k++) ldsm4(frag(hsl, k), q[4 * k], q[4 * k + 1], q[4 * k + 2], q[4 * k + 3]);
          block_fence(32, zero);
        }
        TS(3)
        pv();
        bar_arrive(other_turn, 256);
        TS(4)
        wg_wait<1>();
      }
      pin(s);
      mbar_arrive_cluster_now<10 * KIND + 3>(empty_c + 8 * slk, signaller, zero);
      TS(5)
      if (KIND == 3) {
        shift = false;
        n0 = n1 = l0 = l1 = 0.f;
      } else if (shift) {
        softmax_shift(s, n0, n1);
        pin(s);
      }
      softmax_exp<0, SPLIT>(s);
      pin(s);
      block_fence(10 * KIND + 4, zero);
      TS(6)
      wg_wait<0>();
      pin(o); pin(pf);
      mbar_arrive_cluster_now<10 * KIND + 5>(empty_c + 8 * slv, signaller, zero);
      TS(7)
      const bool kready = mbar_test(full + 8 * slkn, par);
      softmax_exp<SPLIT, 64>(s);
#pragma unroll
      for (int i = 0; i < 32; i++) pf[i] = pack2(s[2 * i], s[2 * i + 1]);
      row_sums(pf, l0, l1);
      if (KIND == 3) {
        park(o, hsl, 0, PARK1, i0, i1);
        if (it) prof(wg, 6 + (it >> 4));
        if (it == 48 && cw == 0) bar_arrive(BAR_HELPER, 128);
      }
      redo = !(l0 + l1 <= SUM_HI) || (KIND == 3 && fminf(l0, l1) < SUM_LO);
      const bool leave = __any_sync(0xffffffffu, redo || !kready);
      return leave;
    };
    int it = -1;
#pragma unroll 1
    while (true) {
      mbar_wait(full + 8 * ((it & 1) ? 3 : 1), ((it + 10) >> 1) & 1);
      it++;
#pragma unroll 1
      while (true) {
        if (it & 1) {
          if (turn(it, IC<1>()) || it == 63) break;
          it++;
        }
        if (it & 15) {
          if (turn(it, IC<2>())) break;
        } else {
          if (turn(it, IC<3>())) break;
        }
        it++;
      }
      if (__any_sync(0xffffffffu, redo)) {
        const int j = it & 15;
        float sc0, sc1;
        if (__all_sync(0xffffffffu, l0 + l1 < 3.0e38f && (j || fminf(l0, l1) >= SUM_LO))) {
          softmax_rebase(s, n0, n1, sc0, sc1);
        } else {
          if (j == 0) n0 = n1 = 3.0e38f;
          softmax_redo(s, q, kc + (size_t)((hs * 2 + (it >> 5)) * SEQ + j * 128) * DH, lane, n0, n1, sc0, sc1);
        }
        l0 = j ? lp0 * sc0 : 0.f;
        l1 = j ? lp1 * sc1 : 0.f;
        shift = true;
        if (j == 0) sc0 = sc1 = 1.f;
#pragma unroll
        for (int i = 0; i < 16; i++) { o[4 * i] *= sc0; o[4 * i + 1] *= sc0; o[4 * i + 2] *= sc1; o[4 * i + 3] *= sc1; }
#pragma unroll
        for (int i = 0; i < 32; i++) pf[i] = pack2(s[2 * i], s[2 * i + 1]);
        row_sums(pf, l0, l1);
      }
      if (it == 63) break;
    }
  }

  {
    constexpr int ST0 = NST_Q + NST_KV;
    float acc[32], red[32];
    auto await = [&](int st) { mbar_wait(full + 8 * (st & 3), (st >> 2) & 1); };
    auto release = [&](int st) { if (signaller) mbar_arrive_cluster(empty_c + 8 * (st & 3)); };
    auto unpark = [&](int h, int k0, int k1) {
#pragma unroll
      for (int k = 0; k < 8; k++)
        if (k >= k0 && k < k1) ldsm4(frag(h, k), oa[32 * h + 4 * k], oa[32 * h + 4 * k + 1], oa[32 * h + 4 * k + 2], oa[32 * h + 4 * k + 3]);
    };
    {
      float ar[64];
      asm volatile("fence.proxy.async.shared::cta;" ::: "memory");
      l0 += __shfl_xor_sync(0xffffffffu, l0, 1); l1 += __shfl_xor_sync(0xffffffffu, l1, 1);
      l0 += __shfl_xor_sync(0xffffffffu, l0, 2); l1 += __shfl_xor_sync(0xffffffffu, l1, 2);
      float f0 = rcp(l0), f1 = rcp(l1);
      asm volatile("" : "+f"(f0), "+f"(f1)::"memory");
      await(ST0 - 1);
      unpark(1, 0, 4);
      bar_sync(my_turn, 256);
      pin(pf); pin(o);
      wg_fence();
#pragma unroll
      for (int k = 0; k < 8; k++)
        mma_n128<1>(o, pf[4 * k], pf[4 * k + 1], pf[4 * k + 2], pf[4 * k + 3], mkdesc(ring + 3 * STAGE, 16384) + k * 128, 1);
      wg_commit();
      await(ST0);
      unpark(1, 4, 8);
      block_fence(61, zero);
#pragma unroll
      for (int k = 0; k < 8; k++) mma_n128_ss<1>(ar, mkdesc(slot, 16) + (k >> 2) * 512 + (k & 3) * 2, mkdesc(ring, 16384) + k * 128, k > 0);
      wg_commit();
      bar_arrive(other_turn, 256);
      wg_wait<1>();
      pin(o); pin(pf);
      mbar_arrive_cluster_now<62>(empty_c + 24, signaller, zero);
#pragma unroll
      for (int i = 0; i < 16; i++) {
        pf[2 * i] = pack2(o[4 * i] * f0, o[4 * i + 1] * f0);
        pf[2 * i + 1] = pack2(o[4 * i + 2] * f1, o[4 * i + 3] * f1);
      }
      pin(pf);
      prof(wg, 10);
#pragma unroll
      for (int u = 1; u < 4; u++) {
        await(ST0 + u);
        wg_wait<0>();
        release(ST0 + u - 1);
        bar_sync(my_turn, 256);
        wg_fence();
#pragma unroll
        for (int k = 0; k < 8; k++) {
          const uint32_t* a = (u == 1 ? oa + 32 : u == 2 ? pf : oa + 64) + 4 * k;
          mma_n128<1>(ar, a[0], a[1], a[2], a[3], mkdesc(ring + u * STAGE, 16384) + k * 128, 1);
        }
        wg_commit();
        bar_arrive(other_turn, 256);
        if (u < 3) {
          block_fence(62 + u, zero);
          unpark(u == 1 ? 2 : 0, 0, 8);
        }
      }
      mbar_wait(cx.sb + SM_BAR_MISC, 0);
      await(ST0 + 4);
      wg_wait<0>();
      release(ST0 + 3);
      pin(ar);
#pragma unroll
      for (int i = 0; i < 32; i++) { acc[i] = ar[i]; red[i] = ar[32 + i]; }
    }
    const uint32_t tag = *(const uint32_t*)(cx.sp + SM_TAG);
    uint4* const xch = at<uint4>(cx.gs->part, (qb << 20) + lane * 16);
    auto send = [&](const float (&v)[32], int dst, int idx) {
      uint4* p = at<uint4>(xch, (dst * 8 + idx) * 2048);
#pragma unroll
      for (int i = 0; i < 4; i++)
        st_gran(p + i * 32, (pack2(v[8 * i], v[8 * i + 1]) & ~1u) | tag, pack2(v[8 * i + 2], v[8 * i + 3]),
                pack2(v[8 * i + 4], v[8 * i + 5]), pack2(v[8 * i + 6], v[8 * i + 7]));
    };
    send(acc, ((hs + 1) & 7) * 7, cw);
    int nrx = 1;
    auto half_step = [&](int s, auto hc, bool arrive) {
      constexpr int h = decltype(hc)::value;
      const int st = ST0 + 2 * s + h;
      const uint64_t db = mkdesc(ring + (st & 3) * STAGE, 16);
      bar_sync(my_turn, 256);
      if (h == 0) pin(pf);
#pragma unroll
      for (int i = 32 * h; i < 32 + 64 * h; i++) asm volatile("" : "+r"(oa[i])::"memory");
      wg_fence();
#pragma unroll
      for (int k = 0; k < 16; k++) {
        const int kb = h * 16 + k - 8;
        if (kb >= 0) mma_n64t(acc, oa[4 * kb], oa[4 * kb + 1], oa[4 * kb + 2], oa[4 * kb + 3], db + k * 128, 1);
        else mma_n64t(acc, pf[4 * k], pf[4 * k + 1], pf[4 * k + 2], pf[4 * k + 3], db + k * 128, k > 0);
      }
      wg_commit();
      if (arrive) bar_arrive(other_turn, 256);
    };
    auto fetch = [&](uint32_t (&g)[16], int n) {
      const uint4* p = at<const uint4>(xch, ((hs * 7 + n - 1) * 8 + cw) * 2048);
#pragma unroll
      for (int i = 0; i < 4; i++) ld_gran(p + i * 32, g[4 * i], g[4 * i + 1], g[4 * i + 2], g[4 * i + 3]);
    };
    uint32_t g[16];
    bool pend = false;
#pragma unroll 1
    for (int s = 2; s < 8; s++) {
      const int st = ST0 + 2 * s;
      half_step(s, IC<0>(), true);
      if (s == 2) {
        bar_arrive(BAR_OA, 352);
        send(red, 56 + cw, hs);
#pragma unroll
        for (int i = 0; i < 32; i++) red[i] = 0.f;
      }
      await(st + 1);
      if (pend && granules_ok(g, tag)) { add_granules(red, g); nrx++; }
      wg_wait<0>();
      if (s < 7) release(st);
      pend = nrx < s - 1;
      if (pend) fetch(g, nrx);
      half_step(s, IC<1>(), true);
      await(st + 2);
      wg_wait<0>();
      if (s < 7) release(st + 1);
      pin(acc);
      if (s == 7) prof(wg, 19);
      send(acc, ((hs + s) & 7) * 7 + s - 1, cw);
    }
    float gf[32], xf[32];
    {
      const int s = 8;
      uint32_t g2[16], xv[16], gt[16];
      half_step(s, IC<0>(), true);
      if (pend && granules_ok(g, tag)) { add_granules(red, g); nrx++; }
      await(NST_Q + NST_KV + NST_O - 1);
      mbar_wait(cx.sb + SM_BAR_XG, 0);
      wg_wait<0>();
      fetch(g, nrx);
#pragma unroll
      for (int k = 0; k < 4; k++) {
        const uint32_t p = cx.sb + SM_XO + wg * 8192 + (lo ^ (k << 5));
        ldsm4(p, xv[4 * k], xv[4 * k + 1], xv[4 * k + 2], xv[4 * k + 3]);
        ldsm4(p + STAGE, gt[4 * k], gt[4 * k + 1], gt[4 * k + 2], gt[4 * k + 3]);
      }
      half_step(s, IC<1>(), wg == 0);
      fetch(g2, 7);
      int last = 8;
      const bool two = nrx < 7;
      if (granules_ok(g, tag)) { add_granules(red, g); nrx++; }
#pragma unroll
      for (int i = 0; i < 16; i++) {
        gf[2 * i] = bf_lo(gt[i]); gf[2 * i + 1] = bf_hi(gt[i]);
        xf[2 * i] = bf_lo(xv[i]); xf[2 * i + 1] = bf_hi(xv[i]);
      }
      wg_wait<0>();
      pin(acc);
#pragma unroll
      for (int i = 0; i < 32; i++) red[i] += acc[i];
      pin(red); pin(gf); pin(xf);
      block_fence(60, zero);
      if (two && granules_ok(g2, tag)) { add_granules(red, g2); last = 7; }
#pragma unroll 1
      for (int spins = 0; nrx < last && spins < (1 << 16); spins++) {
        fetch(g, nrx);
        if (granules_ok(g, tag)) { add_granules(red, g); nrx++; }
      }
    }
    prof(wg, 20);
    const uint32_t ot = ring + 2 * STAGE + cw * (16 * 144);
    uint32_t ow[16];
#pragma unroll
    for (int i = 0; i < 16; i++) ow[i] = pack2(fmaf(red[2 * i], gf[2 * i], xf[2 * i]), fmaf(red[2 * i + 1], gf[2 * i + 1], xf[2 * i + 1]));
#pragma unroll
    for (int i = 0; i < 4; i++)
      stsm4(ot + (lane & 15) * 144 + (2 * i + (lane >> 4)) * 16, ow[4 * i], ow[4 * i + 1], ow[4 * i + 2], ow[4 * i + 3]);
    __syncwarp();
#pragma unroll
    for (int i = 0; i < 4; i++) {
      uint4 v;
      lds128(ot + (i * 4 + (lane >> 3)) * 144 + (lane & 7) * 16, v.x, v.y, v.z, v.w);
      at<uint4>(out, ((qb * 128 + cw * 16 + (lane >> 3)) * DM + hs * 64 + (lane & 7) * 8) * 2)[i * (4 * DM / 8)] = v;
    }
    prof(wg, 22);
  }
}

constexpr int FST_X = 24, FST_END = FST_X + 14 * 12;
__device__ __forceinline__ void ffn_producer(const Ctx& cx, int f, const CUtensorMap* tmX, const CUtensorMap* tmG,
                                             const CUtensorMap* tmU, const CUtensorMap* tmD) {
  const uint32_t full = cx.sb + SM_FULL, empty = cx.sb + SM_EMPTY;
  int pair = -2, u = 0;
#pragma unroll 1
  for (int st = 0; st < FST_END; st++) {
    const uint32_t sl = st & 7;
    const int unit = pair * 2 + (u & 1), k = u >> 1, k3 = k >= 3 ? k - 3 : k;
    if (unit < 27) {
      mbar_wait(empty + 8 * sl, ((st >> 3) & 1) ^ 1);
      mbar_expect_tx(full + 8 * sl, FSTAGE);
      if (pair < 0) tma3d(cx.sb + sl * FSTAGE, tmX, f * 512 + ((pair + 2) * 4 + (k >= 3) * 2 + (u & 1)) * 64, k3 * 3, full + 8 * sl);
      else if (pair < 9) tma2d_stream(cx.sb + sl * FSTAGE, k < 3 ? tmG : tmU, f * 1152 + unit * 64, k3 * 192, full + 8 * sl);
      else tma2d_stream(cx.sb + sl * FSTAGE, tmD, (unit - 18) * 64, f * 1152 + k * 192, full + 8 * sl);
    }
    if (++u == 12) { u = 0; pair++; }
  }
}

__device__ __forceinline__ void ffn_consumer(const Ctx& cx, int f, int wg, int cw, int lane, const __nv_bfloat16* x,
                                             const __nv_bfloat16* w_r) {
  const int r = lane >> 2, c = lane & 3, tid = cw * 32 + lane;
  unsigned e = 0;
  if (tid == 0) {
    e = cx.gs->launch[blockIdx.x];
    cx.gs->launch[blockIdx.x] = e + 1;
    *(unsigned*)(cx.sp + SM_TAG) = e;
  }
  if (tid < 72) *(uint4*)(cx.sp + SM_H + tid * 16) = *(const uint4*)(w_r + tid * 8);
  bar_sync(3, 256);
  prof(wg, 0);
  const uint32_t full = cx.sb + SM_FULL, empty = cx.sb + SM_EMPTY;
  const bool signaller = (tid & 127) == 0;
#pragma unroll 1
  for (int b = wg; b < 8; b += 2) {
    const int row0 = f * 512 + b * 64 + (cw & 3) * 16 + r;
    const uint32_t lo = ((cw & 3) * 16 + (lane & 15)) * 128 + (((lane >> 4) ^ (lane & 7)) << 4);
    LnAcc a;
    a.clear();
#pragma unroll 1
    for (int bx = 0; bx < 9; bx++) {
      const int st = (b >> 1) * 6 + (bx / 3) * 2 + wg;
      if (bx % 3 == 0) mbar_wait(full + 8 * (st & 7), (st >> 3) & 1);
#pragma unroll
      for (int k = 0; k < 4; k++) {
        uint32_t x0, x1, x2, x3;
        ldsm4(cx.sb + (st & 7) * FSTAGE + (bx % 3) * 8192 + (lo ^ (k << 5)), x0, x1, x2, x3);
        ln_accum1(a, k & 1, x0, x1, x2, x3);
      }
    }
    prof(wg, 8 + (b >> 1) * 3);
    float mean0, rstd0, mean1, rstd1;
    ln_stats(a, lane, mean0, rstd0, mean1, rstd1);
    prof(wg, 9 + (b >> 1) * 3);
    const uint32_t mm0 = pack2(mean0, mean0), mm1 = pack2(mean1, mean1);
    float d0[4] = {0, 0, 0, 0}, d1[4] = {0, 0, 0, 0};
#pragma unroll 1
    for (int bx = 0; bx < 9; bx++) {
      const int st = (b >> 1) * 6 + (bx / 3) * 2 + wg;
#pragma unroll
      for (int k = 0; k < 4; k++) {
        uint32_t n[4];
        ldsm4(cx.sb + (st & 7) * FSTAGE + (bx % 3) * 8192 + (lo ^ (k << 5)), n[0], n[1], n[2], n[3]);
        const uint8_t* wp = cx.sp + SM_H + (bx * 4 + k) * 32 + 4 * c;
#pragma unroll
        for (int i = 0; i < 4; i++) {
          const uint32_t t = sub2(n[i], (i & 1) ? mm1 : mm0);
          const float rs = (i & 1) ? rstd1 : rstd0;
          n[i] = pack2(bf_lo(t) * rs, bf_hi(t) * rs);
        }
        if (k & 1) hmma_k16(d1, n[0], n[1], n[2], n[3], *(const uint32_t*)wp, *(const uint32_t*)(wp + 16));
        else hmma_k16(d0, n[0], n[1], n[2], n[3], *(const uint32_t*)wp, *(const uint32_t*)(wp + 16));
      }
    }
    prof(wg, 10 + (b >> 1) * 3);
    bar_sync(4 + wg, 128);
    if (signaller) {
#pragma unroll
      for (int i = 0; i < 3; i++) mbar_arrive(empty + 8 * (((b >> 1) * 6 + i * 2 + wg) & 7));
    }
    if (c == 0) {
      cx.gs->r[row0] = bfr(d0[0] + d1[0]);
      cx.gs->r[row0 + 8] = bfr(d0[2] + d1[2]);
      cx.gs->stats[row0] = make_float2(mean0, rstd0);
      cx.gs->stats[row0 + 8] = make_float2(mean1, rstd1);
    }
  }
  prof(wg, 1);
  bar_sync(3, 256);
  e = *(const unsigned*)(cx.sp + SM_TAG);
  if (tid == 0) {
    atom_add_acq_rel(&cx.gs->rcnt);
#pragma unroll 1
    for (int n = 0; n < (1 << 16) && (int)(ld_acquire(&cx.gs->rcnt) - 4 * (e + 1)) < 0; n++) {}
  }
  bar_sync(3, 256);
  prof(wg, 2);
  uint32_t key[8];
#pragma unroll
  for (int i = 0; i < 8; i++) {
    const int row = i * 256 + tid;
    const uint32_t b = __float_as_uint(__ldcg(&cx.gs->r[row])) >> 16;
    key[i] = (((b & 0x8000u) ? (~b & 0xFFFFu) : (b | 0x8000u)) << 16) | (uint32_t)(0xFFFF - row);
  }
  int mysel = 0;
#pragma unroll 1
  for (int k = 0; k < TOPC; k++) {
    uint32_t m = key[0];
#pragma unroll
    for (int i = 1; i < 8; i++) m = max(m, key[i]);
    m = __reduce_max_sync(0xffffffffu, m);
    uint32_t* tk = (uint32_t*)(cx.sp + SM_TOPK) + (k & 1) * 8;
    if (lane == 0) tk[cw] = m;
    bar_sync(3, 256);
    m = __reduce_max_sync(0xffffffffu, tk[lane & 7]);
#pragma unroll
    for (int i = 0; i < 8; i++) if (key[i] == m) key[i] = 0;
    if (k == cw) mysel = 0xFFFF - (int)(m & 0xFFFF);
  }
  {
    const float2 st = __ldcg(&cx.gs->stats[mysel]);
    const uint32_t mm = pack2(st.x, st.x);
#pragma unroll 3
    for (int i = 0; i < 9; i++) {
      const uint32_t t = sub2(*(const uint32_t*)(x + (size_t)mysel * DM + i * 64 + 2 * lane), mm);
      *(uint32_t*)(cx.sp + SM_XSEL + i * 1024 + cw * 128 + (((lane >> 2) ^ cw) << 4) + (lane & 3) * 4) =
          pack2(bf_lo(t) * st.y, bf_hi(t) * st.y);
    }
    if (lane == 0) *(int*)(cx.sp + SM_IDX + 4 * cw) = mysel;
  }
  asm volatile("fence.proxy.async.shared::cta;" ::: "memory");
  bar_sync(3, 256);
  prof(wg, 3);
  auto run = [&](float (&acc)[4], int st, int n, uint32_t b) {
#pragma unroll 1
    for (int u = 0; u < n; u++, st += 2, b += 3072) {
      const uint32_t sl = st & 7;
      mbar_wait(full + 8 * sl, (st >> 3) & 1);
      wg_fence();
      const uint64_t da = mkdesc(cx.sb + sl * FSTAGE, 16), db = mkdesc(b, 16);
#pragma unroll
      for (int k = 0; k < 12; k++) mma_n8(acc, da + k * 128, db + (k >> 2) * 64 + (k & 3) * 2, u > 0 || k > 0);
      wg_commit();
      wg_wait<0>();
      if (signaller) mbar_arrive(empty + 8 * sl);
    }
    pin(acc);
  };
#pragma unroll 1
  for (int unit = wg; unit < 27; unit += 2) {
    if (unit >> 1 == 9) {
      asm volatile("fence.proxy.async.shared::cta;" ::: "memory");
      bar_sync(3, 256);
      prof(wg, 4);
    }
    const bool gu = unit < 18;
    float a0[4], a1[4];
#pragma unroll 1
    for (int m = 0; m < (gu ? 2 : 1); m++) {
      run(a1, FST_X + (unit >> 1) * 12 + m * 6 + wg, gu ? 3 : 6, cx.sb + (gu ? SM_XSEL : SM_H));
      if (m == 0) { a0[0] = a1[0]; a0[1] = a1[1]; a0[2] = a1[2]; a0[3] = a1[3]; }
    }
#pragma unroll
    for (int i = 0; i < 4; i++) {
      const int fl = (cw & 3) * 16 + r + (i >> 1) * 8, tok = 2 * c + (i & 1);
      if (gu) {
        const float h = bfr(silu_f(bfr(a0[i]))) * bfr(a1[i]);
        *(__nv_bfloat16*)(cx.sp + SM_H + unit * 1024 + tok * 128 + (((fl >> 3) ^ tok) << 4) + (fl & 7) * 2) = __float2bfloat16_rn(h);
      } else {
        cx.gs->ypart[(f * TOPC + tok) * DM + (unit - 18) * 64 + fl] = a1[i];
      }
    }
  }
  prof(wg, 5);
  bar_sync(3, 256);
  if (tid == 0) *(unsigned*)(cx.sp + SM_TOPK) = atom_add_acq_rel(&cx.gs->ycnt) == 4 * e + 3;
  bar_sync(3, 256);
  if (*(const unsigned*)(cx.sp + SM_TOPK)) {
    const int row = *(const int*)(cx.sp + SM_IDX + 4 * cw);
    const float rs = bfr(rcp(1.0f + ex2(-1.4426950408889634f * __ldcg(&cx.gs->r[row]))));
#pragma unroll 1
    for (int d = lane * 2; d < DM; d += 192) {
#pragma unroll
      for (int i = 0; i < 3; i++) {
        const float* p = cx.gs->ypart + cw * DM + d + i * 64;
        const float2 a = __ldcg((const float2*)p), b = __ldcg((const float2*)(p + TOPC * DM)),
                     e2 = __ldcg((const float2*)(p + 2 * TOPC * DM)), h = __ldcg((const float2*)(p + 3 * TOPC * DM));
        const uint32_t y = pack2((a.x + b.x) + (e2.x + h.x), (a.y + b.y) + (e2.y + h.y));
        const uint32_t u = pack2(bf_lo(y) * rs, bf_hi(y) * rs);
        *(float2*)(cx.gs->upd + cw * DM + d + i * 64) = make_float2(bf_lo(u), bf_hi(u));
      }
    }
    if (lane == 0) cx.gs->idx[cw] = row;
    bar_sync(3, 256);
    if (tid == 0) st_release(&cx.gs->ffn_flag, e + 1);
    prof(wg, 6);
  }
}

struct Maps { CUtensorMap m[9]; };
__global__ void __cluster_dims__(2, 1, 1) __launch_bounds__(THREADS, 1)
fused_kernel(const __nv_bfloat16* __restrict__ x, const __nv_bfloat16* __restrict__ w_r, const __nv_bfloat16* __restrict__ wq,
             const __nv_bfloat16* __restrict__ wo, __nv_bfloat16* __restrict__ out, Scratch* gs,
             const __grid_constant__ Maps maps, const __nv_bfloat16* __restrict__ kc) {
  const CUtensorMap &tmX = maps.m[0], &tmWq = maps.m[1], &tmK = maps.m[2], &tmV = maps.m[3], &tmWo = maps.m[4], &tmG = maps.m[5],
                    &tmU = maps.m[6], &tmD = maps.m[7];
  extern __shared__ __align__(1024) uint8_t smem_raw[];
  prof(0, 23, 511);
  Ctx cx;
  cx.sb = smem_u32(smem_raw);
  cx.sp = smem_raw;
  cx.gs = gs;
  cx.rank = blockIdx.x & 1;
  const int warp = __shfl_sync(0xffffffffu, threadIdx.x >> 5, 0);
  const int cluster = blockIdx.x >> 1;
  const bool is_ffn = blockIdx.x >= N_ATT_CTA;
  const int c7 = ((cluster - 36) * 37) >> 8;
  const int hs = cluster < 4 ? 4 + cluster : cluster < 36 ? (cluster - 4) >> 3 : 4 + c7;
  const int qb = (cluster < 4 ? 0 : cluster < 36 ? (cluster - 4) & 7 : cluster - 35 - 7 * c7) * 2 + cx.rank;

  extern __shared__ __align__(1024) uint8_t smem_alias[];
  const uint32_t xf = smem_u32(smem_alias) + SM_MISC + warp * 24;
  if (warp == 4 && elect_one()) prefetch_tmap(&tmX);
  if (warp == 6 && !is_ffn && elect_one()) prefetch_l2(x + (size_t)(qb * 128 + hs * 8) * DM, 8 * DM * 2);
  if (elect_one()) {
    const uint32_t cnt = (warp > 4 && warp < 8 && !is_ffn) ? 4 : 1;
#pragma unroll
    for (int i = 0; i < 3; i++) mbar_init(xf + 8 * i, cnt);
    asm volatile("fence.proxy.async.shared::cta;" ::: "memory");
    asm volatile("fence.mbarrier_init.release.cluster;" ::: "memory");
  }
  __syncwarp();
  cluster_arrive();
  if (warp == 4 && !is_ffn) {
    if (elect_one()) {
      profc(0, 28);
#pragma unroll
      for (int i = 0; i < 3; i++) {
        mbar_expect_tx(xf + 8 * i, 24576);
        tma3d(xf - SM_XFULL + SM_X + i * 24576, &tmX, qb * 128, i * 3, xf + 8 * i);
      }
      profc(0, 29);
    }
  } else if (warp > 8 && elect_one()) {
    prefetch_tmap(&tmX + (is_ffn ? warp - 4 : warp - 8));
  }
  __syncwarp();

  if (warp < 4) {
    asm volatile("setmaxnreg.dec.sync.aligned.u32 24;");
    cluster_wait();
    prof(0, 24, 511);
    if (warp == 0) {
      if (!is_ffn) attn_producer(cx, qb, hs, &tmX, &tmK, &tmV, &tmWq, &tmWo);
      else if (elect_one()) ffn_producer(cx, blockIdx.x - N_ATT_CTA, &tmX, &tmG, &tmU, &tmD);
      prof(0, 25, 511);
    } else if (!is_ffn) {
      attn_gate(cx, qb, hs, threadIdx.x - 32, x);
      if (warp == 1) attn_helper(cx, qb, hs, read_lane(), x, wo, &maps.m[8]);
      else { bar_arrive(BAR_HELPER, 128); bar_sync(BAR_OA, 352); }
      attn_finish8(cx, qb, hs, warp - 1, read_lane(), out);

    }
    __syncwarp();
    cluster_arrive();
    cluster_wait();
  } else {
    asm volatile("setmaxnreg.inc.sync.aligned.u32 240;");
    cluster_wait();
    const int cw = warp - 4, wg = cw >> 2;
    if (is_ffn) ffn_consumer(cx, blockIdx.x - N_ATT_CTA, wg, cw, read_lane(), x, w_r);
    else attn_consumer(cx, qb, hs, wg, cw, read_lane(), x, kc, out);
  }
}

typedef CUresult (*EncodeFn)(CUtensorMap*, CUtensorMapDataType, cuuint32_t, void*, const cuuint64_t*, const cuuint64_t*,
                             const cuuint32_t*, const cuuint32_t*, CUtensorMapInterleave, CUtensorMapSwizzle,
                             CUtensorMapL2promotion, CUtensorMapFloatOOBfill);

void encode(EncodeFn fn, CUtensorMap* m, const void* p, int rank, const cuuint64_t* dims, const cuuint64_t* strides,
            const cuuint32_t* box) {
  const cuuint32_t es[5] = {1, 1, 1, 1, 1};
  fn(m, CU_TENSOR_MAP_DATA_TYPE_BFLOAT16, rank, const_cast<void*>(p), dims, strides, box, es, CU_TENSOR_MAP_INTERLEAVE_NONE,
     CU_TENSOR_MAP_SWIZZLE_128B, CU_TENSOR_MAP_L2_PROMOTION_L2_128B, CU_TENSOR_MAP_FLOAT_OOB_FILL_NONE);
}
void encode2d(EncodeFn fn, CUtensorMap* m, const void* p, uint64_t rows, uint64_t cols, uint32_t box_rows) {
  const cuuint64_t dims[2] = {cols, rows}, strides[1] = {cols * 2};
  const cuuint32_t box[2] = {64, box_rows};
  encode(fn, m, p, 2, dims, strides, box);
}

}

extern "C" void kernel_launch(void* const* d_in, const int* in_sizes, int n_in, void* d_out, int out_size) {
  (void)in_sizes; (void)n_in; (void)out_size;
  void* fnp = nullptr;
  cudaDriverEntryPointQueryResult qr;
  cudaGetDriverEntryPoint("cuTensorMapEncodeTiled", &fnp, cudaEnableDefault, &qr);
  EncodeFn fn = (EncodeFn)fnp;
  Maps maps;
  CUtensorMap &tmX = maps.m[0], &tmWq = maps.m[1], &tmK = maps.m[2], &tmV = maps.m[3], &tmWo = maps.m[4], &tmG = maps.m[5],
              &tmU = maps.m[6], &tmD = maps.m[7];
  encode2d(fn, &tmK, d_in[1], 16 * SEQ, DH, 128);
  encode2d(fn, &tmV, d_in[2], 16 * SEQ, DH, 128);
  encode2d(fn, &tmWq, d_in[3], DM, 4096, 64);
  {
    const cuuint64_t dims[3] = {64, SEQ, 9}, strides[2] = {DM * 2, 128};
    const cuuint32_t box[3] = {64, 64, 3};
    encode(fn, &tmX, d_in[0], 3, dims, strides, box);
  }
  encode2d(fn, &maps.m[8], d_in[0], SEQ, DM, 16);
  encode2d(fn, &tmWo, d_in[4], 4096, DM, 128);
  encode2d(fn, &tmG, d_in[7], DM, FF, 192);
  encode2d(fn, &tmU, d_in[8], DM, FF, 192);
  encode2d(fn, &tmD, d_in[9], FF, DM, 192);
  cudaFuncSetAttribute(fused_kernel, cudaFuncAttributeMaxDynamicSharedMemorySize, SM_TOTAL);
  void* gs = nullptr;
  cudaGetSymbolAddress(&gs, g_scratch);
  fused_kernel<<<N_CTA, THREADS, SM_TOTAL>>>((const __nv_bfloat16*)d_in[0], (const __nv_bfloat16*)d_in[6], (const __nv_bfloat16*)d_in[3],
                                            (const __nv_bfloat16*)d_in[4], (__nv_bfloat16*)d_out, (Scratch*)gs, maps, (const __nv_bfloat16*)d_in[1]);
}
```

```cpp
#include <cuda_runtime.h>
#include <cuda_bf16.h>
#include <cuda.h>
#include <stdint.h>

namespace {

constexpr int SEQ = 2048, DM = 576, DH = 128, FF = 4608, TOPC = 8;
constexpr int N_ATT_CTA = 128, N_CTA = 132;
constexpr int THREADS = 384;

constexpr uint32_t SM_RING = 0;
constexpr uint32_t STAGE = 32768;
constexpr uint32_t SM_SLOT = 131072;
constexpr uint32_t FSTAGE = 24576;
constexpr uint32_t SM_XSEL = 196608;
constexpr uint32_t SM_H = 205824;
constexpr uint32_t SM_MISC = 229376;
constexpr uint32_t SM_FULL = SM_MISC, SM_BAR_MISC = SM_MISC + 64, SM_BAR_XG = SM_MISC + 72, SM_BAR_P8 = SM_MISC + 80, SM_XFULL = SM_MISC + 96,
                   SM_EMPTY = SM_MISC + 120, SM_TAG = SM_MISC + 288, SM_IDX = SM_MISC + 304, SM_TOPK = SM_MISC + 336,
                   SM_STATS = SM_MISC + 400;
constexpr uint32_t SM_TOTAL = SM_MISC + 1424;
constexpr uint32_t SM_X = SM_MISC - 147456;

constexpr int BAR_GATE = 6, BAR_HELPER = 7, BAR_OA = 8;
constexpr int NST_Q = 20, NST_KV = 128, NST_O = 18;
#define X_ORDER 0
#define X_PF 3
#define X_PFQ 3
#define X_REL 0
#define X_SLEEP8 700
#define X_QP 2
#define X_WARM 0
#define X_S1 12
#define X_PFM 1
#define X_IP 0
#define X_XS 0
#define X_CA2 1
#define X_N1 4
#define X_SPLIT 44
#define X_PARK 5
#define X_HO 9
#define X_C0 32
#define X_C1 40
#define X_C2 56
#define X_C3 72
#define X_CA 1
#define X_FIN 4
constexpr float SM_SCALE_LOG2 = 0.08838834764831845f * 1.4426950408889634f;

struct Scratch {
  uint4 part[16 * 64 * 2 * 4 * 128];
  uint4 gate[N_ATT_CTA * 144 * 8];
  float r[SEQ];
  float2 stats[SEQ];
  float ypart[4 * TOPC * DM];
  float upd[TOPC * DM];
  int idx[32];
  unsigned launch[160];
  unsigned rcnt, pad0[31], ycnt, pad1[31], ffn_flag, pad2[31];
};
__device__ __align__(1024) Scratch g_scratch;

__device__ __forceinline__ void profq(int) {}
__device__ __forceinline__ void prof(int, int, int = 0) {}
__device__ __forceinline__ void profc(int, int) {}

__device__ __forceinline__ uint32_t smem_u32(const void* p) { return (uint32_t)__cvta_generic_to_shared(p); }
__device__ __forceinline__ void mbar_init(uint32_t bar, uint32_t cnt) {
  asm volatile("mbarrier.init.shared::cta.b64 [%0], %1;" ::"r"(bar), "r"(cnt) : "memory");
}
__device__ __forceinline__ void mbar_expect_tx(uint32_t bar, uint32_t bytes) {
  asm volatile("mbarrier.arrive.expect_tx.shared::cta.b64 _, [%0], %1;" ::"r"(bar), "r"(bytes) : "memory");
}
__device__ __forceinline__ void mbar_arrive(uint32_t bar) {
  asm volatile("mbarrier.arrive.shared::cta.b64 _, [%0];" ::"r"(bar) : "memory");
}
__device__ __forceinline__ void mbar_arrive_cluster(uint32_t bar_cluster_addr) {
  asm volatile("mbarrier.arrive.shared::cluster.b64 _, [%0];" ::"r"(bar_cluster_addr) : "memory");
}
template <int ID>
__device__ __forceinline__ void mbar_arrive_cluster_now(uint32_t bar_cluster_addr, bool pred, uint32_t zero) {
  asm volatile("{\n.reg .pred p, q;\nsetp.ne.u32 p, %1, 0;\nsetp.eq.u32 q, %2, %3;\n"
               "ARR_LOOP:\n@p mbarrier.arrive.shared::cluster.b64 _, [%0];\n@q bra.uni ARR_LOOP;\n}"
               ::"r"(bar_cluster_addr), "r"((uint32_t)pred), "r"(zero), "n"(ID) : "memory");
}
__device__ __forceinline__ void block_fence(int id, uint32_t zero = blockIdx.y) {
  asm volatile("{\n.reg .pred q;\nsetp.eq.u32 q, %0, %1;\nBF_LOOP:\n@q st.volatile.shared.u32 [%0], %0;\n@q bra.uni BF_LOOP;\n}"
               ::"r"(zero), "r"(id) : "memory");
}
__device__ __forceinline__ bool mbar_test(uint32_t bar, uint32_t parity) {
  uint32_t ok;
  asm volatile("{\n.reg .pred p;\nmbarrier.test_wait.parity.shared::cta.b64 p, [%1], %2;\nselp.u32 %0, 1, 0, p;\n}"
               : "=r"(ok) : "r"(bar), "r"(parity) : "memory");
  return ok;
}
__device__ __forceinline__ void mbar_wait(uint32_t bar, uint32_t parity) {
  asm volatile("{\n.reg .pred p, q;\n.reg .u32 n;\nmov.u32 n, 0;\n"
               "WAIT_LOOP:\nmbarrier.try_wait.parity.shared::cta.b64 p, [%0], %1;\n"
               "add.u32 n, n, 1;\nsetp.lt.u32 q, n, 4194304;\nand.pred q, q, !p;\n@q bra WAIT_LOOP;\n}"
               ::"r"(bar), "r"(parity) : "memory");
}
__device__ __forceinline__ uint32_t mapa(uint32_t addr, uint32_t rank) {
  uint32_t r;
  asm volatile("mapa.shared::cluster.u32 %0, %1, %2;" : "=r"(r) : "r"(addr), "r"(rank));
  return r;
}
__device__ __forceinline__ void cluster_arrive() { asm volatile("barrier.cluster.arrive.relaxed.aligned;" ::: "memory"); }
__device__ __forceinline__ bool elect_one() {
  uint32_t p;
  asm volatile("{\n.reg .pred p;\nelect.sync _|p, 0xffffffff;\nselp.u32 %0, 1, 0, p;\n}" : "=r"(p));
  return p;
}
__device__ __forceinline__ int read_lane() { return threadIdx.x & 31; }
__device__ __forceinline__ void cluster_wait() { asm volatile("barrier.cluster.wait.acquire.aligned;" ::: "memory"); }
__device__ __forceinline__ void bar_sync(int id, int n) { asm volatile("barrier.cta.sync %0, %1;" ::"r"(id), "r"(n) : "memory"); }
__device__ __forceinline__ void bar_arrive(int id, int n) { asm volatile("barrier.cta.arrive %0, %1;" ::"r"(id), "r"(n) : "memory"); }

__device__ __forceinline__ uint64_t policy_evict_first() {
  uint64_t p;
  asm("createpolicy.fractional.L2::evict_first.b64 %0, 1.0;" : "=l"(p));
  return p;
}
__device__ __forceinline__ uint64_t policy_evict_normal() {
  uint64_t p;
  asm("createpolicy.fractional.L2::evict_normal.b64 %0, 1.0;" : "=l"(p));
  return p;
}
__device__ __forceinline__ void tma2d_mc(uint32_t dst, const CUtensorMap* tm, int c0, int c1, uint32_t bar, uint64_t pol) {
  asm volatile("cp.async.bulk.tensor.2d.shared::cluster.global.mbarrier::complete_tx::bytes.multicast::cluster.L2::cache_hint"
               " [%0], [%1, {%2, %3}], [%4], %5, %6;"
               ::"r"(dst), "l"(tm), "r"(c0), "r"(c1), "r"(bar), "h"((uint16_t)3), "l"(pol) : "memory");
}
__device__ __forceinline__ void tma3d(uint32_t dst, const CUtensorMap* tm, int c1, int c2, uint32_t bar) {
  asm volatile("cp.async.bulk.tensor.3d.shared::cluster.global.mbarrier::complete_tx::bytes [%0], [%1, {%2, %3, %4}], [%5];"
               ::"r"(dst), "l"(tm), "r"(0), "r"(c1), "r"(c2), "r"(bar) : "memory");
}
__device__ __forceinline__ void tma2d_stream(uint32_t dst, const CUtensorMap* tm, int c0, int c1, uint32_t bar) {
  asm volatile("{\n.reg .b64 pol;\ncreatepolicy.fractional.L2::evict_first.b64 pol, 1.0;\n"
               "cp.async.bulk.tensor.2d.shared::cluster.global.mbarrier::complete_tx::bytes.L2::cache_hint [%0], [%1, {%2, %3}], [%4], pol;\n}"
               ::"r"(dst), "l"(tm), "r"(c0), "r"(c1), "r"(bar) : "memory");
}
__device__ __forceinline__ void tma2d_prefetch(const CUtensorMap* tm, int c0, int c1) {
  asm volatile("cp.async.bulk.prefetch.tensor.2d.L2.global [%0, {%1, %2}];" ::"l"(tm), "r"(c0), "r"(c1) : "memory");
}
__device__ __forceinline__ void prefetch_l2(const void* p, uint32_t bytes) {
  asm volatile("cp.async.bulk.prefetch.L2.global [%0], %1;" ::"l"(p), "r"(bytes) : "memory");
}
__device__ __forceinline__ void prefetch_tmap(const CUtensorMap* tm) {
  asm volatile("prefetch.tensormap [%0];" ::"l"(tm) : "memory");
}

__device__ __forceinline__ void wg_fence() { asm volatile("wgmma.fence.sync.aligned;" ::: "memory"); }
__device__ __forceinline__ void wg_commit() { asm volatile("wgmma.commit_group.sync.aligned;" ::: "memory"); }
template <int N> __device__ __forceinline__ void wg_wait() { asm volatile("wgmma.wait_group.sync.aligned %0;" ::"n"(N) : "memory"); }

__device__ __forceinline__ uint64_t mkdesc(uint32_t addr, uint32_t lbo_bytes) {
  return (uint64_t)(((addr & 0x3FFFF) >> 4) | ((lbo_bytes >> 4) << 16)) | ((uint64_t)0x40000040u << 32);
}
template <int N> __device__ __forceinline__ void pin(float (&a)[N]) {
#pragma unroll
  for (int i = 0; i < N; i++) asm volatile("" : "+f"(a[i])::"memory");
}
template <int N> __device__ __forceinline__ void pin(uint32_t (&a)[N]) {
#pragma unroll
  for (int i = 0; i < N; i++) asm volatile("" : "+r"(a[i])::"memory");
}

#define F8(d, o) "+f"(d[o]), "+f"(d[o + 1]), "+f"(d[o + 2]), "+f"(d[o + 3]), "+f"(d[o + 4]), "+f"(d[o + 5]), "+f"(d[o + 6]), "+f"(d[o + 7])
#define R32A "%0, %1, %2, %3, %4, %5, %6, %7, %8, %9, %10, %11, %12, %13, %14, %15, %16, %17, %18, %19, %20, %21, %22, %23, %24, %25, %26, %27, %28, %29, %30, %31"
#define R32B "%32, %33, %34, %35, %36, %37, %38, %39, %40, %41, %42, %43, %44, %45, %46, %47, %48, %49, %50, %51, %52, %53, %54, %55, %56, %57, %58, %59, %60, %61, %62, %63"

template <int TB>
__device__ __forceinline__ void mma_n128(float (&d)[64], uint32_t a0, uint32_t a1, uint32_t a2, uint32_t a3, uint64_t db, int acc) {
  asm volatile("{\n.reg .pred p;\nsetp.ne.b32 p, %69, 0;\n"
               "wgmma.mma_async.sync.aligned.m64n128k16.f32.bf16.bf16 {" R32A ", " R32B "}, {%64, %65, %66, %67}, %68, p, 1, 1, %70;\n}\n"
               : F8(d, 0), F8(d, 8), F8(d, 16), F8(d, 24), F8(d, 32), F8(d, 40), F8(d, 48), F8(d, 56)
               : "r"(a0), "r"(a1), "r"(a2), "r"(a3), "l"(db), "r"(acc), "n"(TB));
}
template <int TB>
__device__ __forceinline__ void mma_n128_ss(float (&d)[64], uint64_t da, uint64_t db, int acc) {
  asm volatile("{\n.reg .pred p;\nsetp.ne.b32 p, %66, 0;\n"
               "wgmma.mma_async.sync.aligned.m64n128k16.f32.bf16.bf16 {" R32A ", " R32B "}, %64, %65, p, 1, 1, 0, %67;\n}\n"
               : F8(d, 0), F8(d, 8), F8(d, 16), F8(d, 24), F8(d, 32), F8(d, 40), F8(d, 48), F8(d, 56)
               : "l"(da), "l"(db), "r"(acc), "n"(TB));
}
__device__ __forceinline__ void mma_n64t(float (&d)[32], uint32_t a0, uint32_t a1, uint32_t a2, uint32_t a3, uint64_t db, int acc) {
  asm volatile("{\n.reg .pred p;\nsetp.ne.b32 p, %37, 0;\n"
               "wgmma.mma_async.sync.aligned.m64n64k16.f32.bf16.bf16 {" R32A "}, {%32, %33, %34, %35}, %36, p, 1, 1, 1;\n}\n"
               : F8(d, 0), F8(d, 8), F8(d, 16), F8(d, 24)
               : "r"(a0), "r"(a1), "r"(a2), "r"(a3), "l"(db), "r"(acc));
}
__device__ __forceinline__ void mma_n8(float (&d)[4], uint64_t da, uint64_t db, int acc) {
  asm volatile("{\n.reg .pred p;\nsetp.ne.b32 p, %6, 0;\n"
               "wgmma.mma_async.sync.aligned.m64n8k16.f32.bf16.bf16 {%0, %1, %2, %3}, %4, %5, p, 1, 1, 1, 0;\n}\n"
               : "+f"(d[0]), "+f"(d[1]), "+f"(d[2]), "+f"(d[3])
               : "l"(da), "l"(db), "r"(acc));
}
__device__ __forceinline__ void hmma_k8(float (&d)[4], uint32_t a0, uint32_t a1, uint32_t b0) {
  asm volatile("mma.sync.aligned.m16n8k8.row.col.f32.bf16.bf16.f32 {%0, %1, %2, %3}, {%4, %5}, {%6}, {%0, %1, %2, %3};"
               : "+f"(d[0]), "+f"(d[1]), "+f"(d[2]), "+f"(d[3]) : "r"(a0), "r"(a1), "r"(b0));
}
__device__ __forceinline__ void hmma_k16(float (&d)[4], uint32_t a0, uint32_t a1, uint32_t a2, uint32_t a3, uint32_t b0, uint32_t b1) {
  asm volatile("mma.sync.aligned.m16n8k16.row.col.f32.bf16.bf16.f32 {%0, %1, %2, %3}, {%4, %5, %6, %7}, {%8, %9}, {%0, %1, %2, %3};"
               : "+f"(d[0]), "+f"(d[1]), "+f"(d[2]), "+f"(d[3]) : "r"(a0), "r"(a1), "r"(a2), "r"(a3), "r"(b0), "r"(b1));
}

__device__ __forceinline__ uint32_t pack2(float lo, float hi) {
  uint32_t r;
  asm("cvt.rn.bf16x2.f32 %0, %1, %2;" : "=r"(r) : "f"(hi), "f"(lo));
  return r;
}
__device__ __forceinline__ float bf_lo(uint32_t w) { return __uint_as_float(w << 16); }
__device__ __forceinline__ float bf_hi(uint32_t w) { return __uint_as_float(w & 0xFFFF0000u); }
__device__ __forceinline__ float bfr(float x) { return __bfloat162float(__float2bfloat16_rn(x)); }
__device__ __forceinline__ uint32_t sub2(uint32_t a, uint32_t b) {
  uint32_t r;
  asm("sub.rn.bf16x2 %0, %1, %2;" : "=r"(r) : "r"(a), "r"(b));
  return r;
}
__device__ __forceinline__ uint32_t add2(uint32_t a, uint32_t b) {
  uint32_t r;
  asm("add.rn.bf16x2 %0, %1, %2;" : "=r"(r) : "r"(a), "r"(b));
  return r;
}
__device__ __forceinline__ uint32_t fma2(uint32_t a, uint32_t b, uint32_t c) {
  uint32_t r;
  asm("fma.rn.bf16x2 %0, %1, %2, %3;" : "=r"(r) : "r"(a), "r"(b), "r"(c));
  return r;
}
__device__ __forceinline__ float ex2(float x) {
  float r;
  asm("ex2.approx.ftz.f32 %0, %1;" : "=f"(r) : "f"(x));
  return r;
}
__device__ __forceinline__ float rcp(float x) {
  float r;
  asm("rcp.approx.ftz.f32 %0, %1;" : "=f"(r) : "f"(x));
  return r;
}
__device__ __forceinline__ float silu_f(float t) { return t * rcp(1.0f + ex2(-1.4426950408889634f * t)); }
__device__ __forceinline__ void sts128(uint32_t a, uint32_t x, uint32_t y, uint32_t z, uint32_t w) {
  asm volatile("st.shared.v4.u32 [%0], {%1, %2, %3, %4};" ::"r"(a), "r"(x), "r"(y), "r"(z), "r"(w) : "memory");
}
__device__ __forceinline__ void lds128(uint32_t a, uint32_t& x, uint32_t& y, uint32_t& z, uint32_t& w) {
  asm volatile("ld.shared.v4.u32 {%0, %1, %2, %3}, [%4];" : "=r"(x), "=r"(y), "=r"(z), "=r"(w) : "r"(a) : "memory");
}
__device__ __forceinline__ void ldsm4(uint32_t a, uint32_t& x, uint32_t& y, uint32_t& z, uint32_t& w) {
  asm volatile("ldmatrix.sync.aligned.m8n8.x4.shared.b16 {%0, %1, %2, %3}, [%4];" : "=r"(x), "=r"(y), "=r"(z), "=r"(w) : "r"(a) : "memory");
}
constexpr uint32_t TAG_BIT = 0x10000;
__device__ __forceinline__ void st_gran(uint4* p, uint32_t x, uint32_t y, uint32_t z, uint32_t w) {
  asm volatile("st.relaxed.gpu.global.v4.b32 [%0], {%1, %2, %3, %4};" ::"l"(p), "r"(x), "r"(y), "r"(z), "r"(w) : "memory");
}
__device__ __forceinline__ void ld_gran(const uint4* p, uint32_t& x, uint32_t& y, uint32_t& z, uint32_t& w) {
  asm volatile("ld.relaxed.gpu.global.v4.b32 {%0, %1, %2, %3}, [%4];" : "=r"(x), "=r"(y), "=r"(z), "=r"(w) : "l"(p) : "memory");
}
__device__ __forceinline__ void stsm4(uint32_t a, uint32_t x, uint32_t y, uint32_t z, uint32_t w) {
  asm volatile("stmatrix.sync.aligned.m8n8.x4.shared.b16 [%0], {%1, %2, %3, %4};" ::"r"(a), "r"(x), "r"(y), "r"(z), "r"(w) : "memory");
}
__device__ __forceinline__ void cp16(uint32_t dst, const void* src) {
  asm volatile("cp.async.cg.shared.global [%0], [%1], 16;" ::"r"(dst), "l"(src) : "memory");
}
template <class T>
__device__ __forceinline__ T* at(const void* base, uint32_t off) {
  uint64_t r;
  asm("{\n.reg .u32 lo, hi;\nmov.b64 {lo, hi}, %1;\nadd.cc.u32 lo, lo, %2;\naddc.u32 hi, hi, 0;\nmov.b64 %0, {lo, hi};\n}"
      : "=l"(r) : "l"(base), "r"(off));
  return (T*)__cvta_global_to_generic(r);
}
__device__ __forceinline__ void cp_wait_all() { asm volatile("cp.async.wait_all;" ::: "memory"); }
__device__ __forceinline__ void add_granules(float (&red)[32], const uint32_t (&g)[16]) {
#pragma unroll
  for (int i = 0; i < 16; i++) { red[2 * i] += bf_lo(g[i]); red[2 * i + 1] += bf_hi((i & 3) ? g[i] : g[i] & ~TAG_BIT); }
}
__device__ __forceinline__ bool granules_ok(const uint32_t (&g)[16], uint32_t tag) {
  uint32_t u, v;
  asm("lop3.b32 %0, %1, %2, %3, 0x7E;" : "=r"(u) : "r"(g[0]), "r"(g[4]), "r"(tag));
  asm("lop3.b32 %0, %1, %2, %3, 0x7E;" : "=r"(v) : "r"(g[8]), "r"(g[12]), "r"(tag));
  return __all_sync(0xffffffffu, ((u | v) & TAG_BIT) == 0);
}
__device__ __forceinline__ unsigned ld_acquire(const unsigned* p) {
  unsigned v;
  asm volatile("ld.acquire.gpu.global.u32 %0, [%1];" : "=r"(v) : "l"(p) : "memory");
  return v;
}
__device__ __forceinline__ unsigned atom_add_acq_rel(unsigned* p) {
  unsigned v;
  asm volatile("atom.acq_rel.gpu.global.add.u32 %0, [%1], 1;" : "=r"(v) : "l"(p) : "memory");
  return v;
}
__device__ __forceinline__ void st_release(unsigned* p, unsigned v) {
  asm volatile("st.release.gpu.global.u32 [%0], %1;" ::"l"(p), "r"(v) : "memory");
}

struct LnAcc {
  float sm[2][4], sq[8][4];
  __device__ __forceinline__ void clear() {
#pragma unroll
    for (int i = 0; i < 4; i++) {
      sm[0][i] = sm[1][i] = 0.f;
#pragma unroll
      for (int j = 0; j < 8; j++) sq[j][i] = 0.f;
    }
  }
};
template <int K0, int K1>
__device__ __forceinline__ void ln_fetch(uint32_t (&xa)[144], uint32_t boxes, uint32_t lo) {
#pragma unroll
  for (int k = K0; k < K1; k++) ldsm4(((boxes + lo) ^ ((k & 3) << 5)) + (k >> 2) * 8192, xa[4 * k], xa[4 * k + 1], xa[4 * k + 2], xa[4 * k + 3]);
}
__device__ __forceinline__ void ln_accum1(LnAcc& a, int h, uint32_t x0, uint32_t x1, uint32_t x2, uint32_t x3) {
  const uint32_t ONES = 0x3F803F80u;
  hmma_k16(a.sm[h], x0, x1, x2, x3, ONES, ONES);
  hmma_k8(a.sq[4 * h], x0, x1, x0);
  hmma_k8(a.sq[4 * h + 1], x0, x1, x1);
  hmma_k8(a.sq[4 * h + 2], x2, x3, x2);
  hmma_k8(a.sq[4 * h + 3], x2, x3, x3);
}
template <int K0, int K1>
__device__ __forceinline__ void ln_accum(const uint32_t (&xa)[144], LnAcc& a) {
#pragma unroll
  for (int k = K0; k < K1; k++) ln_accum1(a, k & 1, xa[4 * k], xa[4 * k + 1], xa[4 * k + 2], xa[4 * k + 3]);
}
template <int K0, int K1>
__device__ __forceinline__ void ln_sums(const uint32_t (&xa)[144], float (&sm)[4][4]) {
#pragma unroll
  for (int k = K0; k < K1; k++) hmma_k16(sm[k & 3], xa[4 * k], xa[4 * k + 1], xa[4 * k + 2], xa[4 * k + 3], 0x3F803F80u, 0x3F803F80u);
}
__device__ __forceinline__ uint32_t sq8(const uint32_t* a) {
  uint32_t t, u;
  asm("mul.rn.bf16x2 %0, %1, %1;" : "=r"(t) : "r"(a[0]));
  asm("mul.rn.bf16x2 %0, %1, %1;" : "=r"(u) : "r"(a[2]));
#pragma unroll
  for (int i = 4; i < 16; i += 4) {
    asm("fma.rn.bf16x2 %0, %1, %1, %0;" : "+r"(t) : "r"(a[i]));
    asm("fma.rn.bf16x2 %0, %1, %1, %0;" : "+r"(u) : "r"(a[i + 2]));
  }
  return add2(t, u);
}
__device__ __forceinline__ void ln_centre(uint32_t (&xa)[144], int j0, int j1, uint32_t mm0, uint32_t mm1, float& sq0, float& sq1) {
#pragma unroll
  for (int j = 0; j < 72; j += 8)
    if (j >= j0 && j < j1) {
#pragma unroll
      for (int k = j; k < j + 8; k++) {
        xa[2 * k] = sub2(xa[2 * k], mm0);
        xa[2 * k + 1] = sub2(xa[2 * k + 1], mm1);
      }
      const uint32_t t0 = sq8(xa + 2 * j), t1 = sq8(xa + 2 * j + 1);
      sq0 += bf_lo(t0) + bf_hi(t0);
      sq1 += bf_lo(t1) + bf_hi(t1);
    }
}
__device__ __forceinline__ float ln_rstd(float var) {
  float sd;
  asm("sqrt.approx.f32 %0, %1;" : "=f"(sd) : "f"(bfr(bfr(fmaxf(var, 0.0f)) + 1e-5f)));
  return rcp(bfr(sd));
}
__device__ __forceinline__ void ln_row(float sum, float sq, float& mean_b, float& rstd) {
  const float mean = sum * (1.0f / DM);
  mean_b = bfr(mean);
  rstd = ln_rstd(sq * (1.0f / DM) - mean * mean);
}
__device__ __forceinline__ void ln_diag(const LnAcc& a, int lane, float& t0, float& t1) {
  const bool odd = (lane >> 2) & 1;
  t0 = odd ? (a.sq[0][1] + a.sq[2][1]) + (a.sq[4][1] + a.sq[6][1]) : (a.sq[0][0] + a.sq[2][0]) + (a.sq[4][0] + a.sq[6][0]);
  t1 = odd ? (a.sq[1][3] + a.sq[3][3]) + (a.sq[5][3] + a.sq[7][3]) : (a.sq[1][2] + a.sq[3][2]) + (a.sq[5][2] + a.sq[7][2]);
}
__device__ __forceinline__ void ln_stats(const LnAcc& a, int lane, float& mean0, float& rstd0, float& mean1, float& rstd1) {
  float t0, t1;
  ln_diag(a, lane, t0, t1);
  const int src = (lane & ~3) | (lane >> 3);
  t0 = __shfl_sync(0xffffffffu, t0, src);
  t1 = __shfl_sync(0xffffffffu, t1, src);
  ln_row(a.sm[0][0] + a.sm[1][0], t0, mean0, rstd0);
  ln_row(a.sm[0][2] + a.sm[1][2], t1, mean1, rstd1);
}

template <bool ROUTED>
__device__ __forceinline__ uint32_t gate2(uint32_t x2, float mean_b, float rstd, float2 upd = make_float2(0.f, 0.f)) {
  const uint32_t xc = sub2(x2, pack2(mean_b, mean_b));
  uint32_t t = pack2(bf_lo(xc) * rstd, bf_hi(xc) * rstd);
  if (ROUTED) t = pack2(bf_lo(t) + upd.x, bf_hi(t) + upd.y);
  return pack2(silu_f(bf_lo(t)), silu_f(bf_hi(t)));
}

template <int V> struct IC { static constexpr int value = V; };

struct Ctx {
  uint32_t sb;
  uint8_t* sp;
  uint32_t rank;
  Scratch* gs;
};

__device__ __forceinline__ void dly(int) {}
template <int BOXES>
__device__ __forceinline__ void load_stage(uint32_t dst, const CUtensorMap* tm, int c0, int c1, uint32_t bar, uint32_t bytes, uint64_t pol) {
  asm volatile("{\n.reg .pred p;\nelect.sync _|p, 0xffffffff;\n"
               "@p mbarrier.arrive.expect_tx.shared::cta.b64 _, [%4], %7;\n"
               "@p cp.async.bulk.tensor.2d.shared::cluster.global.mbarrier::complete_tx::bytes.multicast::cluster.L2::cache_hint"
               " [%0], [%1, {%2, %3}], [%4], %5, %6;\n}"
               ::"r"(dst), "l"(tm), "r"(c0), "r"(c1), "r"(bar), "h"((uint16_t)3), "l"(pol), "r"(bytes) : "memory");
  if (BOXES == 2)
    asm volatile("{\n.reg .pred p;\nelect.sync _|p, 0xffffffff;\n"
                 "@p cp.async.bulk.tensor.2d.shared::cluster.global.mbarrier::complete_tx::bytes.multicast::cluster.L2::cache_hint"
                 " [%0], [%1, {%2, %3}], [%4], %5, %6;\n}"
                 ::"r"(dst + 8192), "l"(tm), "r"(c0), "r"(c1 + 64), "r"(bar), "h"((uint16_t)3), "l"(pol) : "memory");
}
__device__ __forceinline__ void attn_producer(const Ctx& cx, int qb, int hs, const CUtensorMap* tmX, const CUtensorMap* tmK,
                                              const CUtensorMap* tmV, const CUtensorMap* tmWq, const CUtensorMap* tmWo) {
  const uint32_t full = cx.sb + SM_FULL, empty = cx.sb + SM_EMPTY, ring = cx.sb + SM_RING + cx.rank * 16384;
  const uint64_t keep = policy_evict_normal(), last_use = policy_evict_first();
  auto acquire = [&](int st) {
    mbar_wait(empty + 8 * (st & 3), ((st >> 2) ^ ((st & 3) >> 1) ^ 1) & 1);
    dly(st);
  };
  if (elect_one()) {
#pragma unroll
    for (int j = 0; j < 3; j++) {
      mbar_expect_tx(cx.sb + SM_XFULL + 96 + 8 * j, 24576);
      tma3d(cx.sb + SM_X + 73728 + j * 24576, tmX, qb * 128 + 64, j * 3, cx.sb + SM_XFULL + 96 + 8 * j);
    }
  }
  __syncwarp();
#pragma unroll 1
  for (int p = 0; p < 4; p++) {
    const int n0 = (hs * 4 + ((0x1320 >> (4 * p)) & 3)) * DH + cx.rank * 64;
#pragma unroll
    for (int i = 0; i < 5; i++) {
      const int st = 5 * p + i, sl = st & 3;
      if (i == 4 && p == 3) break;
      acquire(st);
      if (i == 2) load_stage<1>(ring + sl * STAGE, tmWq, n0, 256, full + 8 * sl, 16384, last_use);
      else load_stage<2>(ring + sl * STAGE, tmWq, n0, i < 2 ? 128 * i : 128 * i - 64, full + 8 * sl, 32768, last_use);
      if (X_PFM == 0 && i == X_PFQ && p == 0 && elect_one()) {
#pragma unroll 1
        for (int b = 8 + qb; b < 72; b += 16) {
          const int bp = (b * 57) >> 10;
          tma2d_prefetch(tmWq, (hs * 4 + ((0x1320 >> (4 * bp)) & 3)) * DH + (b & 1) * 64, ((b - 18 * bp) >> 1) * 64);
        }
      }
      if (X_PFM == 1 && i == X_PFQ && p < 3 && elect_one()) {
        const int b = 14 + 18 * p + qb + (qb > 7) * 2, bp = p + (qb > 3);
        tma2d_prefetch(tmWq, (hs * 4 + ((0x1320 >> (4 * bp)) & 3)) * DH + (b & 1) * 64, ((b - 18 * bp) >> 1) * 64);
      }
      __syncwarp();
    }
  }
  const int c0 = cx.rank * 64;
  int vrow = 0;
  uint64_t vpol = keep;
#pragma unroll 1
  for (int j = 0; j < 32; j++) {
    const int st = NST_Q - 1 + 4 * j, row = (hs * 2 + (j >> 4)) * SEQ + (j & 7) * 256;
    const uint64_t pol = (j & 8) ? last_use : keep;
    acquire(st);
    load_stage<1>(ring + 3 * STAGE, tmK, c0, row, full + 24, 32768, pol);
    acquire(st + 1);
    if (j) load_stage<1>(ring, tmV, c0, vrow, full, 32768, vpol);
    else load_stage<2>(ring, tmWq, (hs * 4 + 1) * DH + c0, 448, full, 32768, last_use);
    vrow = row + 128;
    vpol = pol;
    acquire(st + 2);
    load_stage<1>(ring + STAGE, tmK, c0, vrow, full + 8, 32768, pol);
    acquire(st + 3);
    load_stage<1>(ring + 2 * STAGE, tmV, c0, row, full + 16, 32768, pol);
  }
  acquire(NST_Q + NST_KV - 1);
  load_stage<1>(ring + 3 * STAGE, tmV, c0, vrow, full + 24, 32768, last_use);
#pragma unroll 1
  for (int u = 0; u < NST_O; u++) {
    const int st = NST_Q + NST_KV + u, sl = st & 3;
    const int blk = u < 4 && cx.rank ? 8 : ((hs + max(u >> 1, 1)) & 7);
    const int head = u < 4 ? u ^ (u >> 1) : ((u & 1) * 2 + cx.rank + 3) & 3;
    acquire(st);
    load_stage<1>(ring + sl * STAGE, tmWo, blk * 64, hs * 512 + head * 128, full + 8 * sl, 32768, last_use);
  }
}

__device__ __forceinline__ void attn_gate(const Ctx& cx, int qb, int hs, int t, const __nv_bfloat16* x) {
  const uint32_t base = (qb * 128 * DM + (t & 7) * 8) * 2;
  uint32_t lr = t >> 3;
  uint4 nx = __ldg(at<const uint4>(x, base + (lr * DM + hs * 64) * 2));
  bar_sync(BAR_GATE, 352);
#pragma unroll 1
  for (uint32_t n = t >> 3; n < 144;) {
    const uint4 v = nx;
    const float2 st = *(const float2*)(cx.sp + SM_STATS + 8 * lr);
    uint4* dst = at<uint4>(cx.gs->gate, (blockIdx.x * 144 + n) * 128 + (((t ^ n) & 7) << 4));
    n += 12;
    lr = n < 128 ? n : n + hs * 16 - 128;
    if (n < 144) nx = __ldg(at<const uint4>(x, base + (lr * DM + (n < 128 ? hs * 64 : 512)) * 2));
    *dst = make_uint4(gate2<false>(v.x, st.x, st.y), gate2<false>(v.y, st.x, st.y), gate2<false>(v.z, st.x, st.y), gate2<false>(v.w, st.x, st.y));
  }
  asm volatile("fence.proxy.async;" ::: "memory");
}

constexpr uint32_t SM_XO = SM_SLOT, SM_GO = SM_SLOT + STAGE, SM_P8 = SM_SLOT + 2 * STAGE;
__device__ __forceinline__ void attn_helper(const Ctx& cx, int qb, int hs, int lane, const __nv_bfloat16* x, const __nv_bfloat16* wo,
                                            const CUtensorMap* tmX16) {
  unsigned e = 0;
  if (lane == 0) {
    e = cx.gs->launch[blockIdx.x];
    cx.gs->launch[blockIdx.x] = e + 1;
  }
  e = __shfl_sync(0xffffffffu, e, 0);
  if (lane == 0) {
    *(uint32_t*)(cx.sp + SM_TAG) = (~e & 1) * TAG_BIT;
    mbar_arrive(cx.sb + SM_BAR_MISC);
  }
  bar_sync(BAR_HELPER, 128);
  prefetch_l2(at<const void>(wo, (hs * 512 + qb * 32 + lane) * (DM * 2)), DM * 2);
#pragma unroll 1
  for (int n = 0; n < (1 << 16) && ld_acquire(&cx.gs->ffn_flag) != e + 1; n++) __nanosleep(1000);
#pragma unroll 1
  for (int i = 0; i < 2 * TOPC; i++) {
    const int lr = __ldcg(&cx.gs->idx[i >> 1]) - qb * 128, col = ((i & 1) ? 512 : hs * 64) + 2 * lane;
    if ((i & 1) ? (lr >> 4) == hs : (lr >> 7) == 0) {
      const float2 st = *(const float2*)(cx.sp + SM_STATS + 8 * lr);
      *at<uint32_t>(cx.gs->gate, (blockIdx.x * 144 + ((i & 1) ? 128 + (lr & 15) : lr)) * 128 + ((((lane >> 2) ^ lr) & 7) << 4) + (lane & 3) * 4) =
          gate2<true>(*at<const uint32_t>(x, ((qb * 128 + lr) * DM + col) * 2), st.x, st.y,
                      __ldcg(at<const float2>(cx.gs->upd, ((i >> 1) * DM + col) * 4)));
    }
  }
  asm volatile("fence.proxy.async;" ::: "memory");
  bar_sync(BAR_OA, 352);
  if (elect_one()) {
    const uint32_t bar = cx.sb + SM_BAR_XG;
    mbar_expect_tx(bar, 2 * 144 * 128);
    asm volatile("cp.async.bulk.shared::cluster.global.mbarrier::complete_tx::bytes [%0], [%1], %2, [%3];"
                 ::"r"(cx.sb + SM_GO), "l"(cx.gs->gate + blockIdx.x * (144 * 8)), "n"(144 * 128), "r"(bar) : "memory");
#pragma unroll 1
    for (int i = 0; i < 9; i++) tma2d_stream(cx.sb + SM_XO + i * 2048, tmX16, i < 8 ? hs * 64 : 512, qb * 128 + (i < 8 ? i : hs) * 16, bar);
  }
  __syncwarp();
  const uint4* src = cx.gs->part + (qb * 64 + 56 + hs) * 1024;
#pragma unroll 1
  for (int n = 0; n < (1 << 16); n++) {
    __nanosleep(n ? 400 : X_SLEEP8);
    uint32_t a, b, d, t;
    ld_gran(at<const uint4>(src, (lane & 7) * 2048 + 2032), a, b, d, t);
    if (__all_sync(0xffffffffu, ((a >> 16) ^ e) & 1)) break;
  }
  if (elect_one()) {
    mbar_expect_tx(cx.sb + SM_BAR_P8, 16384);
    asm volatile("cp.async.bulk.shared::cluster.global.mbarrier::complete_tx::bytes [%0], [%1], 16384, [%2];"
                 ::"r"(cx.sb + SM_P8), "l"(src), "r"(cx.sb + SM_BAR_P8) : "memory");
  }
  __syncwarp();
}
__device__ __forceinline__ void attn_finish8(const Ctx& cx, int qb, int hs, int hw, int lane, __nv_bfloat16* out) {
  const uint32_t tag = *(const uint32_t*)(cx.sp + SM_TAG);
  mbar_wait(cx.sb + SM_BAR_P8, 0);
  mbar_wait(cx.sb + SM_BAR_XG, 0);
#pragma unroll 1
  for (int g = 2 - hw; g < 4; g += 3) {
    float acc[8] = {0.f, 0.f, 0.f, 0.f, 0.f, 0.f, 0.f, 0.f};
    uint32_t a[4];
#pragma unroll 1
    for (uint32_t o = g * 512 + lane * 16; o < 16384; o += 2048) {
      lds128(cx.sb + SM_P8 + o, a[0], a[1], a[2], a[3]);
#pragma unroll 1
      for (int n = 0; n < (1 << 16) && __any_sync(0xffffffffu, (a[0] & TAG_BIT) != tag); n++)
        ld_gran(at<const uint4>(cx.gs->part, (qb * 64 + 56 + hs) * 16384 + o), a[0], a[1], a[2], a[3]);
      a[0] &= ~TAG_BIT;
#pragma unroll
      for (int j = 0; j < 4; j++) { acc[2 * j] += bf_lo(a[j]); acc[2 * j + 1] += bf_hi(a[j]); }
    }
    asm volatile("" : "+r"(lane));
    const uint32_t tile = cx.sb + SM_XO + (128 + (lane & 15)) * 128 + (((lane >> 4) ^ (lane & 7)) << 4);
    uint32_t b[4];
    ldsm4((tile ^ (g << 5)) + STAGE, a[0], a[1], a[2], a[3]);
    ldsm4(tile ^ (g << 5), b[0], b[1], b[2], b[3]);
    stsm4(tile ^ (g << 5), fma2(pack2(acc[0], acc[1]), a[0], b[0]), fma2(pack2(acc[2], acc[3]), a[1], b[1]),
          fma2(pack2(acc[4], acc[5]), a[2], b[2]), fma2(pack2(acc[6], acc[7]), a[3], b[3]));
  }
  bar_sync(BAR_GATE, 96);
#pragma unroll 1
  for (int ch = hw * 32 + lane; ch < 128; ch += 96)
    *at<uint4>(out, ((qb * 128 + hs * 16 + (ch >> 3)) * DM + 512 + (ch & 7) * 8) * 2) =
        *(const uint4*)(cx.sp + SM_XO + (128 + (ch >> 3)) * 128 + (((ch ^ (ch >> 3)) & 7) << 4));
}

constexpr float SUM_HI = 1.8446744e19f, SUM_LO = 9.0949470e-13f;

__device__ __forceinline__ void softmax_shift(float (&s)[64], float n0, float n1) {
#pragma unroll
  for (int i = 0; i < 64; i++) s[i] += (i & 2) ? n1 : n0;
}
template <int LO, int HI>
__device__ __forceinline__ void softmax_exp(float (&s)[64]) {
#pragma unroll
  for (int i = LO; i < HI; i++) s[i] = ex2(s[i]);
}
__device__ __forceinline__ void row_sums(const uint32_t (&pf)[32], float& l0, float& l1) {
  uint32_t t[16];
#pragma unroll
  for (int i = 0; i < 16; i++) t[i] = add2(pf[(i >> 1) * 4 + (i & 1)], pf[(i >> 1) * 4 + 2 + (i & 1)]);
#pragma unroll
  for (int i = 0; i < 8; i++) t[i] = add2(t[(i >> 1) * 4 + (i & 1)], t[(i >> 1) * 4 + 2 + (i & 1)]);
#pragma unroll
  for (int i = 0; i < 4; i++) t[i] = add2(t[(i >> 1) * 4 + (i & 1)], t[(i >> 1) * 4 + 2 + (i & 1)]);
  l0 += (bf_lo(t[0]) + bf_lo(t[2])) + (bf_hi(t[0]) + bf_hi(t[2]));
  l1 += (bf_lo(t[1]) + bf_lo(t[3])) + (bf_hi(t[1]) + bf_hi(t[3]));
}
__device__ __forceinline__ void row_max(const float (&s)[64], float& x0, float& x1) {
  x0 = s[0];
  x1 = s[2];
#pragma unroll
  for (int i = 0; i < 64; i += 4) { x0 = fmaxf(x0, fmaxf(s[i], s[i + 1])); x1 = fmaxf(x1, fmaxf(s[i + 2], s[i + 3])); }
  x0 = fmaxf(x0, __shfl_xor_sync(0xffffffffu, x0, 1));
  x1 = fmaxf(x1, __shfl_xor_sync(0xffffffffu, x1, 1));
  x0 = fmaxf(x0, __shfl_xor_sync(0xffffffffu, x0, 2));
  x1 = fmaxf(x1, __shfl_xor_sync(0xffffffffu, x1, 2));
}
__device__ __forceinline__ void softmax_rebase(float (&s)[64], float& n0, float& n1, float& sc0, float& sc1) {
  float x0, x1;
  row_max(s, x0, x1);
  x0 = fmaxf(x0, 1.f);
  x1 = fmaxf(x1, 1.f);
  n0 -= __log2f(x0);
  n1 -= __log2f(x1);
  sc0 = exp2f(-__log2f(x0));
  sc1 = exp2f(-__log2f(x1));
#pragma unroll
  for (int i = 0; i < 64; i++) s[i] *= (i & 2) ? sc1 : sc0;
}
__device__ __forceinline__ void softmax_redo(float (&s)[64], const uint32_t (&q)[32], const __nv_bfloat16* kblk, int lane, float& n0,
                                             float& n1, float& sc0, float& sc1, uint32_t zero) {
  const __nv_bfloat16* kp = kblk + (lane >> 2) * DH + (lane & 3) * 2;
#pragma unroll
  for (int nb = 0; nb < 16; nb++) {
    float d[4] = {0.f, 0.f, 0.f, 0.f};
#pragma unroll
    for (int k = 0; k < 8; k++) {
      hmma_k16(d, q[4 * k], q[4 * k + 1], q[4 * k + 2], q[4 * k + 3], *(const uint32_t*)(kp + nb * 8 * DH + k * 16),
               *(const uint32_t*)(kp + nb * 8 * DH + k * 16 + 8));
    }
    s[4 * nb] = d[0]; s[4 * nb + 1] = d[1]; s[4 * nb + 2] = d[2]; s[4 * nb + 3] = d[3];
    block_fence(200 + nb, zero);
  }
  float x0, x1;
  row_max(s, x0, x1);
  const float m0 = fminf(n0, -x0), m1 = fminf(n1, -x1);
  sc0 = ex2(m0 - n0);
  sc1 = ex2(m1 - n1);
  n0 = m0; n1 = m1;
  softmax_shift(s, n0, n1);
  softmax_exp<0, 64>(s);
}

__device__ __forceinline__ void attn_consumer(const Ctx& cx, int qb, int hs, int wg, int cw, int lane, const __nv_bfloat16* x,
                                              const __nv_bfloat16* kc, __nv_bfloat16* out) {
  const int r = lane >> 2, c = lane & 3;
  const int lr0 = cw * 16 + r;
  const uint32_t full = cx.sb + SM_FULL;
  const uint32_t ring = cx.sb + SM_RING;
  uint32_t lo = ((cw & 3) * 16 + (lane & 15)) * 128 + (((lane >> 4) ^ (lane & 7)) << 4);
  const uint32_t slot = cx.sb + SM_SLOT + wg * 16384;
  auto frag = [&](int sl, int k) { return ((slot + sl * STAGE + lo) ^ ((k & 3) << 5)) + (k >> 2) * 8192; };
  auto park = [&](float (&a)[64], int sl, int k0, int k1, float f0, float f1, bool in_place = false) {
#pragma unroll
    for (int k = 0; k < 8; k++)
      if (k >= k0 && k < k1) {
        float t[8];
#pragma unroll
        for (int i = 0; i < 8; i++) {
          t[i] = a[8 * k + i] * ((i & 2) ? f1 : f0);
          if (in_place) a[8 * k + i] = t[i];
        }
        stsm4(frag(sl, k), pack2(t[0], t[1]), pack2(t[2], t[3]), pack2(t[4], t[5]), pack2(t[6], t[7]));
      }
  };
  const bool signaller = lane == 0 && (cw & 3) < 2;
  int my_turn = 1 + wg, other_turn = 2 - wg;

  uint32_t pf[32], q[32], empty_c;
  float o[64], l0, l1;
  {
    uint32_t xa[144];
    float rstd0, rstd1;
    {
      const uint32_t xb = cx.sb + SM_X + wg * 73728, xf = cx.sb + SM_XFULL + wg * 96;
      float sm[4][4] = {};
      prof(wg, 0);
      if (X_WARM) hmma_k16(sm[0], 0, 0, 0, 0, 0, 0);
      empty_c = mapa(cx.sb + SM_EMPTY, cw & 1);
      mbar_wait(xf, 0);
      if ((threadIdx.x & 127) == 0) profc(wg, 30);
      ln_fetch<0, 12>(xa, xb, lo);
      mbar_wait(xf + 8, 0);
      ln_fetch<12, 24>(xa, xb, lo);
      ln_sums<0, X_S1>(xa, sm);
      mbar_wait(xf + 16, 0);
      if ((threadIdx.x & 127) == 0) profc(wg, 1);
      ln_fetch<24, 36>(xa, xb, lo);
      ln_sums<X_S1, 36>(xa, sm);
      rstd0 = ((sm[0][0] + sm[1][0]) + (sm[2][0] + sm[3][0])) * (1.0f / DM);
      rstd1 = ((sm[0][2] + sm[1][2]) + (sm[2][2] + sm[3][2])) * (1.0f / DM);
    }
    asm volatile("" : "+f"(rstd0), "+f"(rstd1)::"memory");
    block_fence(38);
    if (wg) bar_arrive(other_turn, 256);
    block_fence(39);
    const uint32_t mm0 = pack2(rstd0, rstd0), mm1 = pack2(rstd1, rstd1);
    rstd0 -= bf_lo(mm0);
    rstd1 -= bf_lo(mm1);
    rstd0 *= rstd0 * (-0.25f * DM);
    rstd1 *= rstd1 * (-0.25f * DM);
    auto ln_finish = [&]() {
      rstd0 += __shfl_xor_sync(0xffffffffu, rstd0, 1); rstd1 += __shfl_xor_sync(0xffffffffu, rstd1, 1);
      rstd0 += __shfl_xor_sync(0xffffffffu, rstd0, 2); rstd1 += __shfl_xor_sync(0xffffffffu, rstd1, 2);
      rstd0 = ln_rstd(rstd0 * (1.0f / DM));
      rstd1 = ln_rstd(rstd1 * (1.0f / DM));
      if (c == 0) {
        *(float2*)(cx.sp + SM_STATS + 8 * lr0) = make_float2(bf_lo(mm0), rstd0);
        *(float2*)(cx.sp + SM_STATS + 8 * (lr0 + 8)) = make_float2(bf_lo(mm1), rstd1);
      }
      bar_arrive(BAR_GATE, 352);
      rstd0 *= SM_SCALE_LOG2;
      rstd1 *= SM_SCALE_LOG2;
    };
    ln_centre(xa, 0, X_C0, mm0, mm1, rstd0, rstd1);
    if (wg == 0) {
      bar_sync(4, 128);
      if (signaller) {
        asm volatile("mbarrier.arrive.shared::cluster.b64 _, [%0], 2;" ::"r"(empty_c + 16) : "memory");
        asm volatile("mbarrier.arrive.shared::cluster.b64 _, [%0], 2;" ::"r"(empty_c + 24) : "memory");
      }
      block_fence(37);
      pin(xa);
      ln_centre(xa, X_C0, X_CA == 1 ? X_C1 : X_C2, mm0, mm1, rstd0, rstd1);
    }
    pin(xa);
    if ((threadIdx.x & 127) == 0) profc(wg, 2);

#pragma unroll 1
    for (int p = 0;; p++) {
      const int st0 = p * 5, last = p == 3 ? 3 : 4;
#pragma unroll
      for (int i = 0; i < 5; i++) {
        const int st = st0 + i;
        const uint32_t sl = st & 3;
        mbar_wait(full + 8 * sl, (st >> 2) & 1);
        if (i != (wg ? last : 1)) bar_sync(my_turn, 256);
        wg_fence();
        const uint64_t db = mkdesc(ring + sl * STAGE, 16384);
        const int kb0 = i < 3 ? 8 * i : 8 * i - 4;
#pragma unroll
        for (int k = 0; k < (i == 2 ? 4 : 8); k++) {
          const int kb = kb0 + k;
          mma_n128<1>(o, xa[4 * kb], xa[4 * kb + 1], xa[4 * kb + 2], xa[4 * kb + 3], db + k * 128, kb > 0);
          if (i == 4 && k == X_HO) wg_commit();
        }
        wg_commit();
        if (i == 4 && X_HO < 7) wg_wait<1>();
        if (i != (wg ? last - 1 : 0)) bar_arrive(other_turn, 256);
        if (p == 0 && i <= X_FIN) {
          if ((wg || i >= X_CA) && i < 4)
            ln_centre(xa, i == 0 ? X_C0 : i == 1 ? X_C1 : i == 2 ? X_C2 : X_C3, i == 0 ? X_C1 : i == 1 ? X_C2 : i == 2 ? X_C3 : 72, mm0, mm1, rstd0, rstd1);
          if (i == X_FIN) ln_finish();
          pin(xa);
        }
        if (i == 0 || i == 2) {
          if (i ? p != 3 : wg) {
            wg_wait<0>();
            if (signaller) mbar_arrive_cluster(empty_c + 8 * sl);
          }
        } else if (i == 3) {
          if (p == 3) break;
        } else {
          wg_wait<1>();
          if (signaller && (i == 4 || !wg)) mbar_arrive_cluster(empty_c + 8 * ((st - 1) & 3));
          wg_wait<0>();
          if (signaller) mbar_arrive_cluster(empty_c + 8 * sl);
        }
      }
      if (p == 3) break;
      pin(o);
#pragma unroll
      for (int k = 0; k < 8; k += X_QP) {
        park(o, p, k, k + X_QP, rstd0, rstd1);
        if (k + X_QP < 8) block_fence(40 + k);
      }
    }
    wg_wait<1>();
    if (signaller) mbar_arrive_cluster(empty_c + 8 * ((NST_Q - 3) & 3));
    wg_wait<0>();
    if (signaller) mbar_arrive_cluster(empty_c + 8 * ((NST_Q - 2) & 3));
    prof(wg, 6);
#pragma unroll
    for (int i = 0; i < 32; i++) pf[i] = xa[112 + i];
    l0 = 0.25f * rcp(rstd0);
    l1 = 0.25f * rcp(rstd1);
  }

  uint32_t oa[96];
  const uint32_t zero = __shfl_sync(0xffffffffu, blockIdx.y, lane);
  my_turn = __shfl_sync(0xffffffffu, my_turn, lane);
  other_turn = __shfl_sync(0xffffffffu, other_turn, lane);
  lo = __shfl_sync(0xffffffffu, lo, lane);
  {
    float s[64], n0 = 0.f, n1 = 0.f;
    float lp0, lp1;
    float i0 = 0.f, i1 = 0.f;
    bool redo, shift = false;
    auto turn = [&](int it, auto kc_) -> bool {
      constexpr int KIND = decltype(kc_)::value;
      constexpr uint32_t slk = KIND == 1 ? 1 : 3, slv = KIND == 1 ? 2 : 0, slkn = KIND == 1 ? 3 : 1;
      constexpr int SPLIT = X_SPLIT, PARK1 = X_PARK;
      const uint32_t par = ((it + 10) >> 1) & 1;
      const int hsl = max((it >> 4) - 1, 0);
      const uint64_t dk = mkdesc(ring + slk * STAGE, 16), dv = mkdesc(ring + slv * STAGE, 16384);
      auto qk = [&]() {
#pragma unroll
        for (int k = 0; k < 8; k++) {
          if (KIND == 3) mma_n128_ss<0>(s, mkdesc(slot + hsl * STAGE, 16) + (k >> 2) * 512 + (k & 3) * 2, dk + (k >> 2) * 1024 + (k & 3) * 2, k > 0);
          else mma_n128<0>(s, q[4 * k], q[4 * k + 1], q[4 * k + 2], q[4 * k + 3], dk + (k >> 2) * 1024 + (k & 3) * 2, k > 0);
        }
        wg_commit();
      };
      auto pv = [&]() {
#pragma unroll
        for (int k = 0; k < 8; k++)
          mma_n128<1>(o, pf[4 * k], pf[4 * k + 1], pf[4 * k + 2], pf[4 * k + 3], dv + k * 128, k > 0 || KIND != 1 || (it & 15) != 1);
        wg_commit();
      };
      lp0 = l0; lp1 = l1;
#define TS(i)
      {
        TS(0)
        if (KIND == 3) {
          asm volatile("fence.proxy.async.shared::cta;" ::: "memory");
          const float t0 = lp0 + __shfl_xor_sync(0xffffffffu, lp0, 1), t1 = lp1 + __shfl_xor_sync(0xffffffffu, lp1, 1);
          i0 = rcp(t0 + __shfl_xor_sync(0xffffffffu, t0, 2));
          i1 = rcp(t1 + __shfl_xor_sync(0xffffffffu, t1, 2));
          asm volatile("" : "+f"(i0), "+f"(i1)::"memory");
          block_fence(31, zero);
#pragma unroll
          for (int k = 0; k < X_N1; k++) ldsm4(frag(hsl, k), q[4 * k], q[4 * k + 1], q[4 * k + 2], q[4 * k + 3]);
        }
        bar_sync(my_turn, 256);
        TS(1)
        if (KIND != 3) pin(q);
        pin(pf); pin(o);
        wg_fence();
        qk();
        TS(2)
        mbar_wait(full + 8 * slv, par);
        if (KIND == 1 && (it & 15) == 1) {
          park(o, hsl, PARK1, 8, i0, i1);
          wg_fence();
        }
        if (KIND == 3) {
#pragma unroll
          for (int k = X_N1; k < 8; k++) ldsm4(frag(hsl, k), q[4 * k], q[4 * k + 1], q[4 * k + 2], q[4 * k + 3]);
          block_fence(32, zero);
        }
        TS(3)
        pv();
        bar_arrive(other_turn, 256);
        TS(4)
        wg_wait<1>();
      }
      pin(s);
      mbar_arrive_cluster_now<10 * KIND + 3>(empty_c + 8 * slk, signaller, zero);
      TS(5)
      if (KIND == 3) {
        shift = false;
        n0 = n1 = l0 = l1 = 0.f;
      } else if (shift) {
        softmax_shift(s, n0, n1);
        pin(s);
      }
      softmax_exp<0, SPLIT>(s);
      pin(s);
      block_fence(10 * KIND + 4, zero);
      TS(6)
      wg_wait<0>();
      pin(o); pin(pf);
      mbar_arrive_cluster_now<10 * KIND + 5>(empty_c + 8 * slv, signaller, zero);
      TS(7)
      const bool kready = mbar_test(full + 8 * slkn, par);
      softmax_exp<SPLIT, 64>(s);
#pragma unroll
      for (int i = 0; i < 32; i++) pf[i] = pack2(s[2 * i], s[2 * i + 1]);
      row_sums(pf, l0, l1);
      if (KIND == 3) {
        park(o, hsl, 0, PARK1, i0, i1, X_IP);
        if (it) prof(wg, 6 + (it >> 4));
        if (it == 48 && cw == 0) bar_arrive(BAR_HELPER, 128);
      }
      redo = !(l0 + l1 <= SUM_HI) || (KIND == 3 && fminf(l0, l1) < SUM_LO);
      const bool leave = __any_sync(0xffffffffu, redo || !kready);
      return leave;
    };
    int it = -1;
#pragma unroll 1
    while (true) {
      mbar_wait(full + 8 * ((it & 1) ? 3 : 1), ((it + 10) >> 1) & 1);
      it++;
#pragma unroll 1
      while (true) {
        if (it & 1) {
          if (turn(it, IC<1>()) || it == 63) break;
          it++;
        }
        if (it & 15) {
          if (turn(it, IC<2>())) break;
        } else {
          if (turn(it, IC<3>())) break;
        }
        it++;
      }
      if (__any_sync(0xffffffffu, redo)) {
        const int j = it & 15;
        float sc0, sc1;
        if (__all_sync(0xffffffffu, l0 + l1 < 3.0e38f && (j || fminf(l0, l1) >= SUM_LO))) {
          softmax_rebase(s, n0, n1, sc0, sc1);
        } else {
          if (j == 0) n0 = n1 = 3.0e38f;
          softmax_redo(s, q, kc + (size_t)((hs * 2 + (it >> 5)) * SEQ + j * 128) * DH, lane, n0, n1, sc0, sc1, zero);
        }
        l0 = j ? lp0 * sc0 : 0.f;
        l1 = j ? lp1 * sc1 : 0.f;
        shift = true;
        if (j == 0) sc0 = sc1 = 1.f;
#pragma unroll
        for (int i = 0; i < 16; i++) { o[4 * i] *= sc0; o[4 * i + 1] *= sc0; o[4 * i + 2] *= sc1; o[4 * i + 3] *= sc1; }
#pragma unroll
        for (int i = 0; i < 32; i++) pf[i] = pack2(s[2 * i], s[2 * i + 1]);
        row_sums(pf, l0, l1);
      }
      if (it == 63) break;
    }
  }

#define TE(i) {}
  {
    constexpr int ST0 = NST_Q + NST_KV;
    float acc[32], red[32], first[32];
    auto await = [&](int st) { mbar_wait(full + 8 * (st & 3), (st >> 2) & 1); };
    auto release = [&](int st) { if (signaller) mbar_arrive_cluster(empty_c + 8 * (st & 3)); };
    auto unpark = [&](int h, int k0, int k1) {
#pragma unroll
      for (int k = 0; k < 8; k++)
        if (k >= k0 && k < k1) ldsm4(frag(h, k), oa[32 * h + 4 * k], oa[32 * h + 4 * k + 1], oa[32 * h + 4 * k + 2], oa[32 * h + 4 * k + 3]);
    };
    {
      float ar[64];
      asm volatile("fence.proxy.async.shared::cta;" ::: "memory");
      l0 += __shfl_xor_sync(0xffffffffu, l0, 1); l1 += __shfl_xor_sync(0xffffffffu, l1, 1);
      l0 += __shfl_xor_sync(0xffffffffu, l0, 2); l1 += __shfl_xor_sync(0xffffffffu, l1, 2);
      float f0 = rcp(l0), f1 = rcp(l1);
      asm volatile("" : "+f"(f0), "+f"(f1)::"memory");
      await(ST0 - 1);
      unpark(1, 0, 4);
      bar_sync(my_turn, 256);
      pin(pf); pin(o);
      wg_fence();
#pragma unroll
      for (int k = 0; k < 8; k++)
        mma_n128<1>(o, pf[4 * k], pf[4 * k + 1], pf[4 * k + 2], pf[4 * k + 3], mkdesc(ring + 3 * STAGE, 16384) + k * 128, 1);
      wg_commit();
      await(ST0);
      unpark(1, 4, 8);
      block_fence(61, zero);
#pragma unroll
      for (int k = 0; k < 8; k++) mma_n128_ss<1>(ar, mkdesc(slot, 16) + (k >> 2) * 512 + (k & 3) * 2, mkdesc(ring, 16384) + k * 128, k > 0);
      wg_commit();
      bar_arrive(other_turn, 256);
      wg_wait<1>();
      pin(o); pin(pf);
      mbar_arrive_cluster_now<62>(empty_c + 24, signaller, zero);
#pragma unroll
      for (int i = 0; i < 16; i++) {
        pf[2 * i] = pack2(o[4 * i] * f0, o[4 * i + 1] * f0);
        pf[2 * i + 1] = pack2(o[4 * i + 2] * f1, o[4 * i + 3] * f1);
      }
      pin(pf);
      prof(wg, 10);
#pragma unroll
      for (int u = 1; u < 4; u++) {
        await(ST0 + u);
        wg_wait<0>();
        release(ST0 + u - 1);
        bar_sync(my_turn, 256);
        wg_fence();
#pragma unroll
        for (int k = 0; k < 8; k++) {
          const uint32_t* a = (u == 1 ? oa + 32 : u == 2 ? pf : oa + 64) + 4 * k;
          mma_n128<1>(ar, a[0], a[1], a[2], a[3], mkdesc(ring + u * STAGE, 16384) + k * 128, 1);
        }
        wg_commit();
        bar_arrive(other_turn, 256);
        if (u < 3) {
          block_fence(62 + u, zero);
          unpark(u == 1 ? 2 : 0, 0, 8);
        }
      }
      mbar_wait(cx.sb + SM_BAR_MISC, 0);
      await(ST0 + 4);
      wg_wait<0>();
      release(ST0 + 3);
      pin(ar);
#pragma unroll
      for (int i = 0; i < 32; i++) { first[i] = ar[i]; red[i] = ar[32 + i]; }
    }
    const uint32_t tag = *(const uint32_t*)(cx.sp + SM_TAG);
    uint4* const xch = at<uint4>(cx.gs->part, (qb << 20) + lane * 16);
    auto send = [&](const float (&v)[32], int dst, int idx) {
      uint4* p = at<uint4>(xch, (dst * 8 + idx) * 2048);
#pragma unroll
      for (int i = 0; i < 4; i++)
        st_gran(p + i * 32, (pack2(v[8 * i], v[8 * i + 1]) & ~TAG_BIT) | tag, pack2(v[8 * i + 2], v[8 * i + 3]),
                pack2(v[8 * i + 4], v[8 * i + 5]), pack2(v[8 * i + 6], v[8 * i + 7]));
    };
    send(first, ((hs + 1) & 7) * 7, cw);
    int nrx = 1;
    auto half_step = [&](int s, auto hc, bool arrive) {
      constexpr int h = decltype(hc)::value;
      const int st = ST0 + 2 * s + h;
      const uint64_t db = mkdesc(ring + (st & 3) * STAGE, 16);
      bar_sync(my_turn, 256);
      if (h == 0) pin(pf);
#pragma unroll
      for (int i = 32 * h; i < 32 + 64 * h; i++) asm volatile("" : "+r"(oa[i])::"memory");
      wg_fence();
#pragma unroll
      for (int k = 0; k < 16; k++) {
        const int kb = h * 16 + k - 8;
        if (kb >= 0) mma_n64t(acc, oa[4 * kb], oa[4 * kb + 1], oa[4 * kb + 2], oa[4 * kb + 3], db + k * 128, 1);
        else mma_n64t(acc, pf[4 * k], pf[4 * k + 1], pf[4 * k + 2], pf[4 * k + 3], db + k * 128, k > 0);
      }
      wg_commit();
      if (arrive) bar_arrive(other_turn, 256);
    };
    auto source = [&](int n) { return at<const uint4>(xch, ((hs * 7 + n - 1) * 8 + cw) * 2048); };
    auto fetch = [&](uint32_t (&g)[16], const uint4* p) {
#pragma unroll
      for (int i = 0; i < 4; i++) ld_gran(p + i * 32, g[4 * i], g[4 * i + 1], g[4 * i + 2], g[4 * i + 3]);
    };
    uint32_t g[16];
#pragma unroll 1
    for (int s = 2; s < 8; s++) {
      const int st = ST0 + 2 * s;
      half_step(s, IC<0>(), true);
      if (s == 2) {
        bar_arrive(BAR_OA, 352);
        send(red, 56 + cw, hs);
#pragma unroll
        for (int i = 0; i < 32; i++) red[i] = 0.f;
      }
      await(st + 1);
      if (s > 3 && granules_ok(g, tag)) { add_granules(red, g); nrx++; }
      if (X_XS == 1 && s > 2) fetch(g, source(nrx));
      wg_wait<0>();
      if (s < 7) release(st);
      if (X_XS == 0 && s > 2) fetch(g, source(nrx));
      half_step(s, IC<1>(), true);
      await(st + 2);
      wg_wait<0>();
      if (s < 7) release(st + 1);
      pin(acc);
      if (s == 7) prof(wg, 19);
      if (s == 7) TE(0)
      send(acc, ((hs + s) & 7) * 7 + s - 1, cw);
    }
    TE(1)
    uint32_t xv[16], gt[16];
    {
      const int s = 8;
      uint32_t g2[16];
      half_step(s, IC<0>(), true);
      TE(2)
      await(NST_Q + NST_KV + NST_O - 1);
      cluster_arrive();
      mbar_wait(cx.sb + SM_BAR_XG, 0);
      const uint32_t tile = cx.sb + SM_XO + wg * 8192 + lo;
      if (granules_ok(g, tag)) { add_granules(red, g); nrx++; }
      fetch(g, source(nrx));
      block_fence(58, zero);
      wg_wait<0>();
      TE(3)
#pragma unroll
      for (int k = 0; k < 4; k++) ldsm4((tile ^ (k << 5)) + STAGE, gt[4 * k], gt[4 * k + 1], gt[4 * k + 2], gt[4 * k + 3]);
      half_step(s, IC<1>(), wg == 0);
      TE(4)
      block_fence(56, zero);
      const bool ok = granules_ok(g, tag);
      block_fence(57, zero + ok * 1000);
      const uint4* src = source(7);
      fetch(g2, src);
#pragma unroll
      for (int k = 0; k < 4; k++) ldsm4(tile ^ (k << 5), xv[4 * k], xv[4 * k + 1], xv[4 * k + 2], xv[4 * k + 3]);
      if (ok) { add_granules(red, g); nrx++; }
      TE(5)
      block_fence(59, zero);
      wg_wait<0>();
      pin(acc);
      TE(6)
#pragma unroll
      for (int i = 0; i < 32; i++) red[i] += acc[i];
      pin(red);
      TE(7)
      int n = 7;
#pragma unroll 1
      for (int spins = 0; spins < (1 << 16); spins++) {
        if (granules_ok(g2, tag)) {
          add_granules(red, g2);
          if (--n < nrx) {
            break;
          }
          src -= 1024;
        }
        fetch(g2, src);
      }
      TE(8)
    }
    prof(wg, 20);
    TE(9)
    const uint32_t ot = ring + 2 * STAGE + cw * (16 * 144);
    uint32_t ow[16];
#pragma unroll
    for (int i = 0; i < 16; i++) ow[i] = fma2(pack2(red[2 * i], red[2 * i + 1]), gt[i], xv[i]);
#pragma unroll
    for (int i = 0; i < 4; i++)
      stsm4(ot + (lane & 15) * 144 + (2 * i + (lane >> 4)) * 16, ow[4 * i], ow[4 * i + 1], ow[4 * i + 2], ow[4 * i + 3]);
    __syncwarp();
#pragma unroll
    for (int i = 0; i < 4; i++) {
      uint4 v;
      lds128(ot + (i * 4 + (lane >> 3)) * 144 + (lane & 7) * 16, v.x, v.y, v.z, v.w);
      at<uint4>(out, ((qb * 128 + cw * 16 + (lane >> 3)) * DM + hs * 64 + (lane & 7) * 8) * 2)[i * (4 * DM / 8)] = v;
    }
    TE(10)
    prof(wg, 22);
  }
}

constexpr int FST_X = 24, FST_END = FST_X + 14 * 12;
__device__ __forceinline__ void ffn_producer(const Ctx& cx, int f, const CUtensorMap* tmX, const CUtensorMap* tmG,
                                             const CUtensorMap* tmU, const CUtensorMap* tmD) {
  const uint32_t full = cx.sb + SM_FULL, empty = cx.sb + SM_EMPTY;
  int pair = -2, u = 0;
#pragma unroll 1
  for (int st = 0; st < FST_END; st++) {
    const uint32_t sl = st & 7;
    const int unit = pair * 2 + (u & 1), k = u >> 1, k3 = k >= 3 ? k - 3 : k;
    if (unit < 27) {
      mbar_wait(empty + 8 * sl, ((st >> 3) & 1) ^ 1);
      mbar_expect_tx(full + 8 * sl, FSTAGE);
      if (pair < 0) tma3d(cx.sb + sl * FSTAGE, tmX, f * 512 + ((pair + 2) * 4 + (k >= 3) * 2 + (u & 1)) * 64, k3 * 3, full + 8 * sl);
      else if (pair < 9) tma2d_stream(cx.sb + sl * FSTAGE, k < 3 ? tmG : tmU, f * 1152 + unit * 64, k3 * 192, full + 8 * sl);
      else tma2d_stream(cx.sb + sl * FSTAGE, tmD, (unit - 18) * 64, f * 1152 + k * 192, full + 8 * sl);
    }
    if (++u == 12) { u = 0; pair++; }
  }
}

__device__ __forceinline__ void ffn_consumer(const Ctx& cx, int f, int wg, int cw, int lane, const __nv_bfloat16* x,
                                             const __nv_bfloat16* w_r) {
  const int r = lane >> 2, c = lane & 3, tid = cw * 32 + lane;
  unsigned e = 0;
  if (tid == 0) {
    e = cx.gs->launch[blockIdx.x];
    cx.gs->launch[blockIdx.x] = e + 1;
    *(unsigned*)(cx.sp + SM_TAG) = e;
  }
  if (tid < 72) *(uint4*)(cx.sp + SM_H + tid * 16) = *(const uint4*)(w_r + tid * 8);
  bar_sync(3, 256);
  prof(wg, 0);
  const uint32_t full = cx.sb + SM_FULL, empty = cx.sb + SM_EMPTY;
  const bool signaller = (tid & 127) == 0;
#pragma unroll 1
  for (int b = wg; b < 8; b += 2) {
    const int row0 = f * 512 + b * 64 + (cw & 3) * 16 + r;
    const uint32_t lo = ((cw & 3) * 16 + (lane & 15)) * 128 + (((lane >> 4) ^ (lane & 7)) << 4);
    LnAcc a;
    a.clear();
#pragma unroll 1
    for (int bx = 0; bx < 9; bx++) {
      const int st = (b >> 1) * 6 + (bx / 3) * 2 + wg;
      if (bx % 3 == 0) mbar_wait(full + 8 * (st & 7), (st >> 3) & 1);
#pragma unroll
      for (int k = 0; k < 4; k++) {
        uint32_t x0, x1, x2, x3;
        ldsm4(cx.sb + (st & 7) * FSTAGE + (bx % 3) * 8192 + (lo ^ (k << 5)), x0, x1, x2, x3);
        ln_accum1(a, k & 1, x0, x1, x2, x3);
      }
    }
    prof(wg, 8 + (b >> 1) * 3);
    float mean0, rstd0, mean1, rstd1;
    ln_stats(a, lane, mean0, rstd0, mean1, rstd1);
    prof(wg, 9 + (b >> 1) * 3);
    const uint32_t mm0 = pack2(mean0, mean0), mm1 = pack2(mean1, mean1);
    float d0[4] = {0, 0, 0, 0}, d1[4] = {0, 0, 0, 0};
#pragma unroll 1
    for (int bx = 0; bx < 9; bx++) {
      const int st = (b >> 1) * 6 + (bx / 3) * 2 + wg;
#pragma unroll
      for (int k = 0; k < 4; k++) {
        uint32_t n[4];
        ldsm4(cx.sb + (st & 7) * FSTAGE + (bx % 3) * 8192 + (lo ^ (k << 5)), n[0], n[1], n[2], n[3]);
        const uint8_t* wp = cx.sp + SM_H + (bx * 4 + k) * 32 + 4 * c;
#pragma unroll
        for (int i = 0; i < 4; i++) {
          const uint32_t t = sub2(n[i], (i & 1) ? mm1 : mm0);
          const float rs = (i & 1) ? rstd1 : rstd0;
          n[i] = pack2(bf_lo(t) * rs, bf_hi(t) * rs);
        }
        if (k & 1) hmma_k16(d1, n[0], n[1], n[2], n[3], *(const uint32_t*)wp, *(const uint32_t*)(wp + 16));
        else hmma_k16(d0, n[0], n[1], n[2], n[3], *(const uint32_t*)wp, *(const uint32_t*)(wp + 16));
      }
    }
    prof(wg, 10 + (b >> 1) * 3);
    bar_sync(4 + wg, 128);
    if (signaller) {
#pragma unroll
      for (int i = 0; i < 3; i++) mbar_arrive(empty + 8 * (((b >> 1) * 6 + i * 2 + wg) & 7));
    }
    if (c == 0) {
      cx.gs->r[row0] = bfr(d0[0] + d1[0]);
      cx.gs->r[row0 + 8] = bfr(d0[2] + d1[2]);
      cx.gs->stats[row0] = make_float2(mean0, rstd0);
      cx.gs->stats[row0 + 8] = make_float2(mean1, rstd1);
    }
  }
  prof(wg, 1);
  bar_sync(3, 256);
  e = *(const unsigned*)(cx.sp + SM_TAG);
  if (tid == 0) {
    atom_add_acq_rel(&cx.gs->rcnt);
#pragma unroll 1
    for (int n = 0; n < (1 << 16) && (int)(ld_acquire(&cx.gs->rcnt) - 4 * (e + 1)) < 0; n++) {}
  }
  bar_sync(3, 256);
  prof(wg, 2);
  uint32_t key[8];
#pragma unroll
  for (int i = 0; i < 8; i++) {
    const int row = i * 256 + tid;
    const uint32_t b = __float_as_uint(__ldcg(&cx.gs->r[row])) >> 16;
    key[i] = (((b & 0x8000u) ? (~b & 0xFFFFu) : (b | 0x8000u)) << 16) | (uint32_t)(0xFFFF - row);
  }
  int mysel = 0;
#pragma unroll 1
  for (int k = 0; k < TOPC; k++) {
    uint32_t m = key[0];
#pragma unroll
    for (int i = 1; i < 8; i++) m = max(m, key[i]);
    m = __reduce_max_sync(0xffffffffu, m);
    uint32_t* tk = (uint32_t*)(cx.sp + SM_TOPK) + (k & 1) * 8;
    if (lane == 0) tk[cw] = m;
    bar_sync(3, 256);
    m = __reduce_max_sync(0xffffffffu, tk[lane & 7]);
#pragma unroll
    for (int i = 0; i < 8; i++) if (key[i] == m) key[i] = 0;
    if (k == cw) mysel = 0xFFFF - (int)(m & 0xFFFF);
  }
  {
    const float2 st = __ldcg(&cx.gs->stats[mysel]);
    const uint32_t mm = pack2(st.x, st.x);
#pragma unroll 3
    for (int i = 0; i < 9; i++) {
      const uint32_t t = sub2(*(const uint32_t*)(x + (size_t)mysel * DM + i * 64 + 2 * lane), mm);
      *(uint32_t*)(cx.sp + SM_XSEL + i * 1024 + cw * 128 + (((lane >> 2) ^ cw) << 4) + (lane & 3) * 4) =
          pack2(bf_lo(t) * st.y, bf_hi(t) * st.y);
    }
    if (lane == 0) *(int*)(cx.sp + SM_IDX + 4 * cw) = mysel;
  }
  asm volatile("fence.proxy.async.shared::cta;" ::: "memory");
  bar_sync(3, 256);
  prof(wg, 3);
  auto run = [&](float (&acc)[4], int st, int n, uint32_t b) {
#pragma unroll 1
    for (int u = 0; u < n; u++, st += 2, b += 3072) {
      const uint32_t sl = st & 7;
      mbar_wait(full + 8 * sl, (st >> 3) & 1);
      wg_fence();
      const uint64_t da = mkdesc(cx.sb + sl * FSTAGE, 16), db = mkdesc(b, 16);
#pragma unroll
      for (int k = 0; k < 12; k++) mma_n8(acc, da + k * 128, db + (k >> 2) * 64 + (k & 3) * 2, u > 0 || k > 0);
      wg_commit();
      wg_wait<0>();
      if (signaller) mbar_arrive(empty + 8 * sl);
    }
    pin(acc);
  };
#pragma unroll 1
  for (int unit = wg; unit < 27; unit += 2) {
    if (unit >> 1 == 9) {
      asm volatile("fence.proxy.async.shared::cta;" ::: "memory");
      bar_sync(3, 256);
      prof(wg, 4);
    }
    const bool gu = unit < 18;
    float a0[4], a1[4];
#pragma unroll 1
    for (int m = 0; m < (gu ? 2 : 1); m++) {
      run(a1, FST_X + (unit >> 1) * 12 + m * 6 + wg, gu ? 3 : 6, cx.sb + (gu ? SM_XSEL : SM_H));
      if (m == 0) { a0[0] = a1[0]; a0[1] = a1[1]; a0[2] = a1[2]; a0[3] = a1[3]; }
    }
#pragma unroll
    for (int i = 0; i < 4; i++) {
      const int fl = (cw & 3) * 16 + r + (i >> 1) * 8, tok = 2 * c + (i & 1);
      if (gu) {
        const float h = bfr(silu_f(bfr(a0[i]))) * bfr(a1[i]);
        *(__nv_bfloat16*)(cx.sp + SM_H + unit * 1024 + tok * 128 + (((fl >> 3) ^ tok) << 4) + (fl & 7) * 2) = __float2bfloat16_rn(h);
      } else {
        cx.gs->ypart[(f * TOPC + tok) * DM + (unit - 18) * 64 + fl] = a1[i];
      }
    }
  }
  prof(wg, 5);
  bar_sync(3, 256);
  if (tid == 0) *(unsigned*)(cx.sp + SM_TOPK) = atom_add_acq_rel(&cx.gs->ycnt) == 4 * e + 3;
  bar_sync(3, 256);
  if (*(const unsigned*)(cx.sp + SM_TOPK)) {
    const int row = *(const int*)(cx.sp + SM_IDX + 4 * cw);
    const float rs = bfr(rcp(1.0f + ex2(-1.4426950408889634f * __ldcg(&cx.gs->r[row]))));
#pragma unroll 1
    for (int d = lane * 2; d < DM; d += 192) {
#pragma unroll
      for (int i = 0; i < 3; i++) {
        const float* p = cx.gs->ypart + cw * DM + d + i * 64;
        const float2 a = __ldcg((const float2*)p), b = __ldcg((const float2*)(p + TOPC * DM)),
                     e2 = __ldcg((const float2*)(p + 2 * TOPC * DM)), h = __ldcg((const float2*)(p + 3 * TOPC * DM));
        const uint32_t y = pack2((a.x + b.x) + (e2.x + h.x), (a.y + b.y) + (e2.y + h.y));
        const uint32_t u = pack2(bf_lo(y) * rs, bf_hi(y) * rs);
        *(float2*)(cx.gs->upd + cw * DM + d + i * 64) = make_float2(bf_lo(u), bf_hi(u));
      }
    }
    if (lane == 0) cx.gs->idx[cw] = row;
    bar_sync(3, 256);
    if (tid == 0) st_release(&cx.gs->ffn_flag, e + 1);
    prof(wg, 6);
  }
}

struct Maps { CUtensorMap m[9]; };
__global__ void __cluster_dims__(2, 1, 1) __launch_bounds__(THREADS, 1)
fused_kernel(const __nv_bfloat16* __restrict__ x, const __nv_bfloat16* __restrict__ w_r, const __nv_bfloat16* __restrict__ wq,
             const __nv_bfloat16* __restrict__ wo, __nv_bfloat16* __restrict__ out, Scratch* gs,
             const __grid_constant__ Maps maps, const __nv_bfloat16* __restrict__ kc) {
  const CUtensorMap &tmX = maps.m[0], &tmWq = maps.m[1], &tmK = maps.m[2], &tmV = maps.m[3], &tmWo = maps.m[4], &tmG = maps.m[5],
                    &tmU = maps.m[6], &tmD = maps.m[7];
  extern __shared__ __align__(1024) uint8_t smem_raw[];
  prof(0, 23, 511);
  Ctx cx;
  cx.sb = smem_u32(smem_raw);
  cx.sp = smem_raw;
  cx.gs = gs;
  cx.rank = blockIdx.x & 1;
  const int warp = __shfl_sync(0xffffffffu, threadIdx.x >> 5, 0);
  const int cluster = blockIdx.x >> 1;
  const bool is_ffn = blockIdx.x >= N_ATT_CTA;
  const int c7 = ((cluster - 36) * 37) >> 8;
  const int hs = cluster < 4 ? 4 + cluster : cluster < 36 ? (cluster - 4) >> 3 : 4 + c7;
  const int qb = (cluster < 4 ? 0 : cluster < 36 ? (cluster - 4) & 7 : cluster - 35 - 7 * c7) * 2 + cx.rank;

  extern __shared__ __align__(1024) uint8_t smem_alias[];
  const uint32_t xf = smem_u32(smem_alias) + SM_MISC + warp * 24;
  if (warp == 4 && elect_one()) prefetch_tmap(&tmX);
  if (warp == 6 && !is_ffn && elect_one()) prefetch_l2(x + (size_t)(qb * 128 + hs * 8) * DM, 8 * DM * 2);
  if (elect_one()) {
    const uint32_t cnt = (warp > 4 && warp < 8 && !is_ffn) ? 4 : 1;
#pragma unroll
    for (int i = 0; i < 3; i++) mbar_init(xf + 8 * i, cnt);
    asm volatile("fence.proxy.async.shared::cta;" ::: "memory");
    asm volatile("fence.mbarrier_init.release.cluster;" ::: "memory");
  }
  __syncwarp();
  cluster_arrive();
  if (warp == 4 && !is_ffn) {
    if (elect_one()) {
      profc(0, 28);
#pragma unroll
      for (int i = 0; i < 3; i++) {
        mbar_expect_tx(xf + 8 * i, 24576);
        tma3d(xf - SM_XFULL + SM_X + i * 24576, &tmX, qb * 128, i * 3, xf + 8 * i);
      }
      profc(0, 29);
    }
  } else if (warp > 8 && elect_one()) {
    prefetch_tmap(&tmX + (is_ffn ? warp - 4 : warp - 8));
  }
  __syncwarp();

  if (warp < 4) {
    asm volatile("setmaxnreg.dec.sync.aligned.u32 24;");
    cluster_wait();
    prof(0, 24, 511);
    if (warp == 0) {
      if (!is_ffn) attn_producer(cx, qb, hs, &tmX, &tmK, &tmV, &tmWq, &tmWo);
      else if (elect_one()) ffn_producer(cx, blockIdx.x - N_ATT_CTA, &tmX, &tmG, &tmU, &tmD);
      prof(0, 25, 511);
    } else if (!is_ffn) {
      attn_gate(cx, qb, hs, threadIdx.x - 32, x);
      if (warp == 1) attn_helper(cx, qb, hs, read_lane(), x, wo, &maps.m[8]);
      else { bar_arrive(BAR_HELPER, 128); bar_sync(BAR_OA, 352); }
      attn_finish8(cx, qb, hs, warp - 1, read_lane(), out);

    }
    __syncwarp();
    cluster_arrive();
    cluster_wait();
  } else {
    asm volatile("setmaxnreg.inc.sync.aligned.u32 240;");
    cluster_wait();
    const int cw = warp - 4, wg = cw >> 2;
    if (is_ffn) ffn_consumer(cx, blockIdx.x - N_ATT_CTA, wg, cw, read_lane(), x, w_r);
    else attn_consumer(cx, qb, hs, wg, cw, read_lane(), x, kc, out);
  }
}

typedef CUresult (*EncodeFn)(CUtensorMap*, CUtensorMapDataType, cuuint32_t, void*, const cuuint64_t*, const cuuint64_t*,
                             const cuuint32_t*, const cuuint32_t*, CUtensorMapInterleave, CUtensorMapSwizzle,
                             CUtensorMapL2promotion, CUtensorMapFloatOOBfill);

void encode(EncodeFn fn, CUtensorMap* m, const void* p, int rank, const cuuint64_t* dims, const cuuint64_t* strides,
            const cuuint32_t* box) {
  const cuuint32_t es[5] = {1, 1, 1, 1, 1};
  fn(m, CU_TENSOR_MAP_DATA_TYPE_BFLOAT16, rank, const_cast<void*>(p), dims, strides, box, es, CU_TENSOR_MAP_INTERLEAVE_NONE,
     CU_TENSOR_MAP_SWIZZLE_128B, CU_TENSOR_MAP_L2_PROMOTION_L2_128B, CU_TENSOR_MAP_FLOAT_OOB_FILL_NONE);
}
void encode2d(EncodeFn fn, CUtensorMap* m, const void* p, uint64_t rows, uint64_t cols, uint32_t box_rows) {
  const cuuint64_t dims[2] = {cols, rows}, strides[1] = {cols * 2};
  const cuuint32_t box[2] = {64, box_rows};
  encode(fn, m, p, 2, dims, strides, box);
}

}

extern "C" void kernel_launch(void* const* d_in, const int* in_sizes, int n_in, void* d_out, int out_size) {
  (void)in_sizes; (void)n_in; (void)out_size;
  void* fnp = nullptr;
  cudaDriverEntryPointQueryResult qr;
  cudaGetDriverEntryPoint("cuTensorMapEncodeTiled", &fnp, cudaEnableDefault, &qr);
  EncodeFn fn = (EncodeFn)fnp;
  Maps maps;
  CUtensorMap &tmX = maps.m[0], &tmWq = maps.m[1], &tmK = maps.m[2], &tmV = maps.m[3], &tmWo = maps.m[4], &tmG = maps.m[5],
              &tmU = maps.m[6], &tmD = maps.m[7];
  encode2d(fn, &tmK, d_in[1], 16 * SEQ, DH, 128);
  encode2d(fn, &tmV, d_in[2], 16 * SEQ, DH, 128);
  encode2d(fn, &tmWq, d_in[3], DM, 4096, 64);
  {
    const cuuint64_t dims[3] = {64, SEQ, 9}, strides[2] = {DM * 2, 128};
    const cuuint32_t box[3] = {64, 64, 3};
    encode(fn, &tmX, d_in[0], 3, dims, strides, box);
  }
  encode2d(fn, &maps.m[8], d_in[0], SEQ, DM, 16);
  encode2d(fn, &tmWo, d_in[4], 4096, DM, 128);
  encode2d(fn, &tmG, d_in[7], DM, FF, 192);
  encode2d(fn, &tmU, d_in[8], DM, FF, 192);
  encode2d(fn, &tmD, d_in[9], FF, DM, 192);
  cudaFuncSetAttribute(fused_kernel, cudaFuncAttributeMaxDynamicSharedMemorySize, SM_TOTAL);
  void* gs = nullptr;
  cudaGetSymbolAddress(&gs, g_scratch);
  fused_kernel<<<N_CTA, THREADS, SM_TOTAL>>>((const __nv_bfloat16*)d_in[0], (const __nv_bfloat16*)d_in[6], (const __nv_bfloat16*)d_in[3],
                                            (const __nv_bfloat16*)d_in[4], (__nv_bfloat16*)d_out, (Scratch*)gs, maps, (const __nv_bfloat16*)d_in[1]);
}
```

```cpp
#include <cuda_runtime.h>
#include <cuda_bf16.h>
#include <cuda.h>
#include <stdint.h>

namespace {

constexpr int SEQ = 2048, DM = 576, DH = 128, FF = 4608, TOPC = 8;
constexpr int N_ATT_CTA = 128, N_CTA = 132;
constexpr int THREADS = 384;

constexpr uint32_t SM_RING = 0;
constexpr uint32_t STAGE = 32768;
constexpr uint32_t SM_SLOT = 131072;
constexpr uint32_t FSTAGE = 24576;
constexpr uint32_t SM_XSEL = 196608;
constexpr uint32_t SM_H = 205824;
constexpr uint32_t SM_MISC = 229376;
constexpr uint32_t SM_FULL = SM_MISC, SM_BAR_MISC = SM_MISC + 64, SM_BAR_XG = SM_MISC + 72, SM_BAR_P8 = SM_MISC + 80, SM_BAR_Q3 = SM_MISC + 88, SM_XFULL = SM_MISC + 96,
                   SM_EMPTY = SM_MISC + 120, SM_BAR_ROWS = SM_MISC + 216, SM_TAG = SM_MISC + 288,
                   SM_ROWS = SM_MISC + 304, SM_BOX8 = SM_MISC + 1024;
constexpr uint32_t SM_TOTAL = SM_MISC + 3072;
constexpr uint32_t SM_X = SM_MISC - 147456;

constexpr int BAR_ROWS = 6, BAR_HELPER = 7, BAR_OA = 8;
constexpr int NST_Q = 18, NST_KV = 128, NST_O = 18;
constexpr uint32_t SL_KE = (NST_Q - 1) & 3, SL_VE = NST_Q & 3, SL_KO = (NST_Q + 1) & 3, SL_VO = (NST_Q + 2) & 3;
#define X_ORDER 0
#define X_PF 3
#define X_PFQ 3
#define X_REL 0
#define X_SLEEP8 700
#define X_QP 2
#define X_WARM 0
#define X_S1 12
#define X_IP 0
#define X_XS 0
#define X_CA2 1
#define X_RS 1
#define X_DS 0
#define X_N1 4
#define X_SPLIT 44
#define X_PARK 5
#define X_C0 32
#define X_C1 40
#define X_C2 56
#define X_C3 72
#define X_CA 1
#define X_FIN 4
constexpr float SM_SCALE_LOG2 = 0.08838834764831845f * 1.4426950408889634f;

struct Scratch {
  uint4 part[16 * 64 * 2 * 4 * 128];
  uint4 gate[N_ATT_CTA * 144 * 8];
  uint4 q3[N_ATT_CTA * 1024];
  uint4 xn[SEQ * DM / 8];
  uint32_t key[SEQ];
  float ypart[4 * TOPC * DM];
  uint32_t top[32];
  unsigned launch[160];
  unsigned rows[16 * 32];
  unsigned q3_flag[N_ATT_CTA];
  unsigned ycnt;
};
__device__ __align__(1024) Scratch g_scratch;

__device__ __forceinline__ void prof(int, int, int = 0) {}
__device__ __forceinline__ void profc(int, int) {}

__device__ __forceinline__ uint32_t smem_u32(const void* p) { return (uint32_t)__cvta_generic_to_shared(p); }
__device__ __forceinline__ void mbar_init(uint32_t bar, uint32_t cnt) {
  asm volatile("mbarrier.init.shared::cta.b64 [%0], %1;" ::"r"(bar), "r"(cnt) : "memory");
}
__device__ __forceinline__ void mbar_expect_tx(uint32_t bar, uint32_t bytes) {
  asm volatile("mbarrier.arrive.expect_tx.shared::cta.b64 _, [%0], %1;" ::"r"(bar), "r"(bytes) : "memory");
}
__device__ __forceinline__ void mbar_arrive(uint32_t bar) {
  asm volatile("mbarrier.arrive.shared::cta.b64 _, [%0];" ::"r"(bar) : "memory");
}
__device__ __forceinline__ void mbar_arrive_cluster(uint32_t bar_cluster_addr) {
  asm volatile("mbarrier.arrive.shared::cluster.b64 _, [%0];" ::"r"(bar_cluster_addr) : "memory");
}
template <int ID>
__device__ __forceinline__ void mbar_arrive_cluster_now(uint32_t bar_cluster_addr, bool pred, uint32_t zero) {
  asm volatile("{\n.reg .pred p, q;\nsetp.ne.u32 p, %1, 0;\nsetp.eq.u32 q, %2, %3;\n"
               "ARR_LOOP:\n@p mbarrier.arrive.shared::cluster.b64 _, [%0];\n@q bra.uni ARR_LOOP;\n}"
               ::"r"(bar_cluster_addr), "r"((uint32_t)pred), "r"(zero), "n"(ID) : "memory");
}
__device__ __forceinline__ void block_fence(int id, uint32_t zero = blockIdx.y) {
  asm volatile("{\n.reg .pred q;\nsetp.eq.u32 q, %0, %1;\nBF_LOOP:\n@q st.volatile.shared.u32 [%0], %0;\n@q bra.uni BF_LOOP;\n}"
               ::"r"(zero), "r"(id) : "memory");
}
__device__ __forceinline__ bool mbar_test(uint32_t bar, uint32_t parity) {
  uint32_t ok;
  asm volatile("{\n.reg .pred p;\nmbarrier.test_wait.parity.shared::cta.b64 p, [%1], %2;\nselp.u32 %0, 1, 0, p;\n}"
               : "=r"(ok) : "r"(bar), "r"(parity) : "memory");
  return ok;
}
__device__ __forceinline__ void mbar_wait(uint32_t bar, uint32_t parity) {
  asm volatile("{\n.reg .pred p, q;\n.reg .u32 n;\nmov.u32 n, 0;\n"
               "WAIT_LOOP:\nmbarrier.try_wait.parity.shared::cta.b64 p, [%0], %1;\n"
               "add.u32 n, n, 1;\nsetp.lt.u32 q, n, 4194304;\nand.pred q, q, !p;\n@q bra WAIT_LOOP;\n}"
               ::"r"(bar), "r"(parity) : "memory");
}
__device__ __forceinline__ uint32_t mapa(uint32_t addr, uint32_t rank) {
  uint32_t r;
  asm volatile("mapa.shared::cluster.u32 %0, %1, %2;" : "=r"(r) : "r"(addr), "r"(rank));
  return r;
}
__device__ __forceinline__ void cluster_arrive() { asm volatile("barrier.cluster.arrive.relaxed.aligned;" ::: "memory"); }
__device__ __forceinline__ bool elect_one() {
  uint32_t p;
  asm volatile("{\n.reg .pred p;\nelect.sync _|p, 0xffffffff;\nselp.u32 %0, 1, 0, p;\n}" : "=r"(p));
  return p;
}
__device__ __forceinline__ int read_lane() { return threadIdx.x & 31; }
__device__ __forceinline__ void cluster_wait() { asm volatile("barrier.cluster.wait.acquire.aligned;" ::: "memory"); }
__device__ __forceinline__ void bar_sync(int id, int n) { asm volatile("barrier.cta.sync %0, %1;" ::"r"(id), "r"(n) : "memory"); }
__device__ __forceinline__ void bar_arrive(int id, int n) { asm volatile("barrier.cta.arrive %0, %1;" ::"r"(id), "r"(n) : "memory"); }

__device__ __forceinline__ uint64_t policy_evict_first() {
  uint64_t p;
  asm("createpolicy.fractional.L2::evict_first.b64 %0, 1.0;" : "=l"(p));
  return p;
}
__device__ __forceinline__ uint64_t policy_evict_normal() {
  uint64_t p;
  asm("createpolicy.fractional.L2::evict_normal.b64 %0, 1.0;" : "=l"(p));
  return p;
}
__device__ __forceinline__ void tma3d(uint32_t dst, const CUtensorMap* tm, int c1, int c2, uint32_t bar) {
  asm volatile("cp.async.bulk.tensor.3d.shared::cluster.global.mbarrier::complete_tx::bytes [%0], [%1, {%2, %3, %4}], [%5];"
               ::"r"(dst), "l"(tm), "r"(0), "r"(c1), "r"(c2), "r"(bar) : "memory");
}
__device__ __forceinline__ void tma2d(uint32_t dst, const CUtensorMap* tm, int c0, int c1, uint32_t bar) {
  asm volatile("cp.async.bulk.tensor.2d.shared::cluster.global.mbarrier::complete_tx::bytes [%0], [%1, {%2, %3}], [%4];"
               ::"r"(dst), "l"(tm), "r"(c0), "r"(c1), "r"(bar) : "memory");
}
__device__ __forceinline__ void tma2d_stream(uint32_t dst, const CUtensorMap* tm, int c0, int c1, uint32_t bar) {
  asm volatile("{\n.reg .b64 pol;\ncreatepolicy.fractional.L2::evict_first.b64 pol, 1.0;\n"
               "cp.async.bulk.tensor.2d.shared::cluster.global.mbarrier::complete_tx::bytes.L2::cache_hint [%0], [%1, {%2, %3}], [%4], pol;\n}"
               ::"r"(dst), "l"(tm), "r"(c0), "r"(c1), "r"(bar) : "memory");
}
__device__ __forceinline__ void tma2d_prefetch(const CUtensorMap* tm, int c0, int c1) {
  asm volatile("cp.async.bulk.prefetch.tensor.2d.L2.global [%0, {%1, %2}];" ::"l"(tm), "r"(c0), "r"(c1) : "memory");
}
__device__ __forceinline__ void prefetch_l2(const void* p, uint32_t bytes) {
  asm volatile("cp.async.bulk.prefetch.L2.global [%0], %1;" ::"l"(p), "r"(bytes) : "memory");
}
__device__ __forceinline__ void prefetch_tmap(const CUtensorMap* tm) {
  asm volatile("prefetch.tensormap [%0];" ::"l"(tm) : "memory");
}

__device__ __forceinline__ void wg_fence() { asm volatile("wgmma.fence.sync.aligned;" ::: "memory"); }
__device__ __forceinline__ void wg_commit() { asm volatile("wgmma.commit_group.sync.aligned;" ::: "memory"); }
template <int N> __device__ __forceinline__ void wg_wait() { asm volatile("wgmma.wait_group.sync.aligned %0;" ::"n"(N) : "memory"); }

__device__ __forceinline__ uint64_t mkdesc(uint32_t addr, uint32_t lbo_bytes) {
  return (uint64_t)(((addr & 0x3FFFF) >> 4) | ((lbo_bytes >> 4) << 16)) | ((uint64_t)0x40000040u << 32);
}
template <int N> __device__ __forceinline__ void pin(float (&a)[N]) {
#pragma unroll
  for (int i = 0; i < N; i++) asm volatile("" : "+f"(a[i])::"memory");
}
template <int N> __device__ __forceinline__ void pin(uint32_t (&a)[N]) {
#pragma unroll
  for (int i = 0; i < N; i++) asm volatile("" : "+r"(a[i])::"memory");
}

#define F8(d, o) "+f"(d[o]), "+f"(d[o + 1]), "+f"(d[o + 2]), "+f"(d[o + 3]), "+f"(d[o + 4]), "+f"(d[o + 5]), "+f"(d[o + 6]), "+f"(d[o + 7])
#define R32A "%0, %1, %2, %3, %4, %5, %6, %7, %8, %9, %10, %11, %12, %13, %14, %15, %16, %17, %18, %19, %20, %21, %22, %23, %24, %25, %26, %27, %28, %29, %30, %31"
#define R32B "%32, %33, %34, %35, %36, %37, %38, %39, %40, %41, %42, %43, %44, %45, %46, %47, %48, %49, %50, %51, %52, %53, %54, %55, %56, %57, %58, %59, %60, %61, %62, %63"

template <int TB>
__device__ __forceinline__ void mma_n128(float (&d)[64], uint32_t a0, uint32_t a1, uint32_t a2, uint32_t a3, uint64_t db, int acc) {
  asm volatile("{\n.reg .pred p;\nsetp.ne.b32 p, %69, 0;\n"
               "wgmma.mma_async.sync.aligned.m64n128k16.f32.bf16.bf16 {" R32A ", " R32B "}, {%64, %65, %66, %67}, %68, p, 1, 1, %70;\n}\n"
               : F8(d, 0), F8(d, 8), F8(d, 16), F8(d, 24), F8(d, 32), F8(d, 40), F8(d, 48), F8(d, 56)
               : "r"(a0), "r"(a1), "r"(a2), "r"(a3), "l"(db), "r"(acc), "n"(TB));
}
template <int TB>
__device__ __forceinline__ void mma_n128_ss(float (&d)[64], uint64_t da, uint64_t db, int acc) {
  asm volatile("{\n.reg .pred p;\nsetp.ne.b32 p, %66, 0;\n"
               "wgmma.mma_async.sync.aligned.m64n128k16.f32.bf16.bf16 {" R32A ", " R32B "}, %64, %65, p, 1, 1, 0, %67;\n}\n"
               : F8(d, 0), F8(d, 8), F8(d, 16), F8(d, 24), F8(d, 32), F8(d, 40), F8(d, 48), F8(d, 56)
               : "l"(da), "l"(db), "r"(acc), "n"(TB));
}
template <int TB>
__device__ __forceinline__ void mma_n64(float (&d)[32], uint32_t a0, uint32_t a1, uint32_t a2, uint32_t a3, uint64_t db, int acc) {
  asm volatile("{\n.reg .pred p;\nsetp.ne.b32 p, %37, 0;\n"
               "wgmma.mma_async.sync.aligned.m64n64k16.f32.bf16.bf16 {" R32A "}, {%32, %33, %34, %35}, %36, p, 1, 1, %38;\n}\n"
               : F8(d, 0), F8(d, 8), F8(d, 16), F8(d, 24)
               : "r"(a0), "r"(a1), "r"(a2), "r"(a3), "l"(db), "r"(acc), "n"(TB));
}
__device__ __forceinline__ void mma_n8(float (&d)[4], uint64_t da, uint64_t db, int acc) {
  asm volatile("{\n.reg .pred p;\nsetp.ne.b32 p, %6, 0;\n"
               "wgmma.mma_async.sync.aligned.m64n8k16.f32.bf16.bf16 {%0, %1, %2, %3}, %4, %5, p, 1, 1, 1, 0;\n}\n"
               : "+f"(d[0]), "+f"(d[1]), "+f"(d[2]), "+f"(d[3])
               : "l"(da), "l"(db), "r"(acc));
}
__device__ __forceinline__ void hmma_k16(float (&d)[4], uint32_t a0, uint32_t a1, uint32_t a2, uint32_t a3, uint32_t b0, uint32_t b1) {
  asm volatile("mma.sync.aligned.m16n8k16.row.col.f32.bf16.bf16.f32 {%0, %1, %2, %3}, {%4, %5, %6, %7}, {%8, %9}, {%0, %1, %2, %3};"
               : "+f"(d[0]), "+f"(d[1]), "+f"(d[2]), "+f"(d[3]) : "r"(a0), "r"(a1), "r"(a2), "r"(a3), "r"(b0), "r"(b1));
}

__device__ __forceinline__ uint32_t pack2(float lo, float hi) {
  uint32_t r;
  asm("cvt.rn.bf16x2.f32 %0, %1, %2;" : "=r"(r) : "f"(hi), "f"(lo));
  return r;
}
__device__ __forceinline__ float bf_lo(uint32_t w) { return __uint_as_float(w << 16); }
__device__ __forceinline__ float bf_hi(uint32_t w) { return __uint_as_float(w & 0xFFFF0000u); }
__device__ __forceinline__ float bfr(float x) { return __uint_as_float(pack2(0.f, x)); }
__device__ __forceinline__ uint32_t sub2(uint32_t a, uint32_t b) {
  uint32_t r;
  asm("sub.rn.bf16x2 %0, %1, %2;" : "=r"(r) : "r"(a), "r"(b));
  return r;
}
__device__ __forceinline__ uint32_t add2(uint32_t a, uint32_t b) {
  uint32_t r;
  asm("add.rn.bf16x2 %0, %1, %2;" : "=r"(r) : "r"(a), "r"(b));
  return r;
}
__device__ __forceinline__ uint32_t mul2(uint32_t a, uint32_t b) {
  uint32_t r;
  asm("mul.rn.bf16x2 %0, %1, %2;" : "=r"(r) : "r"(a), "r"(b));
  return r;
}
__device__ __forceinline__ uint32_t fma2(uint32_t a, uint32_t b, uint32_t c) {
  uint32_t r;
  asm("fma.rn.bf16x2 %0, %1, %2, %3;" : "=r"(r) : "r"(a), "r"(b), "r"(c));
  return r;
}
__device__ __forceinline__ float ex2(float x) {
  float r;
  asm("ex2.approx.ftz.f32 %0, %1;" : "=f"(r) : "f"(x));
  return r;
}
__device__ __forceinline__ float rcp(float x) {
  float r;
  asm("rcp.approx.ftz.f32 %0, %1;" : "=f"(r) : "f"(x));
  return r;
}
__device__ __forceinline__ float silu_f(float t) { return t * rcp(1.0f + ex2(-1.4426950408889634f * t)); }
__device__ __forceinline__ void lds128(uint32_t a, uint32_t& x, uint32_t& y, uint32_t& z, uint32_t& w) {
  asm volatile("ld.shared.v4.u32 {%0, %1, %2, %3}, [%4];" : "=r"(x), "=r"(y), "=r"(z), "=r"(w) : "r"(a) : "memory");
}
__device__ __forceinline__ void ldsm4(uint32_t a, uint32_t& x, uint32_t& y, uint32_t& z, uint32_t& w) {
  asm volatile("ldmatrix.sync.aligned.m8n8.x4.shared.b16 {%0, %1, %2, %3}, [%4];" : "=r"(x), "=r"(y), "=r"(z), "=r"(w) : "r"(a) : "memory");
}
constexpr uint32_t TAG_BIT = 0x10000;
__device__ __forceinline__ void st_gran(uint4* p, uint32_t x, uint32_t y, uint32_t z, uint32_t w) {
  asm volatile("st.relaxed.gpu.global.v4.b32 [%0], {%1, %2, %3, %4};" ::"l"(p), "r"(x), "r"(y), "r"(z), "r"(w) : "memory");
}
__device__ __forceinline__ void ld_gran(const uint4* p, uint32_t& x, uint32_t& y, uint32_t& z, uint32_t& w) {
  asm volatile("ld.relaxed.gpu.global.v4.b32 {%0, %1, %2, %3}, [%4];" : "=r"(x), "=r"(y), "=r"(z), "=r"(w) : "l"(p) : "memory");
}
__device__ __forceinline__ void ldsm4t(uint32_t a, uint32_t& x, uint32_t& y, uint32_t& z, uint32_t& w) {
  asm volatile("ldmatrix.sync.aligned.m8n8.x4.trans.shared.b16 {%0, %1, %2, %3}, [%4];" : "=r"(x), "=r"(y), "=r"(z), "=r"(w) : "r"(a) : "memory");
}
__device__ __forceinline__ void stsm4t(uint32_t a, uint32_t x, uint32_t y, uint32_t z, uint32_t w) {
  asm volatile("stmatrix.sync.aligned.m8n8.x4.trans.shared.b16 [%0], {%1, %2, %3, %4};" ::"r"(a), "r"(x), "r"(y), "r"(z), "r"(w) : "memory");
}
__device__ __forceinline__ void stsm4(uint32_t a, uint32_t x, uint32_t y, uint32_t z, uint32_t w) {
  asm volatile("stmatrix.sync.aligned.m8n8.x4.shared.b16 [%0], {%1, %2, %3, %4};" ::"r"(a), "r"(x), "r"(y), "r"(z), "r"(w) : "memory");
}
template <class T>
__device__ __forceinline__ T* at(const void* base, uint32_t off) {
  uint64_t r;
  asm("{\n.reg .u32 lo, hi;\nmov.b64 {lo, hi}, %1;\nadd.cc.u32 lo, lo, %2;\naddc.u32 hi, hi, 0;\nmov.b64 %0, {lo, hi};\n}"
      : "=l"(r) : "l"(base), "r"(off));
  return (T*)__cvta_global_to_generic(r);
}
__device__ __forceinline__ void add_granules(float (&red)[32], const uint32_t (&g)[16]) {
#pragma unroll
  for (int i = 0; i < 16; i++) { red[2 * i] += bf_lo(g[i]); red[2 * i + 1] += bf_hi((i & 3) ? g[i] : g[i] & ~TAG_BIT); }
}
__device__ __forceinline__ bool granules_ok(const uint32_t (&g)[16], uint32_t tag) {
  uint32_t u, v;
  asm("lop3.b32 %0, %1, %2, %3, 0x7E;" : "=r"(u) : "r"(g[0]), "r"(g[4]), "r"(tag));
  asm("lop3.b32 %0, %1, %2, %3, 0x7E;" : "=r"(v) : "r"(g[8]), "r"(g[12]), "r"(tag));
  return __all_sync(0xffffffffu, ((u | v) & TAG_BIT) == 0);
}
__device__ __forceinline__ unsigned ld_acquire(const unsigned* p) {
  unsigned v;
  asm volatile("ld.acquire.gpu.global.u32 %0, [%1];" : "=r"(v) : "l"(p) : "memory");
  return v;
}
__device__ __forceinline__ void red_release(unsigned* p) {
  asm volatile("red.release.gpu.global.add.u32 [%0], 1;" ::"l"(p) : "memory");
}
__device__ __forceinline__ void st_release(unsigned* p, unsigned v) {
  asm volatile("st.release.gpu.global.u32 [%0], %1;" ::"l"(p), "r"(v) : "memory");
}

template <int K0, int K1>
__device__ __forceinline__ void ln_fetch(uint32_t (&xa)[144], uint32_t boxes, uint32_t lo) {
#pragma unroll
  for (int k = K0; k < K1; k++) ldsm4(((boxes + lo) ^ ((k & 3) << 5)) + (k >> 2) * 8192, xa[4 * k], xa[4 * k + 1], xa[4 * k + 2], xa[4 * k + 3]);
}
template <int K0, int K1>
__device__ __forceinline__ void ln_sums(const uint32_t (&xa)[144], float (&sm)[4][4]) {
#pragma unroll
  for (int k = K0; k < K1; k++) hmma_k16(sm[k & 3], xa[4 * k], xa[4 * k + 1], xa[4 * k + 2], xa[4 * k + 3], 0x3F803F80u, 0x3F803F80u);
}
__device__ __forceinline__ uint32_t sq8(const uint32_t* a) {
  uint32_t t, u;
  asm("mul.rn.bf16x2 %0, %1, %1;" : "=r"(t) : "r"(a[0]));
  asm("mul.rn.bf16x2 %0, %1, %1;" : "=r"(u) : "r"(a[2]));
#pragma unroll
  for (int i = 4; i < 16; i += 4) {
    asm("fma.rn.bf16x2 %0, %1, %1, %0;" : "+r"(t) : "r"(a[i]));
    asm("fma.rn.bf16x2 %0, %1, %1, %0;" : "+r"(u) : "r"(a[i + 2]));
  }
  return add2(t, u);
}
__device__ __forceinline__ void ln_centre(uint32_t (&xa)[144], int j0, int j1, uint32_t mm0, uint32_t mm1, float& sq0, float& sq1) {
#pragma unroll
  for (int j = 0; j < 72; j += 8)
    if (j >= j0 && j < j1) {
#pragma unroll
      for (int k = j; k < j + 8; k++) {
        xa[2 * k] = sub2(xa[2 * k], mm0);
        xa[2 * k + 1] = sub2(xa[2 * k + 1], mm1);
      }
      const uint32_t t0 = sq8(xa + 2 * j), t1 = sq8(xa + 2 * j + 1);
      sq0 += bf_lo(t0) + bf_hi(t0);
      sq1 += bf_lo(t1) + bf_hi(t1);
    }
}
__device__ __forceinline__ float ln_rstd(float var) {
  float sd;
  asm("sqrt.approx.ftz.f32 %0, %1;" : "=f"(sd) : "f"(bfr(bfr(fmaxf(var, 0.0f)) + 1e-5f)));
  return rcp(bfr(sd));
}
__device__ __forceinline__ uint32_t silu2(uint32_t t) { return pack2(silu_f(bf_lo(t)), silu_f(bf_hi(t))); }
__device__ __forceinline__ float sum8(float v) {
#pragma unroll
  for (int d = 4; d; d >>= 1) v += __shfl_xor_sync(0xffffffffu, v, d);
  return v;
}
__device__ __forceinline__ void await_count(const unsigned* p, unsigned target, unsigned sleep_ns) {
#pragma unroll 1
  for (int n = 0; n < (1 << 18) && __any_sync(0xffffffffu, (int)(ld_acquire(p) - target) < 0); n++) __nanosleep(sleep_ns);
}
__device__ __forceinline__ void bulk_load(uint32_t dst, const void* src, uint32_t bytes, uint32_t bar) {
  asm volatile("cp.async.bulk.shared::cluster.global.mbarrier::complete_tx::bytes [%0], [%1], %2, [%3];"
               ::"r"(dst), "l"(src), "r"(bytes), "r"(bar) : "memory");
}
__device__ __forceinline__ void proxy_fence() { asm volatile("fence.proxy.async;" ::: "memory"); }

template <int V> struct IC { static constexpr int value = V; };

struct Ctx {
  uint32_t sb;
  uint8_t* sp;
  uint32_t rank;
  Scratch* gs;
};

__device__ __forceinline__ void dly(const Ctx&, int) {}
template <int BOXES>
__device__ __forceinline__ void load_stage(uint32_t dst, const CUtensorMap* tm, int c0, int c1, uint32_t bar, uint32_t bytes, uint64_t pol) {
  asm volatile("{\n.reg .pred p;\nelect.sync _|p, 0xffffffff;\n"
               "@p mbarrier.arrive.expect_tx.shared::cta.b64 _, [%4], %7;\n"
               "@p cp.async.bulk.tensor.2d.shared::cluster.global.mbarrier::complete_tx::bytes.multicast::cluster.L2::cache_hint"
               " [%0], [%1, {%2, %3}], [%4], %5, %6;\n}"
               ::"r"(dst), "l"(tm), "r"(c0), "r"(c1), "r"(bar), "h"((uint16_t)3), "l"(pol), "r"(bytes) : "memory");
  if (BOXES == 2)
    asm volatile("{\n.reg .pred p;\nelect.sync _|p, 0xffffffff;\n"
                 "@p cp.async.bulk.tensor.2d.shared::cluster.global.mbarrier::complete_tx::bytes.multicast::cluster.L2::cache_hint"
                 " [%0], [%1, {%2, %3}], [%4], %5, %6;\n}"
                 ::"r"(dst + 8192), "l"(tm), "r"(c0), "r"(c1 + 64), "r"(bar), "h"((uint16_t)3), "l"(pol) : "memory");
}
__device__ __forceinline__ void attn_producer(const Ctx& cx, int qb, int hs, const CUtensorMap* tmX, const CUtensorMap* tmK,
                                              const CUtensorMap* tmV, const CUtensorMap* tmWq, const CUtensorMap* tmWo) {
  const uint32_t full = cx.sb + SM_FULL, empty = cx.sb + SM_EMPTY, ring = cx.sb + SM_RING + cx.rank * 16384;
  const uint64_t keep = policy_evict_normal(), last_use = policy_evict_first();
  auto acquire = [&](int st) {
    mbar_wait(empty + 8 * (st & 3), ((st >> 2) ^ ((st & 3) >> 1) ^ 1) & 1);
    if (st > 3) dly(cx, st);
  };
  if (elect_one()) {
#pragma unroll
    for (int j = 0; j < 3; j++) {
      mbar_expect_tx(cx.sb + SM_XFULL + 96 + 8 * j, 24576);
      tma3d(cx.sb + SM_X + 73728 + j * 24576, tmX, qb * 128 + 64, j * 3, cx.sb + SM_XFULL + 96 + 8 * j);
    }
  }
  __syncwarp();
  const int c0 = cx.rank * 64;
#pragma unroll 1
  for (int p = 0; p < 3; p++) {
    const int n0 = (hs * 4 + ((0x120 >> (4 * p)) & 3)) * DH + c0;
#pragma unroll
    for (int i = 0; i < 5; i++) {
      const int st = (p == 2 ? 13 : 5 * p) + i, sl = st & 3;
      if (i == 4 && p == 2) break;
      acquire(st);
      if (i == 2) load_stage<1>(ring + sl * STAGE, tmWq, n0, 256, full + 8 * sl, 16384, last_use);
      else load_stage<2>(ring + sl * STAGE, tmWq, n0, i < 2 ? 128 * i : 128 * i - 64, full + 8 * sl, 32768, last_use);
      if (i == X_PFQ && p < 2 && elect_one()) {
        tma2d_prefetch(tmWq, (hs * 4 + 2 - p) * DH + (qb & 1) * 64, (qb >> 1) * 64);
        if (p == 0 && qb < 9) tma2d_prefetch(tmWq, (hs * 4 + 3) * DH, qb * 64);
      }
      __syncwarp();
    }
    if (p == 1) {
      const int n3 = (hs * 4 + 3) * DH;
      acquire(10);
      load_stage<2>(ring + 2 * STAGE, tmWq, n3, 2 * c0, full + 16, 32768, last_use);
      acquire(11);
      if (cx.rank) load_stage<1>(ring + 3 * STAGE, tmWq, n3, 384, full + 24, 24576, last_use);
      else load_stage<2>(ring + 3 * STAGE, tmWq, n3, 256, full + 24, 24576, last_use);
      acquire(12);
      load_stage<1>(ring, tmWq, n3, 448 + c0, full, 16384, last_use);
    }
  }
  int vrow = 0;
  uint64_t vpol = keep;
#pragma unroll 1
  for (int j = 0; j < 32; j++) {
    const int st = NST_Q - 1 + 4 * j, row = (hs * 2 + (j >> 4)) * SEQ + (j & 7) * 256;
    const uint64_t pol = (j & 8) ? last_use : keep;
    acquire(st);
    load_stage<1>(ring + SL_KE * STAGE, tmK, c0, row, full + 8 * SL_KE, 32768, pol);
    acquire(st + 1);
    if (j) load_stage<1>(ring + SL_VE * STAGE, tmV, c0, vrow, full + 8 * SL_VE, 32768, vpol);
    else load_stage<2>(ring + SL_VE * STAGE, tmWq, (hs * 4 + 1) * DH + c0, 448, full + 8 * SL_VE, 32768, last_use);
    vrow = row + 128;
    vpol = pol;
    acquire(st + 2);
    load_stage<1>(ring + SL_KO * STAGE, tmK, c0, vrow, full + 8 * SL_KO, 32768, pol);
    acquire(st + 3);
    load_stage<1>(ring + SL_VO * STAGE, tmV, c0, row, full + 8 * SL_VO, 32768, pol);
  }
  acquire(NST_Q + NST_KV - 1);
  load_stage<1>(ring + SL_KE * STAGE, tmV, c0, vrow, full + 8 * SL_KE, 32768, last_use);
#pragma unroll 1
  for (int u = 0; u < NST_O; u++) {
    const int st = NST_Q + NST_KV + u, sl = st & 3;
    const int blk = u < 4 && cx.rank ? 8 : ((hs + max(u >> 1, 1)) & 7);
    const int head = u < 4 ? u ^ (u >> 1) : ((u & 1) * 2 + cx.rank + 3) & 3;
    acquire(st);
    load_stage<1>(ring + sl * STAGE, tmWo, blk * 64, hs * 512 + head * 128, full + 8 * sl, 32768, last_use);
  }
}

__device__ __forceinline__ uint32_t xn_offset(uint32_t row, int lane) {
  return (row >> 6) * (9 * 8192) + (row & 63) * 128 + ((((lane >> 2) ^ row) & 7) << 4) + (lane & 3) * 4;
}

__device__ __forceinline__ void attn_rows(const Ctx& cx, int qb, int hs, int hw, int lane, const CUtensorMap* tmX16,
                                          const __nv_bfloat16* w_r) {
  extern __shared__ __align__(1024) uint8_t smem_rows[];
  auto box = [&](int blk) { return blk < 8 ? SM_SLOT + 2 * STAGE + 8192 + (blk >> 2) * 16384 + (blk & 3) * 2048 : SM_BOX8; };
  const uint32_t sb = smem_u32(smem_rows);
  if (hw == 0) {
    bar_sync(BAR_HELPER, 160);
    if (elect_one()) {
      mbar_expect_tx(sb + SM_BAR_ROWS, 9 * 2048);
#pragma unroll
      for (int i = 0; i < 9; i++) tma2d(sb + box(i), tmX16, i * 64, qb * 128 + hs * 16, sb + SM_BAR_ROWS);
    }
    __syncwarp();
  }
  uint32_t g = (lane >> 3) * 128 + (((lane ^ (lane >> 3)) & 7) << 4);
  auto next = [&]() {
    g = ((g + 512) & 2047) ^ 64;
    asm volatile("" : "+r"(g));
  };
  float* const part = (float*)(smem_rows + SM_ROWS);
  mbar_wait(sb + SM_BAR_ROWS, 0);
  if (hw == 0) dly(cx, 190);
#pragma unroll 1
  for (int i = 0; i < 4; i++) {
    float a = 0.f, b = 0.f;
#pragma unroll
    for (int j = 0; j < 3; j++) {
      const uint4 v = *(const uint4*)(smem_rows + box(hw * 3 + j) + g);
      const uint32_t w[4] = {v.x, v.y, v.z, v.w};
#pragma unroll
      for (int k = 0; k < 4; k++) {
        a += bf_lo(w[k]) + bf_hi(w[k]);
        b = fmaf(bf_lo(w[k]), bf_lo(w[k]), fmaf(bf_hi(w[k]), bf_hi(w[k]), b));
      }
    }
    a = sum8(a);
    b = sum8(b);
    float* p = part + hw * 16 + (g >> 7);
    p[0] = a;
    p[48] = b;
    next();
  }
  bar_sync(BAR_ROWS, 96);
  if (hw == 0) dly(cx, 191);
  {
    const float* p = part + (lane & 15);
    const float mean = (p[0] + p[16] + p[32]) * (1.0f / DM), rstd = ln_rstd((p[48] + p[64] + p[80]) * (1.0f / DM) - mean * mean);
    const uint32_t mm = pack2(mean, mean), rr = pack2(rstd - bfr(rstd), rstd);
#pragma unroll 1
    for (int u = hw * 12; u < hw * 12 + 12; u++) {
      const int blk = u >> 2;
      uint4* q = (uint4*)(smem_rows + box(blk) + g);
      uint4 v = *q;
      const uint32_t m = __shfl_sync(0xffffffffu, mm, g >> 7), r = __shfl_sync(0xffffffffu, rr, g >> 7);
      const uint32_t hi = __byte_perm(r, 0, 0x3232), lo = __byte_perm(r, 0, 0x1010);
      auto norm = [&](uint32_t w) {
        const uint32_t xc = sub2(w, m);
        return fma2(xc, hi, mul2(xc, lo));
      };
      v = make_uint4(norm(v.x), norm(v.y), norm(v.z), norm(v.w));
      *q = v;
      *at<uint4>(cx.gs->xn + ((qb * 2 + (hs >> 2)) * 9 + blk) * 512 + (hs & 3) * 128, g) = v;
      next();
    }
  }
  bar_sync(BAR_ROWS, 96);
  if (hw == 0) {
    dly(cx, 192);
    if (lane == 0) red_release(&cx.gs->rows[qb * 32]);
    dly(cx, 193);
  }
#pragma unroll 1
  for (int u = hw ? 13 * hw - 3 : 0; u < 13 * hw + 10; u++) {
    const int blk = u >> 2;
    const uint32_t o = (g + (u & 3) * 512) ^ ((u & 1) << 6);
    const uint4 v = *(const uint4*)(smem_rows + box(blk) + o);
    *at<uint4>(cx.gs->gate + (blk < 8 ? (qb * 8 + blk) * 144 + hs * 16 : (qb * 8 + hs) * 144 + 128) * 8, o) =
        make_uint4(silu2(v.x), silu2(v.y), silu2(v.z), silu2(v.w));
  }
  if (hw) dly(cx, 194 + hw);
  if (X_DS) __nanosleep(X_DS);
#pragma unroll 1
  for (int blk = hw * 3; blk < hw * 3 + 3; blk++) {
    const uint4 c = __ldg(at<const uint4>(w_r, blk * 128 + ((g ^ (g >> 3)) & 0x70)));
#pragma unroll 1
    for (int i = 0; i < 4; i++) {
      const uint4 v = *(const uint4*)(smem_rows + box(blk) + g);
      part[blk * 16 + (g >> 7)] =
          sum8(fmaf(bf_lo(v.x), bf_lo(c.x), fmaf(bf_hi(v.x), bf_hi(c.x), fmaf(bf_lo(v.y), bf_lo(c.y), bf_hi(v.y) * bf_hi(c.y)))) +
               fmaf(bf_lo(v.z), bf_lo(c.z), fmaf(bf_hi(v.z), bf_hi(c.z), fmaf(bf_lo(v.w), bf_lo(c.w), bf_hi(v.w) * bf_hi(c.w)))));
      next();
    }
  }
  bar_sync(BAR_ROWS, 96);
  if (hw == 0) {
    dly(cx, 194);
    float d = 0.f;
#pragma unroll
    for (int j = 0; j < 9; j++) d += part[j * 16 + (lane & 15)];
    const uint32_t row = qb * 128 + hs * 16 + (lane & 15), b = pack2(0.f, d);
    *at<uint32_t>(cx.gs->key, row * 4) = (b ^ ((int)b < 0 ? 0xFFFF0000u : 0x80000000u)) + 0xFFFF - row;
    __syncwarp();
    if (lane == 0) red_release(&cx.gs->rows[qb * 32 + 1]);
  }
}

constexpr uint32_t SM_XO = SM_SLOT, SM_GO = SM_SLOT + STAGE, SM_P8 = SM_SLOT + 2 * STAGE;
__device__ __forceinline__ void attn_helper(const Ctx& cx, int qb, int hs, int lane, const __nv_bfloat16* wo, const CUtensorMap* tmX16) {
  unsigned e = 0;
  if (lane == 0) {
    e = cx.gs->launch[blockIdx.x];
    cx.gs->launch[blockIdx.x] = e + 1;
  }
  e = __shfl_sync(0xffffffffu, e, 0);
  if (lane == 0) {
    *(uint32_t*)(cx.sp + SM_TAG) = (~e & 1) * TAG_BIT;
    mbar_arrive(cx.sb + SM_BAR_MISC);
  }
  bar_sync(BAR_HELPER, 64);
  await_count(&cx.gs->rows[qb * 32 + 1], 8 * (e + 1), 1000);
  await_count(&cx.gs->q3_flag[qb * 8 + hs], e + 1, 1000);
  proxy_fence();
  if (elect_one()) {
    mbar_expect_tx(cx.sb + SM_BAR_Q3, 16384);
#pragma unroll
    for (int i = 0; i < 2; i++) bulk_load(cx.sb + SM_SLOT + 2 * STAGE + i * 16384 + 8192, cx.gs->q3 + (qb * 16 + hs * 2 + i) * 512, 8192, cx.sb + SM_BAR_Q3);
  }
  __syncwarp();
  bar_sync(BAR_HELPER, 64);
  prefetch_l2(at<const void>(wo, (hs * 512 + qb * 32 + lane) * (DM * 2)), DM * 2);
  await_count(&cx.gs->ycnt, 4 * (e + 1), 500);
  const uint32_t mykey = __ldcg(at<const uint32_t>(cx.gs->top, (lane >> 1) * 4)), myrow = 0xFFFF - (mykey & 0xFFFF);
#pragma unroll 1
  for (uint32_t todo = __ballot_sync(0xffffffffu, lane < 16 && ((lane & 1) ? myrow >> 4 == qb * 8 + hs : myrow >> 7 == qb)); todo; todo &= todo - 1) {
    const int i = __ffs(todo) - 1, blk = (i & 1) ? 8 : hs;
    const uint32_t key = __shfl_sync(0xffffffffu, mykey, i), row = 0xFFFF - (key & 0xFFFF), o = xn_offset(row, lane);
    const uint32_t t = __ldcg(at<const uint32_t>(cx.gs->xn, o + blk * 8192));
    const float2* p = at<const float2>(cx.gs->ypart, ((i >> 1) * DM + blk * 64 + 2 * lane) * 4);
    const float2 y0 = __ldcg(p), y1 = __ldcg(p + TOPC * DM / 2), y2 = __ldcg(p + TOPC * DM), y3 = __ldcg(p + 3 * TOPC * DM / 2);
    const float rs = bfr(rcp(1.0f + ex2(-1.4426950408889634f * bf_hi(key ^ ((int)key < 0 ? 0x80000000u : 0xFFFF0000u)))));
    const uint32_t y = pack2((y0.x + y1.x) + (y2.x + y3.x), (y0.y + y1.y) + (y2.y + y3.y));
    const uint32_t u = pack2(bf_lo(y) * rs, bf_hi(y) * rs);
    *at<uint32_t>(cx.gs->gate, ((qb * 8 + hs) * 144 + ((i & 1) ? 128 + (row & 15) : row & 127)) * 128 + (o & 127)) = silu2(add2(t, u));
  }
  proxy_fence();
  bar_sync(BAR_OA, 352);
  if (elect_one()) {
    const uint32_t bar = cx.sb + SM_BAR_XG;
    mbar_expect_tx(bar, 2 * 144 * 128);
    bulk_load(cx.sb + SM_GO, cx.gs->gate + (qb * 8 + hs) * (144 * 8), 144 * 128, bar);
#pragma unroll 1
    for (int i = 0; i < 9; i++) tma2d_stream(cx.sb + SM_XO + i * 2048, tmX16, i < 8 ? hs * 64 : 512, qb * 128 + (i < 8 ? i : hs) * 16, bar);
  }
  __syncwarp();
  const uint4* src = cx.gs->part + (qb * 64 + 56 + hs) * 1024;
#pragma unroll 1
  for (int n = 0; n < (1 << 16); n++) {
    __nanosleep(n ? 400 : X_SLEEP8);
    uint32_t a, b, d, t;
    ld_gran(at<const uint4>(src, (lane & 7) * 2048 + 2032), a, b, d, t);
    if (__all_sync(0xffffffffu, ((a >> 16) ^ e) & 1)) break;
  }
  if (elect_one()) {
    mbar_expect_tx(cx.sb + SM_BAR_P8, 16384);
    bulk_load(cx.sb + SM_P8, src, 16384, cx.sb + SM_BAR_P8);
  }
  __syncwarp();
}
__device__ __forceinline__ void attn_finish8(const Ctx& cx, int qb, int hs, int hw, int lane, __nv_bfloat16* out) {
  const uint32_t tag = *(const uint32_t*)(cx.sp + SM_TAG);
  mbar_wait(cx.sb + SM_BAR_P8, 0);
  mbar_wait(cx.sb + SM_BAR_XG, 0);
#pragma unroll 1
  for (int g = 2 - hw; g < 4; g += 3) {
    float acc[8] = {0.f, 0.f, 0.f, 0.f, 0.f, 0.f, 0.f, 0.f};
    uint32_t a[4];
#pragma unroll 1
    for (uint32_t o = g * 512 + lane * 16; o < 16384; o += 2048) {
      lds128(cx.sb + SM_P8 + o, a[0], a[1], a[2], a[3]);
#pragma unroll 1
      for (int n = 0; n < (1 << 16) && __any_sync(0xffffffffu, (a[0] & TAG_BIT) != tag); n++)
        ld_gran(at<const uint4>(cx.gs->part, (qb * 64 + 56 + hs) * 16384 + o), a[0], a[1], a[2], a[3]);
      a[0] &= ~TAG_BIT;
#pragma unroll
      for (int j = 0; j < 4; j++) { acc[2 * j] += bf_lo(a[j]); acc[2 * j + 1] += bf_hi(a[j]); }
    }
    asm volatile("" : "+r"(lane));
    const uint32_t tile = cx.sb + SM_XO + (128 + (lane & 15)) * 128 + (((lane >> 4) ^ (lane & 7)) << 4);
    uint32_t b[4];
    ldsm4((tile ^ (g << 5)) + STAGE, a[0], a[1], a[2], a[3]);
    ldsm4(tile ^ (g << 5), b[0], b[1], b[2], b[3]);
    stsm4(tile ^ (g << 5), fma2(pack2(acc[0], acc[1]), a[0], b[0]), fma2(pack2(acc[2], acc[3]), a[1], b[1]),
          fma2(pack2(acc[4], acc[5]), a[2], b[2]), fma2(pack2(acc[6], acc[7]), a[3], b[3]));
  }
  bar_sync(BAR_ROWS, 96);
#pragma unroll 1
  for (int ch = threadIdx.x - 32; ch < 128; ch += 96)
    *at<uint4>(out, ((qb * 128 + hs * 16 + (ch >> 3)) * DM + 512 + (ch & 7) * 8) * 2) =
        *(const uint4*)(cx.sp + SM_XO + (128 + (ch >> 3)) * 128 + (((ch ^ (ch >> 3)) & 7) << 4));
}

constexpr float SUM_HI = 1.8446744e19f, SUM_LO = 9.0949470e-13f;

__device__ __forceinline__ void softmax_shift(float (&s)[64], float n0, float n1) {
#pragma unroll
  for (int i = 0; i < 64; i++) s[i] += (i & 2) ? n1 : n0;
}
template <int LO, int HI>
__device__ __forceinline__ void softmax_exp(float (&s)[64]) {
#pragma unroll
  for (int i = LO; i < HI; i++) s[i] = ex2(s[i]);
}
__device__ __forceinline__ void row_sums(const uint32_t (&pf)[32], float& l0, float& l1) {
  uint32_t t[16];
#pragma unroll
  for (int i = 0; i < 16; i++) t[i] = add2(pf[(i >> 1) * 4 + (i & 1)], pf[(i >> 1) * 4 + 2 + (i & 1)]);
#pragma unroll
  for (int i = 0; i < 8; i++) t[i] = add2(t[(i >> 1) * 4 + (i & 1)], t[(i >> 1) * 4 + 2 + (i & 1)]);
#pragma unroll
  for (int i = 0; i < 4; i++) t[i] = add2(t[(i >> 1) * 4 + (i & 1)], t[(i >> 1) * 4 + 2 + (i & 1)]);
  l0 += (bf_lo(t[0]) + bf_lo(t[2])) + (bf_hi(t[0]) + bf_hi(t[2]));
  l1 += (bf_lo(t[1]) + bf_lo(t[3])) + (bf_hi(t[1]) + bf_hi(t[3]));
}
__device__ __forceinline__ void row_max(const float (&s)[64], float& x0, float& x1) {
  x0 = s[0];
  x1 = s[2];
#pragma unroll
  for (int i = 0; i < 64; i += 4) { x0 = fmaxf(x0, fmaxf(s[i], s[i + 1])); x1 = fmaxf(x1, fmaxf(s[i + 2], s[i + 3])); }
  x0 = fmaxf(x0, __shfl_xor_sync(0xffffffffu, x0, 1));
  x1 = fmaxf(x1, __shfl_xor_sync(0xffffffffu, x1, 1));
  x0 = fmaxf(x0, __shfl_xor_sync(0xffffffffu, x0, 2));
  x1 = fmaxf(x1, __shfl_xor_sync(0xffffffffu, x1, 2));
}
__device__ __forceinline__ void softmax_rebase(float (&s)[64], float& n0, float& n1, float& sc0, float& sc1) {
  float x0, x1;
  row_max(s, x0, x1);
  x0 = fmaxf(x0, 1.f);
  x1 = fmaxf(x1, 1.f);
  n0 -= __log2f(x0);
  n1 -= __log2f(x1);
  sc0 = exp2f(-__log2f(x0));
  sc1 = exp2f(-__log2f(x1));
#pragma unroll
  for (int i = 0; i < 64; i++) s[i] *= (i & 2) ? sc1 : sc0;
}
__device__ __forceinline__ void softmax_redo(float (&s)[64], const uint32_t (&q)[32], const __nv_bfloat16* kblk, int lane, float& n0,
                                             float& n1, float& sc0, float& sc1, uint32_t zero) {
  const __nv_bfloat16* kp = kblk + (lane >> 2) * DH + (lane & 3) * 2;
#pragma unroll
  for (int nb = 0; nb < 16; nb++) {
    float d[4] = {0.f, 0.f, 0.f, 0.f};
#pragma unroll
    for (int k = 0; k < 8; k++) {
      hmma_k16(d, q[4 * k], q[4 * k + 1], q[4 * k + 2], q[4 * k + 3], *(const uint32_t*)(kp + nb * 8 * DH + k * 16),
               *(const uint32_t*)(kp + nb * 8 * DH + k * 16 + 8));
    }
    s[4 * nb] = d[0]; s[4 * nb + 1] = d[1]; s[4 * nb + 2] = d[2]; s[4 * nb + 3] = d[3];
    block_fence(200 + nb, zero);
  }
  float x0, x1;
  row_max(s, x0, x1);
  const float m0 = fminf(n0, -x0), m1 = fminf(n1, -x1);
  sc0 = ex2(m0 - n0);
  sc1 = ex2(m1 - n1);
  n0 = m0; n1 = m1;
  softmax_shift(s, n0, n1);
  softmax_exp<0, 64>(s);
}

__device__ __forceinline__ void attn_consumer(const Ctx& cx, int qb, int hs, int wg, int cw, int lane, const __nv_bfloat16* x,
                                              const __nv_bfloat16* kc, __nv_bfloat16* out) {
  const uint32_t full = cx.sb + SM_FULL;
  const uint32_t ring = cx.sb + SM_RING;
  uint32_t lo = ((cw & 3) * 16 + (lane & 15)) * 128 + (((lane >> 4) ^ (lane & 7)) << 4);
  const uint32_t slot = cx.sb + SM_SLOT + wg * 16384;
  auto frag = [&](int sl, int k) { return ((slot + sl * STAGE + lo) ^ ((k & 3) << 5)) + (k >> 2) * 8192; };
  auto park = [&](float (&a)[64], int sl, int k0, int k1, float f0, float f1, bool in_place = false) {
#pragma unroll
    for (int k = 0; k < 8; k++)
      if (k >= k0 && k < k1) {
        float t[8];
#pragma unroll
        for (int i = 0; i < 8; i++) {
          t[i] = a[8 * k + i] * ((i & 2) ? f1 : f0);
          if (in_place) a[8 * k + i] = t[i];
        }
        stsm4(frag(sl, k), pack2(t[0], t[1]), pack2(t[2], t[3]), pack2(t[4], t[5]), pack2(t[6], t[7]));
      }
  };
  const bool signaller = lane == 0 && (cw & 3) < 2;
  int my_turn = 1 + wg, other_turn = 2 - wg;

  uint32_t pf[32], q[32], empty_c;
  float o[64], l0, l1;
  {
    uint32_t xa[144];
    float rstd0, rstd1;
    {
      const uint32_t xb = cx.sb + SM_X + wg * 73728, xf = cx.sb + SM_XFULL + wg * 96;
      float sm[4][4] = {};
      prof(wg, 0);
      if (X_WARM) hmma_k16(sm[0], 0, 0, 0, 0, 0, 0);
      empty_c = mapa(cx.sb + SM_EMPTY, cw & 1);
      mbar_wait(xf, 0);
      if ((threadIdx.x & 127) == 0) profc(wg, 30);
      ln_fetch<0, 12>(xa, xb, lo);
      mbar_wait(xf + 8, 0);
      ln_fetch<12, 24>(xa, xb, lo);
      ln_sums<0, X_S1>(xa, sm);
      mbar_wait(xf + 16, 0);
      if ((threadIdx.x & 127) == 0) profc(wg, 1);
      ln_fetch<24, 36>(xa, xb, lo);
      ln_sums<X_S1, 36>(xa, sm);
      rstd0 = ((sm[0][0] + sm[1][0]) + (sm[2][0] + sm[3][0])) * (1.0f / DM);
      rstd1 = ((sm[0][2] + sm[1][2]) + (sm[2][2] + sm[3][2])) * (1.0f / DM);
    }
    asm volatile("" : "+f"(rstd0), "+f"(rstd1)::"memory");
    block_fence(38);
    if (wg) {
      bar_arrive(other_turn, 256);
      if (X_RS < 0) bar_arrive(BAR_HELPER, 160);
    }
    block_fence(39);
    const uint32_t mm0 = pack2(rstd0, rstd0), mm1 = pack2(rstd1, rstd1);
    rstd0 -= bf_lo(mm0);
    rstd1 -= bf_lo(mm1);
    rstd0 *= rstd0 * (-0.25f * DM);
    rstd1 *= rstd1 * (-0.25f * DM);
    auto ln_finish = [&]() {
      rstd0 += __shfl_xor_sync(0xffffffffu, rstd0, 1); rstd1 += __shfl_xor_sync(0xffffffffu, rstd1, 1);
      rstd0 += __shfl_xor_sync(0xffffffffu, rstd0, 2); rstd1 += __shfl_xor_sync(0xffffffffu, rstd1, 2);
      rstd0 = ln_rstd(rstd0 * (1.0f / DM)) * SM_SCALE_LOG2;
      rstd1 = ln_rstd(rstd1 * (1.0f / DM)) * SM_SCALE_LOG2;
    };
    ln_centre(xa, 0, X_C0, mm0, mm1, rstd0, rstd1);
    if (wg == 0) {
      bar_sync(4, 128);
      if (signaller) {
        asm volatile("mbarrier.arrive.shared::cluster.b64 _, [%0], 2;" ::"r"(empty_c + 16) : "memory");
        asm volatile("mbarrier.arrive.shared::cluster.b64 _, [%0], 2;" ::"r"(empty_c + 24) : "memory");
      }
      block_fence(37);
      pin(xa);
      ln_centre(xa, X_C0, X_CA == 1 ? X_C1 : X_C2, mm0, mm1, rstd0, rstd1);
    }
    pin(xa);
    if ((threadIdx.x & 127) == 0) profc(wg, 2);

    extern __shared__ __align__(1024) uint8_t smem_q[];
    const uint32_t ring = smem_u32(smem_q) + SM_RING;
    auto release = [&](int st) { if (signaller) mbar_arrive_cluster(empty_c + 8 * (st & 3)); };
    auto q_stage = [&](float (&acc)[64], int st, int i, int last) {
      mbar_wait(full + 8 * (st & 3), (st >> 2) & 1);
      if (i != (wg ? last : 1)) bar_sync(my_turn, 256);
      wg_fence();
      const uint64_t db = mkdesc(ring + (st & 3) * STAGE, 16384);
#pragma unroll
      for (int k = 0; k < 8; k++) {
        const int kb = (i < 3 ? 8 * i : 8 * i - 4) + k;
        if (i != 2 || k < 4) mma_n128<1>(acc, xa[4 * kb], xa[4 * kb + 1], xa[4 * kb + 2], xa[4 * kb + 3], db + k * 128, kb > 0);
      }
      wg_commit();
      if (i != (wg ? last - 1 : 0)) bar_arrive(other_turn, 256);
    };
    auto q_release = [&](int st, int i, int last) {
      if (i == 1 || i == last) {
        wg_wait<1>();
        if (i == last || !wg) release(st - 1);
      }
      if (i != last - 1 && (i || wg)) {
        wg_wait<0>();
        release(st);
      }
    };
    {
      float (&acc)[64] = o;
#pragma unroll 1
      for (int p = 0; p < 2; p++) {
#pragma unroll
        for (int i = 0; i < 5; i++) {
          q_stage(acc, 5 * p + i, i, 4);
          if (p == 0 && i <= X_FIN) {
            if (i == X_RS && wg) bar_arrive(BAR_HELPER, 160);
            if ((wg || i >= X_CA) && i < 4)
              ln_centre(xa, i == 0 ? X_C0 : i == 1 ? X_C1 : i == 2 ? X_C2 : X_C3, i == 0 ? X_C1 : i == 1 ? X_C2 : i == 2 ? X_C3 : 72, mm0, mm1, rstd0, rstd1);
            if (i == X_FIN) ln_finish();
            pin(xa);
          }
          q_release(5 * p + i, i, 4);
        }
        pin(acc);
#pragma unroll
        for (int k = 0; k < 8; k += X_QP) {
          park(acc, p, k, k + X_QP, rstd0, rstd1);
          if (k + X_QP < 8) block_fence(40 + k);
        }
      }
    }
    {
      float (&h)[32] = *(float (*)[32])&o[0];
#pragma unroll
      for (int i = 0; i < 3; i++) {
        const uint32_t sl = (10 + i) & 3;
        mbar_wait(full + 8 * sl, ((10 + i) >> 2) & 1);
        if (i == 0) bar_sync(my_turn, 256);
        wg_fence();
#pragma unroll
        for (int k = 0; k < 16 - 4 * i; k++) {
          const int kb = (i == 2 ? 28 : 16 * i) + k;
          const uint64_t db = mkdesc(ring + sl * STAGE, 16) + (i == 2 && k >= 4 ? k + 4 : k) * 128;
          mma_n64<1>(h, xa[4 * kb], xa[4 * kb + 1], xa[4 * kb + 2], xa[4 * kb + 3], db, kb > 0);
        }
        wg_commit();
        if (i == 2) bar_arrive(other_turn, 256);
        if (i) {
          wg_wait<1>();
          release(9 + i);
        }
      }
      wg_wait<0>();
      release(12);
      pin(h);
#pragma unroll
      for (int k = 0; k < 4; k++) {
        stsm4(frag(2, k), pack2(h[8 * k] * rstd0, h[8 * k + 1] * rstd0), pack2(h[8 * k + 2] * rstd1, h[8 * k + 3] * rstd1),
              pack2(h[8 * k + 4] * rstd0, h[8 * k + 5] * rstd0), pack2(h[8 * k + 6] * rstd1, h[8 * k + 7] * rstd1));
        if (k == 1) block_fence(49);
      }
    }
#pragma unroll
    for (int i = 0; i < 4; i++) {
      q_stage(o, 13 + i, i, 3);
      q_release(13 + i, i, 3);
    }
    prof(wg, 6);
#pragma unroll
    for (int i = 0; i < 32; i++) pf[i] = xa[112 + i];
    l0 = 0.25f * rcp(rstd0);
    l1 = 0.25f * rcp(rstd1);
  }

  uint32_t oa[96];
  const uint32_t zero = __shfl_sync(0xffffffffu, blockIdx.y, lane);
  my_turn = __shfl_sync(0xffffffffu, my_turn, lane);
  other_turn = __shfl_sync(0xffffffffu, other_turn, lane);
  lo = __shfl_sync(0xffffffffu, lo, lane);
  {
    float s[64], n0 = 0.f, n1 = 0.f;
    float lp0, lp1;
    float i0 = 0.f, i1 = 0.f;
    bool redo, shift = false;
    auto turn = [&](int it, auto kc_) -> bool {
      constexpr int KIND = decltype(kc_)::value;
      constexpr uint32_t slk = KIND == 1 ? SL_KO : SL_KE, slv = KIND == 1 ? SL_VO : SL_VE, slkn = KIND == 1 ? SL_KE : SL_KO;
      constexpr int SPLIT = X_SPLIT, PARK1 = X_PARK;
      const uint32_t par = ((it + NST_Q / 2) >> 1) & 1;
      const int hsl = max((it >> 4) - 1, 0);
      const uint64_t dk = mkdesc(ring + slk * STAGE, 16), dv = mkdesc(ring + slv * STAGE, 16384);
      auto qk = [&]() {
#pragma unroll
        for (int k = 0; k < 8; k++) {
          if (KIND == 3) mma_n128_ss<0>(s, mkdesc(slot + hsl * STAGE, 16) + (k >> 2) * 512 + (k & 3) * 2, dk + (k >> 2) * 1024 + (k & 3) * 2, k > 0);
          else mma_n128<0>(s, q[4 * k], q[4 * k + 1], q[4 * k + 2], q[4 * k + 3], dk + (k >> 2) * 1024 + (k & 3) * 2, k > 0);
        }
        wg_commit();
      };
      auto pv = [&]() {
#pragma unroll
        for (int k = 0; k < 8; k++)
          mma_n128<1>(o, pf[4 * k], pf[4 * k + 1], pf[4 * k + 2], pf[4 * k + 3], dv + k * 128, k > 0 || KIND != 1 || (it & 15) != 1);
        wg_commit();
      };
      lp0 = l0; lp1 = l1;
#define TS(i)
      {
        TS(0)
        if (KIND == 3) {
          asm volatile("fence.proxy.async.shared::cta;" ::: "memory");
          if (it == 48) mbar_wait(cx.sb + SM_BAR_Q3, 0);
          const float t0 = lp0 + __shfl_xor_sync(0xffffffffu, lp0, 1), t1 = lp1 + __shfl_xor_sync(0xffffffffu, lp1, 1);
          i0 = rcp(t0 + __shfl_xor_sync(0xffffffffu, t0, 2));
          i1 = rcp(t1 + __shfl_xor_sync(0xffffffffu, t1, 2));
          asm volatile("" : "+f"(i0), "+f"(i1)::"memory");
          block_fence(31, zero);
#pragma unroll
          for (int k = 0; k < X_N1; k++) ldsm4(frag(hsl, k), q[4 * k], q[4 * k + 1], q[4 * k + 2], q[4 * k + 3]);
        }
        bar_sync(my_turn, 256);
        TS(1)
        if (KIND != 3) pin(q);
        pin(pf); pin(o);
        wg_fence();
        qk();
        TS(2)
        mbar_wait(full + 8 * slv, par);
        if (KIND == 1 && (it & 15) == 1) {
          park(o, hsl, PARK1, 8, i0, i1);
          wg_fence();
        }
        if (KIND == 3) {
#pragma unroll
          for (int k = X_N1; k < 8; k++) ldsm4(frag(hsl, k), q[4 * k], q[4 * k + 1], q[4 * k + 2], q[4 * k + 3]);
          block_fence(32, zero);
        }
        TS(3)
        pv();
        bar_arrive(other_turn, 256);
        TS(4)
        wg_wait<1>();
      }
      pin(s);
      mbar_arrive_cluster_now<10 * KIND + 3>(empty_c + 8 * slk, signaller, zero);
      TS(5)
      if (KIND == 3) {
        shift = false;
        n0 = n1 = l0 = l1 = 0.f;
      } else if (shift) {
        softmax_shift(s, n0, n1);
        pin(s);
      }
      softmax_exp<0, SPLIT>(s);
      pin(s);
      block_fence(10 * KIND + 4, zero);
      TS(6)
      wg_wait<0>();
      pin(o); pin(pf);
      mbar_arrive_cluster_now<10 * KIND + 5>(empty_c + 8 * slv, signaller, zero);
      TS(7)
      const bool kready = mbar_test(full + 8 * slkn, par);
      softmax_exp<SPLIT, 64>(s);
#pragma unroll
      for (int i = 0; i < 32; i++) pf[i] = pack2(s[2 * i], s[2 * i + 1]);
      row_sums(pf, l0, l1);
      if (KIND == 3) {
        park(o, hsl, 0, PARK1, i0, i1, X_IP);
        if (it) prof(wg, 6 + (it >> 4));
        if (it >= 32 && cw == 0) bar_arrive(BAR_HELPER, 64);
      }
      redo = !(l0 + l1 <= SUM_HI) || (KIND == 3 && fminf(l0, l1) < SUM_LO);
      const bool leave = __any_sync(0xffffffffu, redo || !kready);
      return leave;
    };
    int it = -1;
#pragma unroll 1
    while (true) {
      mbar_wait(full + 8 * ((it & 1) ? SL_KE : SL_KO), ((it + NST_Q / 2) >> 1) & 1);
      it++;
#pragma unroll 1
      while (true) {
        if (it & 1) {
          if (turn(it, IC<1>()) || it == 63) break;
          it++;
        }
        if (it & 15) {
          if (turn(it, IC<2>())) break;
        } else {
          if (turn(it, IC<3>())) break;
        }
        it++;
      }
      if (__any_sync(0xffffffffu, redo)) {
        const int j = it & 15;
        float sc0, sc1;
        if (__all_sync(0xffffffffu, l0 + l1 < 3.0e38f && (j || fminf(l0, l1) >= SUM_LO))) {
          softmax_rebase(s, n0, n1, sc0, sc1);
        } else {
          if (j == 0) n0 = n1 = 3.0e38f;
          softmax_redo(s, q, kc + (size_t)((hs * 2 + (it >> 5)) * SEQ + j * 128) * DH, lane, n0, n1, sc0, sc1, zero);
        }
        l0 = j ? lp0 * sc0 : 0.f;
        l1 = j ? lp1 * sc1 : 0.f;
        shift = true;
        if (j == 0) sc0 = sc1 = 1.f;
#pragma unroll
        for (int i = 0; i < 16; i++) { o[4 * i] *= sc0; o[4 * i + 1] *= sc0; o[4 * i + 2] *= sc1; o[4 * i + 3] *= sc1; }
#pragma unroll
        for (int i = 0; i < 32; i++) pf[i] = pack2(s[2 * i], s[2 * i + 1]);
        row_sums(pf, l0, l1);
      }
      if (it == 63) break;
    }
  }

#define TE(i) {}
  {
    constexpr int ST0 = NST_Q + NST_KV;
    float acc[32], red[32], first[32];
    auto await = [&](int st) { mbar_wait(full + 8 * (st & 3), (st >> 2) & 1); };
    auto release = [&](int st) { if (signaller) mbar_arrive_cluster(empty_c + 8 * (st & 3)); };
    auto unpark = [&](int h, int k0, int k1) {
#pragma unroll
      for (int k = 0; k < 8; k++)
        if (k >= k0 && k < k1) ldsm4(frag(h, k), oa[32 * h + 4 * k], oa[32 * h + 4 * k + 1], oa[32 * h + 4 * k + 2], oa[32 * h + 4 * k + 3]);
    };
    {
      float ar[64];
      asm volatile("fence.proxy.async.shared::cta;" ::: "memory");
      l0 += __shfl_xor_sync(0xffffffffu, l0, 1); l1 += __shfl_xor_sync(0xffffffffu, l1, 1);
      l0 += __shfl_xor_sync(0xffffffffu, l0, 2); l1 += __shfl_xor_sync(0xffffffffu, l1, 2);
      float f0 = rcp(l0), f1 = rcp(l1);
      asm volatile("" : "+f"(f0), "+f"(f1)::"memory");
      await(ST0 - 1);
      unpark(1, 0, 4);
      bar_sync(my_turn, 256);
      pin(pf); pin(o);
      wg_fence();
#pragma unroll
      for (int k = 0; k < 8; k++)
        mma_n128<1>(o, pf[4 * k], pf[4 * k + 1], pf[4 * k + 2], pf[4 * k + 3], mkdesc(ring + SL_KE * STAGE, 16384) + k * 128, 1);
      wg_commit();
      await(ST0);
      unpark(1, 4, 8);
      block_fence(61, zero);
#pragma unroll
      for (int k = 0; k < 8; k++) mma_n128_ss<1>(ar, mkdesc(slot, 16) + (k >> 2) * 512 + (k & 3) * 2, mkdesc(ring + (ST0 & 3) * STAGE, 16384) + k * 128, k > 0);
      wg_commit();
      bar_arrive(other_turn, 256);
      wg_wait<1>();
      pin(o); pin(pf);
      mbar_arrive_cluster_now<62>(empty_c + 8 * SL_KE, signaller, zero);
#pragma unroll
      for (int i = 0; i < 16; i++) {
        pf[2 * i] = pack2(o[4 * i] * f0, o[4 * i + 1] * f0);
        pf[2 * i + 1] = pack2(o[4 * i + 2] * f1, o[4 * i + 3] * f1);
      }
      pin(pf);
      prof(wg, 10);
#pragma unroll
      for (int u = 1; u < 4; u++) {
        await(ST0 + u);
        wg_wait<0>();
        release(ST0 + u - 1);
        bar_sync(my_turn, 256);
        wg_fence();
#pragma unroll
        for (int k = 0; k < 8; k++) {
          const uint32_t* a = (u == 1 ? oa + 32 : u == 2 ? pf : oa + 64) + 4 * k;
          mma_n128<1>(ar, a[0], a[1], a[2], a[3], mkdesc(ring + ((ST0 + u) & 3) * STAGE, 16384) + k * 128, 1);
        }
        wg_commit();
        bar_arrive(other_turn, 256);
        if (u < 3) {
          block_fence(62 + u, zero);
          unpark(u == 1 ? 2 : 0, 0, 8);
        }
      }
      mbar_wait(cx.sb + SM_BAR_MISC, 0);
      await(ST0 + 4);
      wg_wait<0>();
      release(ST0 + 3);
      pin(ar);
#pragma unroll
      for (int i = 0; i < 32; i++) { first[i] = ar[i]; red[i] = ar[32 + i]; }
    }
    const uint32_t tag = *(const uint32_t*)(cx.sp + SM_TAG);
    uint4* const xch = at<uint4>(cx.gs->part, (qb << 20) + lane * 16);
    auto send = [&](const float (&v)[32], int dst, int idx) {
      uint4* p = at<uint4>(xch, (dst * 8 + idx) * 2048);
#pragma unroll
      for (int i = 0; i < 4; i++)
        st_gran(p + i * 32, (pack2(v[8 * i], v[8 * i + 1]) & ~TAG_BIT) | tag, pack2(v[8 * i + 2], v[8 * i + 3]),
                pack2(v[8 * i + 4], v[8 * i + 5]), pack2(v[8 * i + 6], v[8 * i + 7]));
    };
    send(first, ((hs + 1) & 7) * 7, cw);
    int nrx = 1;
    auto half_step = [&](int s, auto hc, bool arrive) {
      constexpr int h = decltype(hc)::value;
      const int st = ST0 + 2 * s + h;
      const uint64_t db = mkdesc(ring + (st & 3) * STAGE, 16);
      bar_sync(my_turn, 256);
      if (h == 0) pin(pf);
#pragma unroll
      for (int i = 32 * h; i < 32 + 64 * h; i++) asm volatile("" : "+r"(oa[i])::"memory");
      wg_fence();
#pragma unroll
      for (int k = 0; k < 16; k++) {
        const int kb = h * 16 + k - 8;
        if (kb >= 0) mma_n64<1>(acc, oa[4 * kb], oa[4 * kb + 1], oa[4 * kb + 2], oa[4 * kb + 3], db + k * 128, 1);
        else mma_n64<1>(acc, pf[4 * k], pf[4 * k + 1], pf[4 * k + 2], pf[4 * k + 3], db + k * 128, k > 0);
      }
      wg_commit();
      if (arrive) bar_arrive(other_turn, 256);
    };
    auto source = [&](int n) { return at<const uint4>(xch, ((hs * 7 + n - 1) * 8 + cw) * 2048); };
    auto fetch = [&](uint32_t (&g)[16], const uint4* p) {
#pragma unroll
      for (int i = 0; i < 4; i++) ld_gran(p + i * 32, g[4 * i], g[4 * i + 1], g[4 * i + 2], g[4 * i + 3]);
    };
    uint32_t g[16];
#pragma unroll 1
    for (int s = 2; s < 8; s++) {
      const int st = ST0 + 2 * s;
      half_step(s, IC<0>(), true);
      if (s == 2) {
        bar_arrive(BAR_OA, 352);
        send(red, 56 + cw, hs);
#pragma unroll
        for (int i = 0; i < 32; i++) red[i] = 0.f;
      }
      await(st + 1);
      if (s > 3 && granules_ok(g, tag)) { add_granules(red, g); nrx++; }
      if (X_XS == 1 && s > 2) fetch(g, source(nrx));
      wg_wait<0>();
      if (s < 7) release(st);
      if (X_XS == 0 && s > 2) fetch(g, source(nrx));
      half_step(s, IC<1>(), true);
      await(st + 2);
      wg_wait<0>();
      if (s < 7) release(st + 1);
      pin(acc);
      if (s == 7) prof(wg, 19);
      if (s == 7) TE(0)
      send(acc, ((hs + s) & 7) * 7 + s - 1, cw);
    }
    TE(1)
    uint32_t xv[16], gt[16];
    {
      const int s = 8;
      uint32_t g2[16];
      half_step(s, IC<0>(), true);
      TE(2)
      await(NST_Q + NST_KV + NST_O - 1);
      cluster_arrive();
      mbar_wait(cx.sb + SM_BAR_XG, 0);
      const uint32_t tile = cx.sb + SM_XO + wg * 8192 + lo;
      if (granules_ok(g, tag)) { add_granules(red, g); nrx++; }
      fetch(g, source(nrx));
      block_fence(58, zero);
      wg_wait<0>();
      TE(3)
#pragma unroll
      for (int k = 0; k < 4; k++) ldsm4((tile ^ (k << 5)) + STAGE, gt[4 * k], gt[4 * k + 1], gt[4 * k + 2], gt[4 * k + 3]);
      half_step(s, IC<1>(), wg == 0);
      TE(4)
      block_fence(56, zero);
      const bool ok = granules_ok(g, tag);
      block_fence(57, zero + ok * 1000);
      const uint4* src = source(7);
      fetch(g2, src);
#pragma unroll
      for (int k = 0; k < 4; k++) ldsm4(tile ^ (k << 5), xv[4 * k], xv[4 * k + 1], xv[4 * k + 2], xv[4 * k + 3]);
      if (ok) { add_granules(red, g); nrx++; }
      TE(5)
      block_fence(59, zero);
      wg_wait<0>();
      pin(acc);
      TE(6)
#pragma unroll
      for (int i = 0; i < 32; i++) red[i] += acc[i];
      pin(red);
      TE(7)
      int n = 7;
#pragma unroll 1
      for (int spins = 0; spins < (1 << 16); spins++) {
        if (granules_ok(g2, tag)) {
          add_granules(red, g2);
          if (--n < nrx) {
            break;
          }
          src -= 1024;
        }
        fetch(g2, src);
      }
      TE(8)
    }
    prof(wg, 20);
    TE(9)
    const uint32_t ot = ring + ((ST0 + NST_O) & 3) * STAGE + cw * (16 * 144);
    uint32_t ow[16];
#pragma unroll
    for (int i = 0; i < 16; i++) ow[i] = fma2(pack2(red[2 * i], red[2 * i + 1]), gt[i], xv[i]);
#pragma unroll
    for (int i = 0; i < 4; i++)
      stsm4(ot + (lane & 15) * 144 + (2 * i + (lane >> 4)) * 16, ow[4 * i], ow[4 * i + 1], ow[4 * i + 2], ow[4 * i + 3]);
    __syncwarp();
#pragma unroll
    for (int i = 0; i < 4; i++) {
      uint4 v;
      lds128(ot + (i * 4 + (lane >> 3)) * 144 + (lane & 7) * 16, v.x, v.y, v.z, v.w);
      at<uint4>(out, ((qb * 128 + cw * 16 + (lane >> 3)) * DM + hs * 64 + (lane & 7) * 8) * 2)[i * (4 * DM / 8)] = v;
    }
    TE(10)
    prof(wg, 22);
  }
}

constexpr int AST_X = 6, AST_F = AST_X + 96;
__device__ __forceinline__ void aux_producer(const Ctx& cx, int f, const CUtensorMap* tmWq, const CUtensorMap* tmG) {
  const uint32_t full = cx.sb + SM_FULL, empty = cx.sb + SM_EMPTY;
  if (elect_one()) {
#pragma unroll 1
    for (int st = 0; st < AST_X; st++) {
      mbar_expect_tx(full + 8 * st, FSTAGE);
#pragma unroll
      for (int i = 0; i < 3; i++)
        tma2d_stream(cx.sb + st * FSTAGE + i * 8192, tmWq, (2 * f + (st & 1)) * 512 + 448, (st >> 1) * 192 + i * 64, full + 8 * st);
    }
  }
  __syncwarp();
  mbar_wait(cx.sb + SM_BAR_MISC, 0);
  proxy_fence();
  int st = AST_X;
#pragma unroll 1
  for (; st < AST_F; st++) {
    const uint32_t sl = st & 7;
    mbar_wait(empty + 8 * sl, ((st >> 3) & 1) ^ 1);
    if (elect_one()) {
      mbar_expect_tx(full + 8 * sl, FSTAGE);
      bulk_load(cx.sb + sl * FSTAGE, cx.gs->xn + (st - AST_X) * (FSTAGE / 16), FSTAGE, full + 8 * sl);
    }
    __syncwarp();
  }
#pragma unroll 1
  for (int pair = 0; pair < 14; pair++) {
#pragma unroll 1
    for (int u = 0; u < 12; u++, st++) {
      const uint32_t sl = st & 7;
      const int unit = pair * 2 + (u & 1), k = u >> 1;
      if (unit == 27) continue;
      const bool gu = pair < 9;
      mbar_wait(empty + 8 * sl, ((st >> 3) & 1) ^ 1);
      if (elect_one()) {
        mbar_expect_tx(full + 8 * sl, FSTAGE);
        tma2d_stream(cx.sb + sl * FSTAGE, tmG + (gu ? k >= 3 : 2), gu ? f * 1152 + unit * 64 : (unit - 18) * 64,
                     gu ? (k >= 3 ? k - 3 : k) * 192 : f * 1152 + k * 192, full + 8 * sl);
      }
      __syncwarp();
    }
  }
}

constexpr int BAR_FREE = 4, BAR_TILE = 6;
__device__ __forceinline__ void aux_helper(const Ctx& cx, int f, int warp, int lane) {
  unsigned epoch = 0;
  if (lane == 0) epoch = cx.gs->launch[blockIdx.x] + 1;
  epoch = __shfl_sync(0xffffffffu, epoch, 0);
  bar_sync(BAR_OA, 96);
  if (warp == 3) {
    if (lane == 0) cx.gs->launch[blockIdx.x] = epoch;
    await_count(at<const unsigned>(cx.gs->rows, (lane & 15) * 128), 8 * epoch, 200);
    if (lane == 0) mbar_arrive(cx.sb + SM_BAR_MISC);
    prof(0, 1, 31);
    await_count(at<const unsigned>(cx.gs->rows, (lane & 15) * 128 + 4), 8 * epoch, 500);
    uint32_t bound = 0xFFFFFFFFu, m0 = 0, m1 = 0;
#pragma unroll 1
    for (int k = 0; k < TOPC; k++) {
      if (__any_sync(0xffffffffu, m0 == 0)) {
        m0 = m1 = 0;
#pragma unroll 2
        for (int i = 0; i < 16; i++) {
          const uint4 v = __ldcg(at<const uint4>(cx.gs->key, lane * 16 + i * 512));
          const uint32_t w[4] = {v.x, v.y, v.z, v.w};
#pragma unroll
          for (int j = 0; j < 4; j++) {
            const uint32_t t = w[j] <= bound ? w[j] : 0;
            m1 = max(m1, min(m0, t));
            m0 = max(m0, t);
          }
        }
      }
      uint32_t m = m0;
      m = __reduce_max_sync(0xffffffffu, m);
      bound = m - 1;
      if (m0 == m) { m0 = m1; m1 = 0; }
      if (f == 0 && lane == 0) *at<uint32_t>(cx.gs->top, k * 4) = m;
#pragma unroll
      for (int j = 0; j < 3; j++) {
        const uint32_t row = 0xFFFF - (m & 0xFFFF), i = min(j * 4 + (lane >> 3), 8);
        *(uint4*)(cx.sp + SM_XSEL + i * 1024 + k * 128 + (((lane ^ k) & 7) << 4)) =
            __ldcg(at<const uint4>(cx.gs->xn, xn_offset(row, (lane & 7) * 4) + i * 8192));
      }
    }
    asm volatile("fence.proxy.async.shared::cta;" ::: "memory");
    prof(0, 2, 31);
  } else {
    const int wg = warp - 1;
#pragma unroll 1
    for (int u = 0; u < 32; u++) {
      bar_arrive(BAR_FREE + wg, 160);
      bar_sync(BAR_TILE + wg, 160);
      if (elect_one()) {
        const int n = (u >> 1) * 8 + 2 * f + wg;
        asm volatile("cp.async.bulk.global.shared::cta.bulk_group [%0], [%1], 8192;\ncp.async.bulk.commit_group;\ncp.async.bulk.wait_group 0;"
                     ::"l"(cx.gs->q3 + (n * 2 + (u & 1)) * 512), "r"(cx.sb + SM_H + wg * 8192) : "memory");
        if (u & 1) st_release(&cx.gs->q3_flag[n], epoch);
      }
      __syncwarp();
    }
  }
  bar_arrive(3, 352);
}

__device__ __forceinline__ void aux_consumer(const Ctx& cx, int f, int wg, int cw, int lane) {
  const int r = lane >> 2, c = lane & 3, tid = cw * 32 + lane;
  const uint32_t full = cx.sb + SM_FULL, empty = cx.sb + SM_EMPTY;
  const bool signaller = (tid & 127) == 0;
  auto await = [&](int st) { mbar_wait(full + 8 * (st & 7), (st >> 3) & 1); };
  auto release = [&](int st, int cnt) {
    asm volatile("{\n.reg .pred p;\nsetp.ne.u32 p, %2, 0;\n@p mbarrier.arrive.shared::cta.b64 _, [%0], %1;\n}"
                 ::"r"(empty + 8 * (st & 7)), "r"(cnt), "r"((uint32_t)signaller) : "memory");
  };
  prof(wg, 0);
  {
    const uint32_t lt = ((lane & 7) + (lane >> 4) * 8) * 128 + ((((cw & 3) * 2 + ((lane >> 3) & 1)) ^ (lane & 7)) << 4);
    uint32_t wa[144];
#pragma unroll
    for (int i = 0; i < 3; i++) {
      await(2 * i + wg);
#pragma unroll
      for (int k = 0; k < 12; k++) {
        const int kb = 12 * i + k;
        ldsm4t(cx.sb + (2 * i + wg) * FSTAGE + k * 2048 + lt, wa[4 * kb], wa[4 * kb + 1], wa[4 * kb + 2], wa[4 * kb + 3]);
      }
    }
    bar_sync(1, 256);
#pragma unroll
    for (int i = 0; i < 3; i++) release(2 * i + wg, 2);
    if (wg) bar_arrive(1, 256);
#pragma unroll 1
    for (int st = AST_X; st < AST_F; st += 3) {
      float acc[32];
      await(st);
      await(st + 1);
      await(st + 2);
      bar_sync(1 + wg, 256);
      wg_fence();
#pragma unroll
      for (int kb = 0; kb < 36; kb++) {
        const int i = kb / 12, k = kb % 12;
        mma_n64<0>(acc, wa[4 * kb], wa[4 * kb + 1], wa[4 * kb + 2], wa[4 * kb + 3],
                   mkdesc(cx.sb + ((st + i) & 7) * FSTAGE, 16) + (k >> 2) * 512 + (k & 3) * 2, kb > 0);
        if (k == 11) wg_commit();
      }
      if (st < AST_F - 3 || !wg) bar_arrive(2 - wg, 256);
      wg_wait<1>();
      release(st, 1);
      release(st + 1, 1);
      bar_sync(BAR_FREE + wg, 160);
      wg_wait<0>();
      pin(acc);
      release(st + 2, 1);
#pragma unroll
      for (int k = 0; k < 4; k++)
        stsm4t(cx.sb + SM_H + wg * 8192 + k * 2048 + lt, pack2(acc[8 * k] * SM_SCALE_LOG2, acc[8 * k + 1] * SM_SCALE_LOG2),
               pack2(acc[8 * k + 2] * SM_SCALE_LOG2, acc[8 * k + 3] * SM_SCALE_LOG2),
               pack2(acc[8 * k + 4] * SM_SCALE_LOG2, acc[8 * k + 5] * SM_SCALE_LOG2),
               pack2(acc[8 * k + 6] * SM_SCALE_LOG2, acc[8 * k + 7] * SM_SCALE_LOG2));
      asm volatile("fence.proxy.async.shared::cta;" ::: "memory");
      bar_arrive(BAR_TILE + wg, 160);
    }
    bar_sync(3, 352);
  }
  prof(wg, 3);
#pragma unroll 1
  for (int unit = wg; unit < 27; unit += 2) {
    if (unit >> 1 == 9) {
      asm volatile("fence.proxy.async.shared::cta;" ::: "memory");
      bar_sync(3, 256);
      prof(wg, 4);
    }
    const bool gu = unit < 18;
    float a0[4], a1[4];
#pragma unroll 1
    for (int m = 0; m < 2; m++) {
      float p0[4], p1[4];
      int st = AST_F + (unit >> 1) * 12 + m * 6 + wg;
      uint32_t b = cx.sb + (gu ? SM_XSEL : SM_H + m * 9216);
#pragma unroll 1
      for (int u = 0; u < 3; u++, st += 2, b += 3072) {
        await(st);
        wg_fence();
        const uint64_t da = mkdesc(cx.sb + (st & 7) * FSTAGE, 16), db = mkdesc(b, 16);
#pragma unroll
        for (int k = 0; k < 12; k++) mma_n8((k & 1) ? p1 : p0, da + k * 128, db + (k >> 2) * 64 + (k & 3) * 2, u > 0 || k > 1);
        wg_commit();
        wg_wait<1>();
        if (u) release(st - 2, 2);
      }
      wg_wait<0>();
      release(st - 2, 2);
      pin(p0); pin(p1);
#pragma unroll
      for (int i = 0; i < 4; i++) { a0[i] = a1[i]; a1[i] = p0[i] + p1[i]; }
    }
#pragma unroll
    for (int i = 0; i < 4; i++) {
      const int fl = (cw & 3) * 16 + r + (i >> 1) * 8, tok = 2 * c + (i & 1);
      if (gu) {
        const float h = bfr(silu_f(bfr(a0[i]))) * bfr(a1[i]);
        *(__nv_bfloat16*)(cx.sp + SM_H + unit * 1024 + tok * 128 + (((fl >> 3) ^ tok) << 4) + (fl & 7) * 2) = __float2bfloat16_rn(h);
      } else {
        *at<float>(cx.gs->ypart, ((f * TOPC + tok) * DM + (unit - 18) * 64 + fl) * 4) = a0[i] + a1[i];
      }
    }
  }
  prof(wg, 5);
  bar_sync(3, 256);
  if (tid == 0) red_release(&cx.gs->ycnt);
  prof(wg, 6);
}

struct Maps { CUtensorMap m[9]; };
__global__ void __cluster_dims__(2, 1, 1) __launch_bounds__(THREADS, 1)
fused_kernel(const __nv_bfloat16* __restrict__ x, const __nv_bfloat16* __restrict__ w_r, const __nv_bfloat16* __restrict__ wq,
             const __nv_bfloat16* __restrict__ wo, __nv_bfloat16* __restrict__ out, Scratch* gs,
             const __grid_constant__ Maps maps, const __nv_bfloat16* __restrict__ kc) {
  const CUtensorMap &tmX = maps.m[0], &tmWq = maps.m[1], &tmK = maps.m[2], &tmV = maps.m[3], &tmWo = maps.m[4];
  extern __shared__ __align__(1024) uint8_t smem_raw[];
  prof(0, 23, 511);
  Ctx cx;
  cx.sb = smem_u32(smem_raw);
  cx.sp = smem_raw;
  cx.gs = gs;
  cx.rank = blockIdx.x & 1;
  const int warp = __shfl_sync(0xffffffffu, threadIdx.x >> 5, 0);
  const int cluster = blockIdx.x >> 1;
  const bool is_ffn = blockIdx.x >= N_ATT_CTA;
  const int c7 = ((cluster - 36) * 37) >> 8;
  const int hs = cluster < 4 ? 4 + cluster : cluster < 36 ? (cluster - 4) >> 3 : 4 + c7;
  const int qb = (cluster < 4 ? 0 : cluster < 36 ? (cluster - 4) & 7 : cluster - 35 - 7 * c7) * 2 + cx.rank;

  extern __shared__ __align__(1024) uint8_t smem_alias[];
  const uint32_t xf = smem_u32(smem_alias) + SM_MISC + warp * 24;
  if (warp == 4 && elect_one()) prefetch_tmap(&tmX);
  if (warp == 6 && !is_ffn && elect_one()) prefetch_l2(x + (size_t)(qb * 128 + hs * 8) * DM, 8 * DM * 2);
  if (elect_one()) {
    const uint32_t cnt = (warp > 4 && warp < 8) ? (is_ffn ? 2 : 4) : 1;
#pragma unroll
    for (int i = 0; i < 3; i++) mbar_init(xf + 8 * i, cnt);
    asm volatile("fence.proxy.async.shared::cta;" ::: "memory");
    asm volatile("fence.mbarrier_init.release.cluster;" ::: "memory");
  }
  __syncwarp();
  cluster_arrive();
  if (warp == 4 && !is_ffn) {
    if (elect_one()) {
      profc(0, 28);
#pragma unroll
      for (int i = 0; i < 3; i++) {
        mbar_expect_tx(xf + 8 * i, 24576);
        tma3d(xf - SM_XFULL + SM_X + i * 24576, &tmX, qb * 128, i * 3, xf + 8 * i);
      }
      profc(0, 29);
    }
  } else if (warp > 7 && elect_one()) {
    prefetch_tmap(&tmX + (is_ffn ? warp - 4 : warp == 8 ? 8 : warp - 8));
  }
  __syncwarp();

  if (warp < 4) {
    asm volatile("setmaxnreg.dec.sync.aligned.u32 24;");
    cluster_wait();
    prof(0, 24, 511);
    if (warp == 0) {
      if (!is_ffn) attn_producer(cx, qb, hs, &tmX, &tmK, &tmV, &tmWq, &tmWo);
      else aux_producer(cx, blockIdx.x - N_ATT_CTA, &tmWq, &maps.m[5]);
      prof(0, 25, 511);
    } else if (!is_ffn) {
      attn_rows(cx, qb, hs, 3 - warp, read_lane(), &maps.m[8], w_r);
      if (warp == 1) attn_helper(cx, qb, hs, read_lane(), wo, &maps.m[8]);
      else bar_sync(BAR_OA, 352);
      attn_finish8(cx, qb, hs, warp - 1, read_lane(), out);
    } else {
      aux_helper(cx, blockIdx.x - N_ATT_CTA, warp, read_lane());
    }
    __syncwarp();
    cluster_arrive();
    cluster_wait();
    if (threadIdx.x == 32) { dly(cx, 201); dly(cx, 251); }
  } else {
    asm volatile("setmaxnreg.inc.sync.aligned.u32 240;");
    cluster_wait();
    const int cw = warp - 4, wg = cw >> 2;
    if (is_ffn) aux_consumer(cx, blockIdx.x - N_ATT_CTA, wg, cw, read_lane());
    else attn_consumer(cx, qb, hs, wg, cw, read_lane(), x, kc, out);
  }
}

typedef CUresult (*EncodeFn)(CUtensorMap*, CUtensorMapDataType, cuuint32_t, void*, const cuuint64_t*, const cuuint64_t*,
                             const cuuint32_t*, const cuuint32_t*, CUtensorMapInterleave, CUtensorMapSwizzle,
                             CUtensorMapL2promotion, CUtensorMapFloatOOBfill);

void encode(EncodeFn fn, CUtensorMap* m, const void* p, int rank, const cuuint64_t* dims, const cuuint64_t* strides,
            const cuuint32_t* box) {
  const cuuint32_t es[5] = {1, 1, 1, 1, 1};
  fn(m, CU_TENSOR_MAP_DATA_TYPE_BFLOAT16, rank, const_cast<void*>(p), dims, strides, box, es, CU_TENSOR_MAP_INTERLEAVE_NONE,
     CU_TENSOR_MAP_SWIZZLE_128B, CU_TENSOR_MAP_L2_PROMOTION_L2_128B, CU_TENSOR_MAP_FLOAT_OOB_FILL_NONE);
}
void encode2d(EncodeFn fn, CUtensorMap* m, const void* p, uint64_t rows, uint64_t cols, uint32_t box_rows) {
  const cuuint64_t dims[2] = {cols, rows}, strides[1] = {cols * 2};
  const cuuint32_t box[2] = {64, box_rows};
  encode(fn, m, p, 2, dims, strides, box);
}

}

extern "C" void kernel_launch(void* const* d_in, const int* in_sizes, int n_in, void* d_out, int out_size) {
  (void)in_sizes; (void)n_in; (void)out_size;
  void* fnp = nullptr;
  cudaDriverEntryPointQueryResult qr;
  cudaGetDriverEntryPoint("cuTensorMapEncodeTiled", &fnp, cudaEnableDefault, &qr);
  EncodeFn fn = (EncodeFn)fnp;
  void* gs = nullptr;
  cudaGetSymbolAddress(&gs, g_scratch);
  Maps maps;
  CUtensorMap &tmX = maps.m[0], &tmWq = maps.m[1], &tmK = maps.m[2], &tmV = maps.m[3], &tmWo = maps.m[4], &tmG = maps.m[5],
              &tmU = maps.m[6], &tmD = maps.m[7];
  encode2d(fn, &tmK, d_in[1], 16 * SEQ, DH, 128);
  encode2d(fn, &tmV, d_in[2], 16 * SEQ, DH, 128);
  encode2d(fn, &tmWq, d_in[3], DM, 4096, 64);
  {
    const cuuint64_t dims[3] = {64, SEQ, 9}, strides[2] = {DM * 2, 128};
    const cuuint32_t box[3] = {64, 64, 3};
    encode(fn, &tmX, d_in[0], 3, dims, strides, box);
  }
  encode2d(fn, &maps.m[8], d_in[0], SEQ, DM, 16);
  encode2d(fn, &tmWo, d_in[4], 4096, DM, 128);
  encode2d(fn, &tmG, d_in[7], DM, FF, 192);
  encode2d(fn, &tmU, d_in[8], DM, FF, 192);
  encode2d(fn, &tmD, d_in[9], FF, DM, 192);
  cudaFuncSetAttribute(fused_kernel, cudaFuncAttributeMaxDynamicSharedMemorySize, SM_TOTAL);
  fused_kernel<<<N_CTA, THREADS, SM_TOTAL>>>((const __nv_bfloat16*)d_in[0], (const __nv_bfloat16*)d_in[6], (const __nv_bfloat16*)d_in[3],
                                            (const __nv_bfloat16*)d_in[4], (__nv_bfloat16*)d_out, (Scratch*)gs, maps, (const __nv_bfloat16*)d_in[1]);
}
```

```cpp
#include <cuda_runtime.h>
#include <cuda_bf16.h>
#include <cuda.h>
#include <stdint.h>

namespace {

constexpr int SEQ = 2048, DM = 576, DH = 128, FF = 4608, TOPC = 8;
constexpr int N_ATT_CTA = 128, N_CTA = 132;
constexpr int THREADS = 384;

constexpr uint32_t SM_RING = 0;
constexpr uint32_t STAGE = 32768;
constexpr uint32_t SM_SLOT = 131072;
constexpr uint32_t FSTAGE = 24576;
constexpr uint32_t SM_XSEL = 196608;
constexpr uint32_t SM_H = 205824;
constexpr uint32_t SM_MISC = 229376;
constexpr uint32_t SM_FULL = SM_MISC, SM_BAR_MISC = SM_MISC + 64, SM_BAR_XG = SM_MISC + 72, SM_BAR_P8 = SM_MISC + 80, SM_BAR_Q3 = SM_MISC + 88, SM_XFULL = SM_MISC + 96,
                   SM_EMPTY = SM_MISC + 120, SM_BAR_ROWS = SM_MISC + 216, SM_TAG = SM_MISC + 288,
                   SM_ROWS = SM_MISC + 304, SM_BOX8 = SM_MISC + 1024;
constexpr uint32_t SM_TOTAL = SM_MISC + 3072;
constexpr uint32_t SM_X = SM_MISC - 147456;

constexpr int BAR_ROWS = 6, BAR_HELPER = 7, BAR_OA = 8;
constexpr int NST_Q = 18, NST_KV = 128, NST_O = 18;
constexpr uint32_t SL_KE = (NST_Q - 1) & 3, SL_VE = NST_Q & 3, SL_KO = (NST_Q + 1) & 3, SL_VO = (NST_Q + 2) & 3;
#define X_ORDER 0
#define X_PF 3
#define X_PFQ 3
#define X_REL 0
#define X_SLEEP8 700
#define X_QP 2
#define X_WARM 0
#define X_S1 12
#define X_IP 0
#define X_XS 0
#define X_CA2 1
#define X_RS 1
#define X_DS 0
#define X_HT 1
#define X_N1 5
#define X_SPLIT 44
#define X_PARK 5
#define X_C0 32
#define X_C1 40
#define X_C2 56
#define X_C3 72
#define X_CA 1
#define X_FIN 4
constexpr float SM_SCALE_LOG2 = 0.08838834764831845f * 1.4426950408889634f;

struct Scratch {
  uint4 part[16 * 64 * 2 * 4 * 128];
  uint4 gate[N_ATT_CTA * 144 * 8];
  uint4 q3[N_ATT_CTA * 1024];
  uint4 xn[SEQ * DM / 8];
  uint32_t key[SEQ];
  float ypart[4 * TOPC * DM];
  uint32_t top[32];
  unsigned launch[160];
  unsigned rows[16 * 32];
  unsigned q3_flag[N_ATT_CTA];
  unsigned ycnt;
};
__device__ __align__(1024) Scratch g_scratch;

__device__ __forceinline__ void prof(int, int, int = 0) {}
__device__ __forceinline__ void profc(int, int) {}

__device__ __forceinline__ uint32_t smem_u32(const void* p) { return (uint32_t)__cvta_generic_to_shared(p); }
__device__ __forceinline__ void mbar_init(uint32_t bar, uint32_t cnt) {
  asm volatile("mbarrier.init.shared::cta.b64 [%0], %1;" ::"r"(bar), "r"(cnt) : "memory");
}
__device__ __forceinline__ void mbar_expect_tx(uint32_t bar, uint32_t bytes) {
  asm volatile("mbarrier.arrive.expect_tx.shared::cta.b64 _, [%0], %1;" ::"r"(bar), "r"(bytes) : "memory");
}
__device__ __forceinline__ void mbar_arrive(uint32_t bar) {
  asm volatile("mbarrier.arrive.shared::cta.b64 _, [%0];" ::"r"(bar) : "memory");
}
__device__ __forceinline__ void mbar_arrive_cluster(uint32_t bar_cluster_addr) {
  asm volatile("mbarrier.arrive.shared::cluster.b64 _, [%0];" ::"r"(bar_cluster_addr) : "memory");
}
template <int ID>
__device__ __forceinline__ void mbar_arrive_cluster_now(uint32_t bar_cluster_addr, bool pred, uint32_t zero) {
  asm volatile("{\n.reg .pred p, q;\nsetp.ne.u32 p, %1, 0;\nsetp.eq.u32 q, %2, %3;\n"
               "ARR_LOOP:\n@p mbarrier.arrive.shared::cluster.b64 _, [%0];\n@q bra.uni ARR_LOOP;\n}"
               ::"r"(bar_cluster_addr), "r"((uint32_t)pred), "r"(zero), "n"(ID) : "memory");
}
__device__ __forceinline__ void block_fence(int id, uint32_t zero = blockIdx.y) {
  asm volatile("{\n.reg .pred q;\nsetp.eq.u32 q, %0, %1;\nBF_LOOP:\n@q st.volatile.shared.u32 [%0], %0;\n@q bra.uni BF_LOOP;\n}"
               ::"r"(zero), "r"(id) : "memory");
}
__device__ __forceinline__ bool mbar_test(uint32_t bar, uint32_t parity) {
  uint32_t ok;
  asm volatile("{\n.reg .pred p;\nmbarrier.test_wait.parity.shared::cta.b64 p, [%1], %2;\nselp.u32 %0, 1, 0, p;\n}"
               : "=r"(ok) : "r"(bar), "r"(parity) : "memory");
  return ok;
}
__device__ __forceinline__ void mbar_wait(uint32_t bar, uint32_t parity) {
  asm volatile("{\n.reg .pred p, q;\n.reg .u32 n;\nmov.u32 n, 0;\n"
               "WAIT_LOOP:\nmbarrier.try_wait.parity.shared::cta.b64 p, [%0], %1;\n"
               "add.u32 n, n, 1;\nsetp.lt.u32 q, n, 4194304;\nand.pred q, q, !p;\n@q bra WAIT_LOOP;\n}"
               ::"r"(bar), "r"(parity) : "memory");
}
__device__ __forceinline__ uint32_t mapa(uint32_t addr, uint32_t rank) {
  uint32_t r;
  asm volatile("mapa.shared::cluster.u32 %0, %1, %2;" : "=r"(r) : "r"(addr), "r"(rank));
  return r;
}
__device__ __forceinline__ void cluster_arrive() { asm volatile("barrier.cluster.arrive.relaxed.aligned;" ::: "memory"); }
__device__ __forceinline__ bool elect_one() {
  uint32_t p;
  asm volatile("{\n.reg .pred p;\nelect.sync _|p, 0xffffffff;\nselp.u32 %0, 1, 0, p;\n}" : "=r"(p));
  return p;
}
__device__ __forceinline__ int read_lane() { return threadIdx.x & 31; }
__device__ __forceinline__ void cluster_wait() { asm volatile("barrier.cluster.wait.acquire.aligned;" ::: "memory"); }
__device__ __forceinline__ void bar_sync(int id, int n) { asm volatile("barrier.cta.sync %0, %1;" ::"r"(id), "r"(n) : "memory"); }
__device__ __forceinline__ void bar_arrive(int id, int n) { asm volatile("barrier.cta.arrive %0, %1;" ::"r"(id), "r"(n) : "memory"); }

__device__ __forceinline__ uint64_t policy_evict_first() {
  uint64_t p;
  asm("createpolicy.fractional.L2::evict_first.b64 %0, 1.0;" : "=l"(p));
  return p;
}
__device__ __forceinline__ uint64_t policy_evict_normal() {
  uint64_t p;
  asm("createpolicy.fractional.L2::evict_normal.b64 %0, 1.0;" : "=l"(p));
  return p;
}
__device__ __forceinline__ void tma3d(uint32_t dst, const CUtensorMap* tm, int c1, int c2, uint32_t bar) {
  asm volatile("cp.async.bulk.tensor.3d.shared::cluster.global.mbarrier::complete_tx::bytes [%0], [%1, {%2, %3, %4}], [%5];"
               ::"r"(dst), "l"(tm), "r"(0), "r"(c1), "r"(c2), "r"(bar) : "memory");
}
__device__ __forceinline__ void tma2d(uint32_t dst, const CUtensorMap* tm, int c0, int c1, uint32_t bar) {
  asm volatile("cp.async.bulk.tensor.2d.shared::cluster.global.mbarrier::complete_tx::bytes [%0], [%1, {%2, %3}], [%4];"
               ::"r"(dst), "l"(tm), "r"(c0), "r"(c1), "r"(bar) : "memory");
}
__device__ __forceinline__ void tma2d_stream(uint32_t dst, const CUtensorMap* tm, int c0, int c1, uint32_t bar) {
  asm volatile("{\n.reg .b64 pol;\ncreatepolicy.fractional.L2::evict_first.b64 pol, 1.0;\n"
               "cp.async.bulk.tensor.2d.shared::cluster.global.mbarrier::complete_tx::bytes.L2::cache_hint [%0], [%1, {%2, %3}], [%4], pol;\n}"
               ::"r"(dst), "l"(tm), "r"(c0), "r"(c1), "r"(bar) : "memory");
}
__device__ __forceinline__ void tma2d_prefetch(const CUtensorMap* tm, int c0, int c1) {
  asm volatile("cp.async.bulk.prefetch.tensor.2d.L2.global [%0, {%1, %2}];" ::"l"(tm), "r"(c0), "r"(c1) : "memory");
}
__device__ __forceinline__ void prefetch_l2(const void* p, uint32_t bytes) {
  asm volatile("cp.async.bulk.prefetch.L2.global [%0], %1;" ::"l"(p), "r"(bytes) : "memory");
}
__device__ __forceinline__ void prefetch_tmap(const CUtensorMap* tm) {
  asm volatile("prefetch.tensormap [%0];" ::"l"(tm) : "memory");
}

__device__ __forceinline__ void wg_fence() { asm volatile("wgmma.fence.sync.aligned;" ::: "memory"); }
__device__ __forceinline__ void wg_commit() { asm volatile("wgmma.commit_group.sync.aligned;" ::: "memory"); }
template <int N> __device__ __forceinline__ void wg_wait() { asm volatile("wgmma.wait_group.sync.aligned %0;" ::"n"(N) : "memory"); }

__device__ __forceinline__ uint64_t mkdesc(uint32_t addr, uint32_t lbo_bytes) {
  return (uint64_t)(((addr & 0x3FFFF) >> 4) | ((lbo_bytes >> 4) << 16)) | ((uint64_t)0x40000040u << 32);
}
template <int N> __device__ __forceinline__ void pin(float (&a)[N]) {
#pragma unroll
  for (int i = 0; i < N; i++) asm volatile("" : "+f"(a[i])::"memory");
}
template <int N> __device__ __forceinline__ void pin(uint32_t (&a)[N]) {
#pragma unroll
  for (int i = 0; i < N; i++) asm volatile("" : "+r"(a[i])::"memory");
}

#define F8(d, o) "+f"(d[o]), "+f"(d[o + 1]), "+f"(d[o + 2]), "+f"(d[o + 3]), "+f"(d[o + 4]), "+f"(d[o + 5]), "+f"(d[o + 6]), "+f"(d[o + 7])
#define R32A "%0, %1, %2, %3, %4, %5, %6, %7, %8, %9, %10, %11, %12, %13, %14, %15, %16, %17, %18, %19, %20, %21, %22, %23, %24, %25, %26, %27, %28, %29, %30, %31"
#define R32B "%32, %33, %34, %35, %36, %37, %38, %39, %40, %41, %42, %43, %44, %45, %46, %47, %48, %49, %50, %51, %52, %53, %54, %55, %56, %57, %58, %59, %60, %61, %62, %63"

template <int TB>
__device__ __forceinline__ void mma_n128(float (&d)[64], uint32_t a0, uint32_t a1, uint32_t a2, uint32_t a3, uint64_t db, int acc) {
  asm volatile("{\n.reg .pred p;\nsetp.ne.b32 p, %69, 0;\n"
               "wgmma.mma_async.sync.aligned.m64n128k16.f32.bf16.bf16 {" R32A ", " R32B "}, {%64, %65, %66, %67}, %68, p, 1, 1, %70;\n}\n"
               : F8(d, 0), F8(d, 8), F8(d, 16), F8(d, 24), F8(d, 32), F8(d, 40), F8(d, 48), F8(d, 56)
               : "r"(a0), "r"(a1), "r"(a2), "r"(a3), "l"(db), "r"(acc), "n"(TB));
}
template <int TB>
__device__ __forceinline__ void mma_n128_ss(float (&d)[64], uint64_t da, uint64_t db, int acc) {
  asm volatile("{\n.reg .pred p;\nsetp.ne.b32 p, %66, 0;\n"
               "wgmma.mma_async.sync.aligned.m64n128k16.f32.bf16.bf16 {" R32A ", " R32B "}, %64, %65, p, 1, 1, 0, %67;\n}\n"
               : F8(d, 0), F8(d, 8), F8(d, 16), F8(d, 24), F8(d, 32), F8(d, 40), F8(d, 48), F8(d, 56)
               : "l"(da), "l"(db), "r"(acc), "n"(TB));
}
template <int TB>
__device__ __forceinline__ void mma_n64(float (&d)[32], uint32_t a0, uint32_t a1, uint32_t a2, uint32_t a3, uint64_t db, int acc) {
  asm volatile("{\n.reg .pred p;\nsetp.ne.b32 p, %37, 0;\n"
               "wgmma.mma_async.sync.aligned.m64n64k16.f32.bf16.bf16 {" R32A "}, {%32, %33, %34, %35}, %36, p, 1, 1, %38;\n}\n"
               : F8(d, 0), F8(d, 8), F8(d, 16), F8(d, 24)
               : "r"(a0), "r"(a1), "r"(a2), "r"(a3), "l"(db), "r"(acc), "n"(TB));
}
__device__ __forceinline__ void mma_n8(float (&d)[4], uint64_t da, uint64_t db, int acc) {
  asm volatile("{\n.reg .pred p;\nsetp.ne.b32 p, %6, 0;\n"
               "wgmma.mma_async.sync.aligned.m64n8k16.f32.bf16.bf16 {%0, %1, %2, %3}, %4, %5, p, 1, 1, 1, 0;\n}\n"
               : "+f"(d[0]), "+f"(d[1]), "+f"(d[2]), "+f"(d[3])
               : "l"(da), "l"(db), "r"(acc));
}
__device__ __forceinline__ void hmma_k16(float (&d)[4], uint32_t a0, uint32_t a1, uint32_t a2, uint32_t a3, uint32_t b0, uint32_t b1) {
  asm volatile("mma.sync.aligned.m16n8k16.row.col.f32.bf16.bf16.f32 {%0, %1, %2, %3}, {%4, %5, %6, %7}, {%8, %9}, {%0, %1, %2, %3};"
               : "+f"(d[0]), "+f"(d[1]), "+f"(d[2]), "+f"(d[3]) : "r"(a0), "r"(a1), "r"(a2), "r"(a3), "r"(b0), "r"(b1));
}

__device__ __forceinline__ uint32_t pack2(float lo, float hi) {
  uint32_t r;
  asm("cvt.rn.bf16x2.f32 %0, %1, %2;" : "=r"(r) : "f"(hi), "f"(lo));
  return r;
}
__device__ __forceinline__ float bf_lo(uint32_t w) { return __uint_as_float(w << 16); }
__device__ __forceinline__ float bf_hi(uint32_t w) { return __uint_as_float(w & 0xFFFF0000u); }
__device__ __forceinline__ float bfr(float x) { return __uint_as_float(pack2(0.f, x)); }
__device__ __forceinline__ uint32_t sub2(uint32_t a, uint32_t b) {
  uint32_t r;
  asm("sub.rn.bf16x2 %0, %1, %2;" : "=r"(r) : "r"(a), "r"(b));
  return r;
}
__device__ __forceinline__ uint32_t add2(uint32_t a, uint32_t b) {
  uint32_t r;
  asm("add.rn.bf16x2 %0, %1, %2;" : "=r"(r) : "r"(a), "r"(b));
  return r;
}
__device__ __forceinline__ uint32_t mul2(uint32_t a, uint32_t b) {
  uint32_t r;
  asm("mul.rn.bf16x2 %0, %1, %2;" : "=r"(r) : "r"(a), "r"(b));
  return r;
}
__device__ __forceinline__ uint32_t fma2(uint32_t a, uint32_t b, uint32_t c) {
  uint32_t r;
  asm("fma.rn.bf16x2 %0, %1, %2, %3;" : "=r"(r) : "r"(a), "r"(b), "r"(c));
  return r;
}
__device__ __forceinline__ float ex2(float x) {
  float r;
  asm("ex2.approx.ftz.f32 %0, %1;" : "=f"(r) : "f"(x));
  return r;
}
__device__ __forceinline__ float rcp(float x) {
  float r;
  asm("rcp.approx.ftz.f32 %0, %1;" : "=f"(r) : "f"(x));
  return r;
}
__device__ __forceinline__ float silu_f(float t) { return t * rcp(1.0f + ex2(-1.4426950408889634f * t)); }
__device__ __forceinline__ void lds128(uint32_t a, uint32_t& x, uint32_t& y, uint32_t& z, uint32_t& w) {
  asm volatile("ld.shared.v4.u32 {%0, %1, %2, %3}, [%4];" : "=r"(x), "=r"(y), "=r"(z), "=r"(w) : "r"(a) : "memory");
}
__device__ __forceinline__ void ldsm4(uint32_t a, uint32_t& x, uint32_t& y, uint32_t& z, uint32_t& w) {
  asm volatile("ldmatrix.sync.aligned.m8n8.x4.shared.b16 {%0, %1, %2, %3}, [%4];" : "=r"(x), "=r"(y), "=r"(z), "=r"(w) : "r"(a) : "memory");
}
constexpr uint32_t TAG_BIT = 0x10000;
__device__ __forceinline__ void st_gran(uint4* p, uint32_t x, uint32_t y, uint32_t z, uint32_t w) {
  asm volatile("st.relaxed.gpu.global.v4.b32 [%0], {%1, %2, %3, %4};" ::"l"(p), "r"(x), "r"(y), "r"(z), "r"(w) : "memory");
}
__device__ __forceinline__ void ld_gran(const uint4* p, uint32_t& x, uint32_t& y, uint32_t& z, uint32_t& w) {
  asm volatile("ld.relaxed.gpu.global.v4.b32 {%0, %1, %2, %3}, [%4];" : "=r"(x), "=r"(y), "=r"(z), "=r"(w) : "l"(p) : "memory");
}
__device__ __forceinline__ void ldsm4t(uint32_t a, uint32_t& x, uint32_t& y, uint32_t& z, uint32_t& w) {
  asm volatile("ldmatrix.sync.aligned.m8n8.x4.trans.shared.b16 {%0, %1, %2, %3}, [%4];" : "=r"(x), "=r"(y), "=r"(z), "=r"(w) : "r"(a) : "memory");
}
__device__ __forceinline__ void stsm4t(uint32_t a, uint32_t x, uint32_t y, uint32_t z, uint32_t w) {
  asm volatile("stmatrix.sync.aligned.m8n8.x4.trans.shared.b16 [%0], {%1, %2, %3, %4};" ::"r"(a), "r"(x), "r"(y), "r"(z), "r"(w) : "memory");
}
__device__ __forceinline__ void stsm4(uint32_t a, uint32_t x, uint32_t y, uint32_t z, uint32_t w) {
  asm volatile("stmatrix.sync.aligned.m8n8.x4.shared.b16 [%0], {%1, %2, %3, %4};" ::"r"(a), "r"(x), "r"(y), "r"(z), "r"(w) : "memory");
}
template <class T>
__device__ __forceinline__ T* at(const void* base, uint32_t off) {
  uint64_t r;
  asm("{\n.reg .u32 lo, hi;\nmov.b64 {lo, hi}, %1;\nadd.cc.u32 lo, lo, %2;\naddc.u32 hi, hi, 0;\nmov.b64 %0, {lo, hi};\n}"
      : "=l"(r) : "l"(base), "r"(off));
  return (T*)__cvta_global_to_generic(r);
}
__device__ __forceinline__ void add_granules(float (&red)[32], const uint32_t (&g)[16]) {
#pragma unroll
  for (int i = 0; i < 16; i++) { red[2 * i] += bf_lo(g[i]); red[2 * i + 1] += bf_hi((i & 3) ? g[i] : g[i] & ~TAG_BIT); }
}
__device__ __forceinline__ bool granules_ok(const uint32_t (&g)[16], uint32_t tag) {
  uint32_t u, v;
  asm("lop3.b32 %0, %1, %2, %3, 0x7E;" : "=r"(u) : "r"(g[0]), "r"(g[4]), "r"(tag));
  asm("lop3.b32 %0, %1, %2, %3, 0x7E;" : "=r"(v) : "r"(g[8]), "r"(g[12]), "r"(tag));
  return __all_sync(0xffffffffu, ((u | v) & TAG_BIT) == 0);
}
__device__ __forceinline__ unsigned ld_acquire(const unsigned* p) {
  unsigned v;
  asm volatile("ld.acquire.gpu.global.u32 %0, [%1];" : "=r"(v) : "l"(p) : "memory");
  return v;
}
__device__ __forceinline__ void red_release(unsigned* p) {
  asm volatile("red.release.gpu.global.add.u32 [%0], 1;" ::"l"(p) : "memory");
}
__device__ __forceinline__ void st_release(unsigned* p, unsigned v) {
  asm volatile("st.release.gpu.global.u32 [%0], %1;" ::"l"(p), "r"(v) : "memory");
}

template <int K0, int K1>
__device__ __forceinline__ void ln_fetch(uint32_t (&xa)[144], uint32_t boxes, uint32_t lo) {
#pragma unroll
  for (int k = K0; k < K1; k++) ldsm4(((boxes + lo) ^ ((k & 3) << 5)) + (k >> 2) * 8192, xa[4 * k], xa[4 * k + 1], xa[4 * k + 2], xa[4 * k + 3]);
}
template <int K0, int K1>
__device__ __forceinline__ void ln_sums(const uint32_t (&xa)[144], float (&sm)[4][4]) {
#pragma unroll
  for (int k = K0; k < K1; k++) hmma_k16(sm[k & 3], xa[4 * k], xa[4 * k + 1], xa[4 * k + 2], xa[4 * k + 3], 0x3F803F80u, 0x3F803F80u);
}
__device__ __forceinline__ uint32_t sq8(const uint32_t* a) {
  uint32_t t, u;
  asm("mul.rn.bf16x2 %0, %1, %1;" : "=r"(t) : "r"(a[0]));
  asm("mul.rn.bf16x2 %0, %1, %1;" : "=r"(u) : "r"(a[2]));
#pragma unroll
  for (int i = 4; i < 16; i += 4) {
    asm("fma.rn.bf16x2 %0, %1, %1, %0;" : "+r"(t) : "r"(a[i]));
    asm("fma.rn.bf16x2 %0, %1, %1, %0;" : "+r"(u) : "r"(a[i + 2]));
  }
  return add2(t, u);
}
__device__ __forceinline__ void ln_centre(uint32_t (&xa)[144], int j0, int j1, uint32_t mm0, uint32_t mm1, float& sq0, float& sq1) {
#pragma unroll
  for (int j = 0; j < 72; j += 8)
    if (j >= j0 && j < j1) {
#pragma unroll
      for (int k = j; k < j + 8; k++) {
        xa[2 * k] = sub2(xa[2 * k], mm0);
        xa[2 * k + 1] = sub2(xa[2 * k + 1], mm1);
      }
      const uint32_t t0 = sq8(xa + 2 * j), t1 = sq8(xa + 2 * j + 1);
      sq0 += bf_lo(t0) + bf_hi(t0);
      sq1 += bf_lo(t1) + bf_hi(t1);
    }
}
__device__ __forceinline__ float ln_rstd(float var) {
  float sd;
  asm("sqrt.approx.ftz.f32 %0, %1;" : "=f"(sd) : "f"(bfr(bfr(fmaxf(var, 0.0f)) + 1e-5f)));
  return rcp(bfr(sd));
}
__device__ __forceinline__ uint32_t silu2(uint32_t t) { return pack2(silu_f(bf_lo(t)), silu_f(bf_hi(t))); }
__device__ __forceinline__ float sum8(float v) {
#pragma unroll
  for (int d = 4; d; d >>= 1) v += __shfl_xor_sync(0xffffffffu, v, d);
  return v;
}
__device__ __forceinline__ void await_count(const unsigned* p, unsigned target, unsigned sleep_ns) {
#pragma unroll 1
  for (int n = 0; n < (1 << 18) && __any_sync(0xffffffffu, (int)(ld_acquire(p) - target) < 0); n++) __nanosleep(sleep_ns);
}
__device__ __forceinline__ void bulk_load(uint32_t dst, const void* src, uint32_t bytes, uint32_t bar) {
  asm volatile("cp.async.bulk.shared::cluster.global.mbarrier::complete_tx::bytes [%0], [%1], %2, [%3];"
               ::"r"(dst), "l"(src), "r"(bytes), "r"(bar) : "memory");
}
__device__ __forceinline__ void proxy_fence() { asm volatile("fence.proxy.async;" ::: "memory"); }

template <int V> struct IC { static constexpr int value = V; };

struct Ctx {
  uint32_t sb;
  uint8_t* sp;
  uint32_t rank;
  Scratch* gs;
};

__device__ __forceinline__ void dly(const Ctx&, int) {}
template <int BOXES>
__device__ __forceinline__ void load_stage(uint32_t dst, const CUtensorMap* tm, int c0, int c1, uint32_t bar, uint32_t bytes, uint64_t pol) {
  asm volatile("{\n.reg .pred p;\nelect.sync _|p, 0xffffffff;\n"
               "@p mbarrier.arrive.expect_tx.shared::cta.b64 _, [%4], %7;\n"
               "@p cp.async.bulk.tensor.2d.shared::cluster.global.mbarrier::complete_tx::bytes.multicast::cluster.L2::cache_hint"
               " [%0], [%1, {%2, %3}], [%4], %5, %6;\n}"
               ::"r"(dst), "l"(tm), "r"(c0), "r"(c1), "r"(bar), "h"((uint16_t)3), "l"(pol), "r"(bytes) : "memory");
  if (BOXES == 2)
    asm volatile("{\n.reg .pred p;\nelect.sync _|p, 0xffffffff;\n"
                 "@p cp.async.bulk.tensor.2d.shared::cluster.global.mbarrier::complete_tx::bytes.multicast::cluster.L2::cache_hint"
                 " [%0], [%1, {%2, %3}], [%4], %5, %6;\n}"
                 ::"r"(dst + 8192), "l"(tm), "r"(c0), "r"(c1 + 64), "r"(bar), "h"((uint16_t)3), "l"(pol) : "memory");
}
__device__ __forceinline__ void attn_producer(const Ctx& cx, int qb, int hs, const CUtensorMap* tmX, const CUtensorMap* tmK,
                                              const CUtensorMap* tmV, const CUtensorMap* tmWq, const CUtensorMap* tmWo) {
  const uint32_t full = cx.sb + SM_FULL, empty = cx.sb + SM_EMPTY, ring = cx.sb + SM_RING + cx.rank * 16384;
  const uint64_t keep = policy_evict_normal(), last_use = policy_evict_first();
  auto acquire = [&](int st) {
    mbar_wait(empty + 8 * (st & 3), ((st >> 2) ^ ((st & 3) >> 1) ^ 1) & 1);
    if (st > 3) dly(cx, st);
  };
  if (elect_one()) {
#pragma unroll
    for (int j = 0; j < 3; j++) {
      mbar_expect_tx(cx.sb + SM_XFULL + 96 + 8 * j, 24576);
      tma3d(cx.sb + SM_X + 73728 + j * 24576, tmX, qb * 128 + 64, j * 3, cx.sb + SM_XFULL + 96 + 8 * j);
    }
  }
  __syncwarp();
  const int c0 = cx.rank * 64;
#pragma unroll 1
  for (int p = 0; p < 3; p++) {
    const int n0 = (hs * 4 + ((0x120 >> (4 * p)) & 3)) * DH + c0;
#pragma unroll
    for (int i = 0; i < 5; i++) {
      const int st = (p == 2 ? 13 : 5 * p) + i, sl = st & 3;
      if (i == 4 && p == 2) break;
      acquire(st);
      if (i == 2) load_stage<1>(ring + sl * STAGE, tmWq, n0, 256, full + 8 * sl, 16384, last_use);
      else load_stage<2>(ring + sl * STAGE, tmWq, n0, i < 2 ? 128 * i : 128 * i - 64, full + 8 * sl, 32768, last_use);
      if (i == X_PFQ && p < 2 && elect_one()) {
        tma2d_prefetch(tmWq, (hs * 4 + 2 - p) * DH + (qb & 1) * 64, (qb >> 1) * 64);
        if (p == 0 && qb < 9) tma2d_prefetch(tmWq, (hs * 4 + 3) * DH, qb * 64);
      }
      __syncwarp();
    }
    if (p == 1) {
      const int n3 = (hs * 4 + 3) * DH;
      acquire(10);
      load_stage<2>(ring + 2 * STAGE, tmWq, n3, 2 * c0, full + 16, 32768, last_use);
      acquire(11);
      if (cx.rank) load_stage<1>(ring + 3 * STAGE, tmWq, n3, 384, full + 24, 24576, last_use);
      else load_stage<2>(ring + 3 * STAGE, tmWq, n3, 256, full + 24, 24576, last_use);
      acquire(12);
      load_stage<1>(ring, tmWq, n3, 448 + c0, full, 16384, last_use);
    }
  }
  int vrow = 0;
  uint64_t vpol = keep;
#pragma unroll 1
  for (int j = 0; j < 32; j++) {
    const int st = NST_Q - 1 + 4 * j, row = (hs * 2 + (j >> 4)) * SEQ + (j & 7) * 256;
    const uint64_t pol = (j & 8) ? last_use : keep;
    if (j == 24) mbar_wait(cx.sb + SM_BAR_Q3, 0);
    acquire(st);
    load_stage<1>(ring + SL_KE * STAGE, tmK, c0, row, full + 8 * SL_KE, 32768, pol);
    acquire(st + 1);
    if (j) load_stage<1>(ring + SL_VE * STAGE, tmV, c0, vrow, full + 8 * SL_VE, 32768, vpol);
    else load_stage<2>(ring + SL_VE * STAGE, tmWq, (hs * 4 + 1) * DH + c0, 448, full + 8 * SL_VE, 32768, last_use);
    vrow = row + 128;
    vpol = pol;
    acquire(st + 2);
    load_stage<1>(ring + SL_KO * STAGE, tmK, c0, vrow, full + 8 * SL_KO, 32768, pol);
    acquire(st + 3);
    load_stage<1>(ring + SL_VO * STAGE, tmV, c0, row, full + 8 * SL_VO, 32768, pol);
  }
  acquire(NST_Q + NST_KV - 1);
  load_stage<1>(ring + SL_KE * STAGE, tmV, c0, vrow, full + 8 * SL_KE, 32768, last_use);
#pragma unroll 1
  for (int u = 0; u < NST_O; u++) {
    const int st = NST_Q + NST_KV + u, sl = st & 3;
    const int blk = u < 4 && cx.rank ? 8 : ((hs + max(u >> 1, 1)) & 7);
    const int head = u < 4 ? u ^ (u >> 1) : ((u & 1) * 2 + cx.rank + 3) & 3;
    acquire(st);
    load_stage<1>(ring + sl * STAGE, tmWo, blk * 64, hs * 512 + head * 128, full + 8 * sl, 32768, last_use);
  }
}

__device__ __forceinline__ uint32_t xn_offset(uint32_t row, int lane) {
  return (row >> 6) * (9 * 8192) + (row & 63) * 128 + ((((lane >> 2) ^ row) & 7) << 4) + (lane & 3) * 4;
}

__device__ __forceinline__ void attn_rows(const Ctx& cx, int qb, int hs, int hw, int lane, const CUtensorMap* tmX16,
                                          const __nv_bfloat16* w_r) {
  extern __shared__ __align__(1024) uint8_t smem_rows[];
  auto box = [&](int blk) { return blk < 8 ? SM_SLOT + 2 * STAGE + 8192 + (blk >> 2) * 16384 + (blk & 3) * 2048 : SM_BOX8; };
  const uint32_t sb = smem_u32(smem_rows);
  if (hw == 0) {
    bar_sync(BAR_HELPER, 160);
    if (elect_one()) {
      mbar_expect_tx(sb + SM_BAR_ROWS, 9 * 2048);
#pragma unroll
      for (int i = 0; i < 9; i++) tma2d(sb + box(i), tmX16, i * 64, qb * 128 + hs * 16, sb + SM_BAR_ROWS);
    }
    __syncwarp();
  }
  uint32_t g = (lane >> 3) * 128 + (((lane ^ (lane >> 3)) & 7) << 4);
  auto next = [&]() {
    g = ((g + 512) & 2047) ^ 64;
    asm volatile("" : "+r"(g));
  };
  float* const part = (float*)(smem_rows + SM_ROWS);
  mbar_wait(sb + SM_BAR_ROWS, 0);
  if (hw == 0) dly(cx, 190);
#pragma unroll 1
  for (int i = 0; i < 4; i++) {
    float a = 0.f, b = 0.f;
#pragma unroll
    for (int j = 0; j < 3; j++) {
      const uint4 v = *(const uint4*)(smem_rows + box(hw * 3 + j) + g);
      const uint32_t w[4] = {v.x, v.y, v.z, v.w};
#pragma unroll
      for (int k = 0; k < 4; k++) {
        a += bf_lo(w[k]) + bf_hi(w[k]);
        b = fmaf(bf_lo(w[k]), bf_lo(w[k]), fmaf(bf_hi(w[k]), bf_hi(w[k]), b));
      }
    }
    a = sum8(a);
    b = sum8(b);
    float* p = part + hw * 16 + (g >> 7);
    p[0] = a;
    p[48] = b;
    next();
  }
  bar_sync(BAR_ROWS, 96);
  if (hw == 0) dly(cx, 191);
  {
    const float* p = part + (lane & 15);
    const float mean = (p[0] + p[16] + p[32]) * (1.0f / DM), rstd = ln_rstd((p[48] + p[64] + p[80]) * (1.0f / DM) - mean * mean);
    const uint32_t mm = pack2(mean, mean), rr = pack2(rstd - bfr(rstd), rstd);
#pragma unroll 1
    for (int u = hw * 12; u < hw * 12 + 12; u++) {
      const int blk = u >> 2;
      uint4* q = (uint4*)(smem_rows + box(blk) + g);
      uint4 v = *q;
      const uint32_t m = __shfl_sync(0xffffffffu, mm, g >> 7), r = __shfl_sync(0xffffffffu, rr, g >> 7);
      const uint32_t hi = __byte_perm(r, 0, 0x3232), lo = __byte_perm(r, 0, 0x1010);
      auto norm = [&](uint32_t w) {
        const uint32_t xc = sub2(w, m);
        return fma2(xc, hi, mul2(xc, lo));
      };
      v = make_uint4(norm(v.x), norm(v.y), norm(v.z), norm(v.w));
      *q = v;
      *at<uint4>(cx.gs->xn + ((qb * 2 + (hs >> 2)) * 9 + blk) * 512 + (hs & 3) * 128, g) = v;
      next();
    }
  }
  bar_sync(BAR_ROWS, 96);
  if (hw == 0) {
    dly(cx, 192);
    if (lane == 0) red_release(&cx.gs->rows[qb * 32]);
    dly(cx, 193);
  }
#pragma unroll 1
  for (int u = hw ? 13 * hw - 3 : 0; u < 13 * hw + 10; u++) {
    const int blk = u >> 2;
    const uint32_t o = (g + (u & 3) * 512) ^ ((u & 1) << 6);
    const uint4 v = *(const uint4*)(smem_rows + box(blk) + o);
    *at<uint4>(cx.gs->gate + (blk < 8 ? (qb * 8 + blk) * 144 + hs * 16 : (qb * 8 + hs) * 144 + 128) * 8, o) =
        make_uint4(silu2(v.x), silu2(v.y), silu2(v.z), silu2(v.w));
  }
  if (hw) dly(cx, 194 + hw);
  if (X_DS) __nanosleep(X_DS);
#pragma unroll 1
  for (int blk = hw * 3; blk < hw * 3 + 3; blk++) {
    const uint4 c = __ldg(at<const uint4>(w_r, blk * 128 + ((g ^ (g >> 3)) & 0x70)));
#pragma unroll 1
    for (int i = 0; i < 4; i++) {
      const uint4 v = *(const uint4*)(smem_rows + box(blk) + g);
      part[blk * 16 + (g >> 7)] =
          sum8(fmaf(bf_lo(v.x), bf_lo(c.x), fmaf(bf_hi(v.x), bf_hi(c.x), fmaf(bf_lo(v.y), bf_lo(c.y), bf_hi(v.y) * bf_hi(c.y)))) +
               fmaf(bf_lo(v.z), bf_lo(c.z), fmaf(bf_hi(v.z), bf_hi(c.z), fmaf(bf_lo(v.w), bf_lo(c.w), bf_hi(v.w) * bf_hi(c.w)))));
      next();
    }
  }
  bar_sync(BAR_ROWS, 96);
  if (hw == 0) {
    dly(cx, 194);
    float d = 0.f;
#pragma unroll
    for (int j = 0; j < 9; j++) d += part[j * 16 + (lane & 15)];
    const uint32_t row = qb * 128 + hs * 16 + (lane & 15), b = pack2(0.f, d);
    *at<uint32_t>(cx.gs->key, row * 4) = (b ^ ((int)b < 0 ? 0xFFFF0000u : 0x80000000u)) + 0xFFFF - row;
    __syncwarp();
    if (lane == 0) red_release(&cx.gs->rows[qb * 32 + 1]);
  }
}

constexpr uint32_t SM_XO = SM_SLOT, SM_GO = SM_SLOT + STAGE, SM_P8 = SM_SLOT + 2 * STAGE;
__device__ __forceinline__ void attn_helper(const Ctx& cx, int qb, int hs, int lane, const __nv_bfloat16* wo, const CUtensorMap* tmX16) {
  unsigned e = 0;
  if (lane == 0) {
    e = cx.gs->launch[blockIdx.x];
    cx.gs->launch[blockIdx.x] = e + 1;
  }
  e = __shfl_sync(0xffffffffu, e, 0);
  if (lane == 0) {
    *(uint32_t*)(cx.sp + SM_TAG) = (~e & 1) * TAG_BIT;
    mbar_arrive(cx.sb + SM_BAR_MISC);
  }
  bar_sync(BAR_HELPER, 64);
  await_count(&cx.gs->rows[qb * 32 + 1], 8 * (e + 1), 1000);
  await_count(&cx.gs->q3_flag[qb * 8 + hs], e + 1, 1000);
  proxy_fence();
  if (elect_one()) {
    mbar_expect_tx(cx.sb + SM_BAR_Q3, 16384);
#pragma unroll
    for (int i = 0; i < 2; i++) bulk_load(cx.sb + SM_SLOT + 2 * STAGE + i * 16384 + 8192, cx.gs->q3 + (qb * 16 + hs * 2 + i) * 512, 8192, cx.sb + SM_BAR_Q3);
  }
  __syncwarp();
  bar_sync(BAR_HELPER, 64);
  prefetch_l2(at<const void>(wo, (hs * 512 + qb * 32 + lane) * (DM * 2)), DM * 2);
  await_count(&cx.gs->ycnt, 4 * (e + 1), 500);
  const uint32_t mykey = __ldcg(at<const uint32_t>(cx.gs->top, (lane >> 1) * 4)), myrow = 0xFFFF - (mykey & 0xFFFF);
#pragma unroll 1
  for (uint32_t todo = __ballot_sync(0xffffffffu, lane < 16 && ((lane & 1) ? myrow >> 4 == qb * 8 + hs : myrow >> 7 == qb)); todo; todo &= todo - 1) {
    const int i = __ffs(todo) - 1, blk = (i & 1) ? 8 : hs;
    const uint32_t key = __shfl_sync(0xffffffffu, mykey, i), row = 0xFFFF - (key & 0xFFFF), o = xn_offset(row, lane);
    const uint32_t t = __ldcg(at<const uint32_t>(cx.gs->xn, o + blk * 8192));
    const float2* p = at<const float2>(cx.gs->ypart, ((i >> 1) * DM + blk * 64 + 2 * lane) * 4);
    const float2 y0 = __ldcg(p), y1 = __ldcg(p + TOPC * DM / 2), y2 = __ldcg(p + TOPC * DM), y3 = __ldcg(p + 3 * TOPC * DM / 2);
    const float rs = bfr(rcp(1.0f + ex2(-1.4426950408889634f * bf_hi(key ^ ((int)key < 0 ? 0x80000000u : 0xFFFF0000u)))));
    const uint32_t y = pack2((y0.x + y1.x) + (y2.x + y3.x), (y0.y + y1.y) + (y2.y + y3.y));
    const uint32_t u = pack2(bf_lo(y) * rs, bf_hi(y) * rs);
    *at<uint32_t>(cx.gs->gate, ((qb * 8 + hs) * 144 + ((i & 1) ? 128 + (row & 15) : row & 127)) * 128 + (o & 127)) = silu2(add2(t, u));
  }
  proxy_fence();
  bar_sync(BAR_OA, 352);
  if (elect_one()) {
    const uint32_t bar = cx.sb + SM_BAR_XG;
    mbar_expect_tx(bar, 2 * 144 * 128);
    bulk_load(cx.sb + SM_GO, cx.gs->gate + (qb * 8 + hs) * (144 * 8), 144 * 128, bar);
#pragma unroll 1
    for (int i = 0; i < 9; i++) tma2d_stream(cx.sb + SM_XO + i * 2048, tmX16, i < 8 ? hs * 64 : 512, qb * 128 + (i < 8 ? i : hs) * 16, bar);
  }
  __syncwarp();
  const uint4* src = cx.gs->part + (qb * 64 + 56 + hs) * 1024;
#pragma unroll 1
  for (int n = 0; n < (1 << 16); n++) {
    __nanosleep(n ? 400 : X_SLEEP8);
    uint32_t a, b, d, t;
    ld_gran(at<const uint4>(src, (lane & 7) * 2048 + 2032), a, b, d, t);
    if (__all_sync(0xffffffffu, ((a >> 16) ^ e) & 1)) break;
  }
  if (elect_one()) {
    mbar_expect_tx(cx.sb + SM_BAR_P8, 16384);
    bulk_load(cx.sb + SM_P8, src, 16384, cx.sb + SM_BAR_P8);
  }
  __syncwarp();
}
__device__ __forceinline__ void attn_finish8(const Ctx& cx, int qb, int hs, int hw, int lane, __nv_bfloat16* out) {
  const uint32_t tag = *(const uint32_t*)(cx.sp + SM_TAG);
  mbar_wait(cx.sb + SM_BAR_P8, 0);
  mbar_wait(cx.sb + SM_BAR_XG, 0);
#pragma unroll 1
  for (int g = 2 - hw; g < 4; g += 3) {
    float acc[8] = {0.f, 0.f, 0.f, 0.f, 0.f, 0.f, 0.f, 0.f};
    uint32_t a[4];
#pragma unroll 1
    for (uint32_t o = g * 512 + lane * 16; o < 16384; o += 2048) {
      lds128(cx.sb + SM_P8 + o, a[0], a[1], a[2], a[3]);
#pragma unroll 1
      for (int n = 0; n < (1 << 16) && __any_sync(0xffffffffu, (a[0] & TAG_BIT) != tag); n++)
        ld_gran(at<const uint4>(cx.gs->part, (qb * 64 + 56 + hs) * 16384 + o), a[0], a[1], a[2], a[3]);
      a[0] &= ~TAG_BIT;
#pragma unroll
      for (int j = 0; j < 4; j++) { acc[2 * j] += bf_lo(a[j]); acc[2 * j + 1] += bf_hi(a[j]); }
    }
    asm volatile("" : "+r"(lane));
    const uint32_t tile = cx.sb + SM_XO + (128 + (lane & 15)) * 128 + (((lane >> 4) ^ (lane & 7)) << 4);
    uint32_t b[4];
    ldsm4((tile ^ (g << 5)) + STAGE, a[0], a[1], a[2], a[3]);
    ldsm4(tile ^ (g << 5), b[0], b[1], b[2], b[3]);
    stsm4(tile ^ (g << 5), fma2(pack2(acc[0], acc[1]), a[0], b[0]), fma2(pack2(acc[2], acc[3]), a[1], b[1]),
          fma2(pack2(acc[4], acc[5]), a[2], b[2]), fma2(pack2(acc[6], acc[7]), a[3], b[3]));
  }
  bar_sync(BAR_ROWS, 96);
#pragma unroll 1
  for (int ch = threadIdx.x - 32; ch < 128; ch += 96)
    *at<uint4>(out, ((qb * 128 + hs * 16 + (ch >> 3)) * DM + 512 + (ch & 7) * 8) * 2) =
        *(const uint4*)(cx.sp + SM_XO + (128 + (ch >> 3)) * 128 + (((ch ^ (ch >> 3)) & 7) << 4));
}

constexpr float SUM_HI = 1.8446744e19f, SUM_LO = 9.0949470e-13f;

__device__ __forceinline__ void softmax_shift(float (&s)[64], float n0, float n1) {
#pragma unroll
  for (int i = 0; i < 64; i++) s[i] += (i & 2) ? n1 : n0;
}
template <int LO, int HI>
__device__ __forceinline__ void softmax_exp(float (&s)[64]) {
#pragma unroll
  for (int i = LO; i < HI; i++) s[i] = ex2(s[i]);
}
__device__ __forceinline__ void row_sums(const uint32_t (&pf)[32], float& l0, float& l1) {
  uint32_t t[16];
#pragma unroll
  for (int i = 0; i < 16; i++) t[i] = add2(pf[(i >> 1) * 4 + (i & 1)], pf[(i >> 1) * 4 + 2 + (i & 1)]);
#pragma unroll
  for (int i = 0; i < 8; i++) t[i] = add2(t[(i >> 1) * 4 + (i & 1)], t[(i >> 1) * 4 + 2 + (i & 1)]);
#pragma unroll
  for (int i = 0; i < 4; i++) t[i] = add2(t[(i >> 1) * 4 + (i & 1)], t[(i >> 1) * 4 + 2 + (i & 1)]);
  l0 += (bf_lo(t[0]) + bf_lo(t[2])) + (bf_hi(t[0]) + bf_hi(t[2]));
  l1 += (bf_lo(t[1]) + bf_lo(t[3])) + (bf_hi(t[1]) + bf_hi(t[3]));
}
__device__ __forceinline__ void softmax_redo(uint32_t (&pf)[32], const uint32_t (&q)[32], const __nv_bfloat16* kblk, int lane, float& n0,
                                             float& n1, float& l0, float& l1, float& sc0, float& sc1) {
  float x0 = -n0, x1 = -n1;
#pragma unroll 1
  for (int u = 0; u < 16; u++) {
    const uint32_t* kp = (const uint32_t*)(kblk + ((u & 7) * 16 + (lane >> 2)) * DH) + (lane & 3);
    float d[2][4] = {};
#pragma unroll
    for (int k = 0; k < 16; k++)
      hmma_k16(d[k & 1], q[2 * (k & 14)], q[2 * (k & 14) + 1], q[2 * (k & 14) + 2], q[2 * (k & 14) + 3],
               kp[(k & 1) * 4 * DH + (k >> 1) * 8], kp[(k & 1) * 4 * DH + (k >> 1) * 8 + 4]);
    if (u < 8) {
      x0 = fmaxf(fmaxf(x0, fmaxf(d[0][0], d[0][1])), fmaxf(d[1][0], d[1][1]));
      x1 = fmaxf(fmaxf(x1, fmaxf(d[0][2], d[0][3])), fmaxf(d[1][2], d[1][3]));
      if (u == 7) {
#pragma unroll
        for (int m = 1; m < 4; m <<= 1) {
          x0 = fmaxf(x0, __shfl_xor_sync(0xffffffffu, x0, m));
          x1 = fmaxf(x1, __shfl_xor_sync(0xffffffffu, x1, m));
        }
        sc0 = ex2(-x0 - n0);
        sc1 = ex2(-x1 - n1);
        n0 = -x0;
        n1 = -x1;
        l0 *= sc0;
        l1 *= sc1;
      }
    } else {
#pragma unroll
      for (int i = 0; i < 28; i++) pf[i] = pf[i + 4];
#pragma unroll
      for (int i = 0; i < 4; i++) {
        const float n = (i & 1) ? n1 : n0;
        pf[28 + i] = pack2(ex2(d[i >> 1][(i & 1) * 2] + n), ex2(d[i >> 1][(i & 1) * 2 + 1] + n));
        ((i & 1) ? l1 : l0) += bf_lo(pf[28 + i]) + bf_hi(pf[28 + i]);
      }
    }
  }
}

__device__ __forceinline__ void attn_consumer(const Ctx& cx, int qb, int hs, int wg, int cw, int lane, const __nv_bfloat16* x,
                                              const __nv_bfloat16* kc, __nv_bfloat16* out) {
  const uint32_t full = cx.sb + SM_FULL;
  const uint32_t ring = cx.sb + SM_RING;
  uint32_t lo = ((cw & 3) * 16 + (lane & 15)) * 128 + (((lane >> 4) ^ (lane & 7)) << 4);
  const uint32_t slot = cx.sb + SM_SLOT + wg * 16384;
  auto frag = [&](int sl, int k) { return ((slot + sl * STAGE + lo) ^ ((k & 3) << 5)) + (k >> 2) * 8192; };
  auto park = [&](float (&a)[64], int sl, int k0, int k1, float f0, float f1, bool in_place = false) {
#pragma unroll
    for (int k = 0; k < 8; k++)
      if (k >= k0 && k < k1) {
        float t[8];
#pragma unroll
        for (int i = 0; i < 8; i++) {
          t[i] = a[8 * k + i] * ((i & 2) ? f1 : f0);
          if (in_place) a[8 * k + i] = t[i];
        }
        stsm4(frag(sl, k), pack2(t[0], t[1]), pack2(t[2], t[3]), pack2(t[4], t[5]), pack2(t[6], t[7]));
      }
  };
  const bool signaller = lane == 0 && (cw & 3) < 2;
  int my_turn = 1 + wg, other_turn = 2 - wg;

  uint32_t pf[32], q[32], empty_c;
  float o[64], l0, l1;
  {
    uint32_t xa[144];
    float rstd0, rstd1;
    {
      const uint32_t xb = cx.sb + SM_X + wg * 73728, xf = cx.sb + SM_XFULL + wg * 96;
      float sm[4][4] = {};
      prof(wg, 0);
      if (X_WARM) hmma_k16(sm[0], 0, 0, 0, 0, 0, 0);
      empty_c = mapa(cx.sb + SM_EMPTY, cw & 1);
      mbar_wait(xf, 0);
      if ((threadIdx.x & 127) == 0) profc(wg, 30);
      ln_fetch<0, 12>(xa, xb, lo);
      mbar_wait(xf + 8, 0);
      ln_fetch<12, 24>(xa, xb, lo);
      ln_sums<0, X_S1>(xa, sm);
      mbar_wait(xf + 16, 0);
      if ((threadIdx.x & 127) == 0) profc(wg, 1);
      ln_fetch<24, 36>(xa, xb, lo);
      ln_sums<X_S1, 36>(xa, sm);
      rstd0 = ((sm[0][0] + sm[1][0]) + (sm[2][0] + sm[3][0])) * (1.0f / DM);
      rstd1 = ((sm[0][2] + sm[1][2]) + (sm[2][2] + sm[3][2])) * (1.0f / DM);
    }
    asm volatile("" : "+f"(rstd0), "+f"(rstd1)::"memory");
    block_fence(38);
    if (wg) {
      bar_arrive(other_turn, 256);
      if (X_RS < 0) bar_arrive(BAR_HELPER, 160);
    }
    block_fence(39);
    const uint32_t mm0 = pack2(rstd0, rstd0), mm1 = pack2(rstd1, rstd1);
    rstd0 -= bf_lo(mm0);
    rstd1 -= bf_lo(mm1);
    rstd0 *= rstd0 * (-0.25f * DM);
    rstd1 *= rstd1 * (-0.25f * DM);
    auto ln_finish = [&]() {
      rstd0 += __shfl_xor_sync(0xffffffffu, rstd0, 1); rstd1 += __shfl_xor_sync(0xffffffffu, rstd1, 1);
      rstd0 += __shfl_xor_sync(0xffffffffu, rstd0, 2); rstd1 += __shfl_xor_sync(0xffffffffu, rstd1, 2);
      rstd0 = ln_rstd(rstd0 * (1.0f / DM)) * SM_SCALE_LOG2;
      rstd1 = ln_rstd(rstd1 * (1.0f / DM)) * SM_SCALE_LOG2;
    };
    ln_centre(xa, 0, X_C0, mm0, mm1, rstd0, rstd1);
    if (wg == 0) {
      bar_sync(4, 128);
      if (signaller) {
        asm volatile("mbarrier.arrive.shared::cluster.b64 _, [%0], 2;" ::"r"(empty_c + 16) : "memory");
        asm volatile("mbarrier.arrive.shared::cluster.b64 _, [%0], 2;" ::"r"(empty_c + 24) : "memory");
      }
      block_fence(37);
      pin(xa);
      ln_centre(xa, X_C0, X_CA == 1 ? X_C1 : X_C2, mm0, mm1, rstd0, rstd1);
    }
    pin(xa);
    if ((threadIdx.x & 127) == 0) profc(wg, 2);

    extern __shared__ __align__(1024) uint8_t smem_q[];
    const uint32_t ring = smem_u32(smem_q) + SM_RING;
    auto release = [&](int st) { if (signaller) mbar_arrive_cluster(empty_c + 8 * (st & 3)); };
    auto q_stage = [&](float (&acc)[64], int st, int i, int last) {
      mbar_wait(full + 8 * (st & 3), (st >> 2) & 1);
      if (i != (wg ? last : 1)) bar_sync(my_turn, 256);
      wg_fence();
      const uint64_t db = mkdesc(ring + (st & 3) * STAGE, 16384);
#pragma unroll
      for (int k = 0; k < 8; k++) {
        const int kb = (i < 3 ? 8 * i : 8 * i - 4) + k;
        if (i != 2 || k < 4) mma_n128<1>(acc, xa[4 * kb], xa[4 * kb + 1], xa[4 * kb + 2], xa[4 * kb + 3], db + k * 128, kb > 0);
      }
      wg_commit();
      if (i != (wg ? last - 1 : 0)) bar_arrive(other_turn, 256);
    };
    auto q_release = [&](int st, int i, int last) {
      if (i == 1 || i == last) {
        wg_wait<1>();
        if (i == last || !wg) release(st - 1);
      }
      if (i != last - 1 && (i || wg)) {
        wg_wait<0>();
        release(st);
      }
    };
    {
      float (&acc)[64] = o;
#pragma unroll 1
      for (int p = 0; p < 2; p++) {
#pragma unroll
        for (int i = 0; i < 5; i++) {
          q_stage(acc, 5 * p + i, i, 4);
          if (p == 0 && i <= X_FIN) {
            if (i == X_RS && wg) bar_arrive(BAR_HELPER, 160);
            if ((wg || i >= X_CA) && i < 4)
              ln_centre(xa, i == 0 ? X_C0 : i == 1 ? X_C1 : i == 2 ? X_C2 : X_C3, i == 0 ? X_C1 : i == 1 ? X_C2 : i == 2 ? X_C3 : 72, mm0, mm1, rstd0, rstd1);
            if (i == X_FIN) ln_finish();
            pin(xa);
          }
          q_release(5 * p + i, i, 4);
        }
        pin(acc);
#pragma unroll
        for (int k = 0; k < 8; k += X_QP) {
          park(acc, p, k, k + X_QP, rstd0, rstd1);
          if (k + X_QP < 8) block_fence(40 + k);
        }
      }
    }
    {
      float (&h)[32] = *(float (*)[32])&o[0];
#pragma unroll
      for (int i = 0; i < 3; i++) {
        const uint32_t sl = (10 + i) & 3;
        mbar_wait(full + 8 * sl, ((10 + i) >> 2) & 1);
        if (X_HT ? i != (wg ? 2 : 1) : i == 0) bar_sync(my_turn, 256);
        wg_fence();
#pragma unroll
        for (int k = 0; k < 16 - 4 * i; k++) {
          const int kb = (i == 2 ? 28 : 16 * i) + k;
          const uint64_t db = mkdesc(ring + sl * STAGE, 16) + (i == 2 && k >= 4 ? k + 4 : k) * 128;
          mma_n64<1>(h, xa[4 * kb], xa[4 * kb + 1], xa[4 * kb + 2], xa[4 * kb + 3], db, kb > 0);
        }
        wg_commit();
        if (X_HT ? i != (wg ? 1 : 0) : i == 2) bar_arrive(other_turn, 256);
        if (X_HT) {
          q_release(10 + i, i, 2);
        } else if (i) {
          wg_wait<1>();
          release(9 + i);
          if (i == 2) {
            wg_wait<0>();
            release(12);
          }
        }
      }
      pin(h);
#pragma unroll
      for (int k = 0; k < 4; k++) {
        stsm4(frag(2, k), pack2(h[8 * k] * rstd0, h[8 * k + 1] * rstd0), pack2(h[8 * k + 2] * rstd1, h[8 * k + 3] * rstd1),
              pack2(h[8 * k + 4] * rstd0, h[8 * k + 5] * rstd0), pack2(h[8 * k + 6] * rstd1, h[8 * k + 7] * rstd1));
        if (k == 1) block_fence(49);
      }
    }
#pragma unroll
    for (int i = 0; i < 4; i++) {
      q_stage(o, 13 + i, i, 3);
      q_release(13 + i, i, 3);
    }
    prof(wg, 6);
#pragma unroll
    for (int i = 0; i < 32; i++) pf[i] = xa[112 + i];
    l0 = 0.25f * rcp(rstd0);
    l1 = 0.25f * rcp(rstd1);
  }

  uint32_t oa[96];
  const uint32_t zero = __shfl_sync(0xffffffffu, blockIdx.y, lane);
  my_turn = __shfl_sync(0xffffffffu, my_turn, lane);
  other_turn = __shfl_sync(0xffffffffu, other_turn, lane);
  lo = __shfl_sync(0xffffffffu, lo, lane);
  {
    float s[64], n0 = 0.f, n1 = 0.f;
    float lp0, lp1;
    float i0 = 0.f, i1 = 0.f;
    bool redo, shift = false;
    auto turn = [&](int it, auto kc_) -> bool {
      constexpr int KIND = decltype(kc_)::value;
      constexpr uint32_t slk = KIND == 1 ? SL_KO : SL_KE, slv = KIND == 1 ? SL_VO : SL_VE, slkn = KIND == 1 ? SL_KE : SL_KO;
      constexpr int SPLIT = X_SPLIT, PARK1 = X_PARK;
      const uint32_t par = ((it + NST_Q / 2) >> 1) & 1;
      const int hsl = max((it >> 4) - 1, 0);
      const uint64_t dk = mkdesc(ring + slk * STAGE, 16), dv = mkdesc(ring + slv * STAGE, 16384);
      auto qk = [&]() {
#pragma unroll
        for (int k = 0; k < 8; k++) {
          if (KIND == 3) mma_n128_ss<0>(s, mkdesc(slot + hsl * STAGE, 16) + (k >> 2) * 512 + (k & 3) * 2, dk + (k >> 2) * 1024 + (k & 3) * 2, k > 0);
          else mma_n128<0>(s, q[4 * k], q[4 * k + 1], q[4 * k + 2], q[4 * k + 3], dk + (k >> 2) * 1024 + (k & 3) * 2, k > 0);
        }
        wg_commit();
      };
      auto pv = [&]() {
#pragma unroll
        for (int k = 0; k < 8; k++)
          mma_n128<1>(o, pf[4 * k], pf[4 * k + 1], pf[4 * k + 2], pf[4 * k + 3], dv + k * 128, k > 0 || KIND != 1 || (it & 15) != 1);
        wg_commit();
      };
      lp0 = l0; lp1 = l1;
#define TS(i)
      {
        TS(0)
        if (KIND == 3) {
          asm volatile("fence.proxy.async.shared::cta;" ::: "memory");
          const float t0 = lp0 + __shfl_xor_sync(0xffffffffu, lp0, 1), t1 = lp1 + __shfl_xor_sync(0xffffffffu, lp1, 1);
          i0 = rcp(t0 + __shfl_xor_sync(0xffffffffu, t0, 2));
          i1 = rcp(t1 + __shfl_xor_sync(0xffffffffu, t1, 2));
          asm volatile("" : "+f"(i0), "+f"(i1)::"memory");
          block_fence(31, zero);
#pragma unroll
          for (int k = 0; k < X_N1; k++) ldsm4(frag(hsl, k), q[4 * k], q[4 * k + 1], q[4 * k + 2], q[4 * k + 3]);
        }
        bar_sync(my_turn, 256);
        TS(1)
        if (KIND != 3) pin(q);
        pin(pf); pin(o);
        wg_fence();
        qk();
        TS(2)
        mbar_wait(full + 8 * slv, par);
        if (KIND == 1 && (it & 15) == 1) {
          park(o, hsl, PARK1, 8, i0, i1);
          wg_fence();
        }
        if (KIND == 3) {
#pragma unroll
          for (int k = X_N1; k < 8; k++) ldsm4(frag(hsl, k), q[4 * k], q[4 * k + 1], q[4 * k + 2], q[4 * k + 3]);
          block_fence(32, zero);
        }
        TS(3)
        pv();
        bar_arrive(other_turn, 256);
        TS(4)
        wg_wait<1>();
      }
      pin(s);
      mbar_arrive_cluster_now<10 * KIND + 3>(empty_c + 8 * slk, signaller, zero);
      TS(5)
      if (KIND == 3) {
        shift = false;
        n0 = n1 = l0 = l1 = 0.f;
      } else if (shift) {
        softmax_shift(s, n0, n1);
        pin(s);
      }
      softmax_exp<0, SPLIT>(s);
      pin(s);
      block_fence(10 * KIND + 4, zero);
      TS(6)
      wg_wait<0>();
      pin(o); pin(pf);
      mbar_arrive_cluster_now<10 * KIND + 5>(empty_c + 8 * slv, signaller, zero);
      TS(7)
      const bool kready = mbar_test(full + 8 * slkn, par);
      softmax_exp<SPLIT, 64>(s);
#pragma unroll
      for (int i = 0; i < 32; i++) pf[i] = pack2(s[2 * i], s[2 * i + 1]);
      row_sums(pf, l0, l1);
      if (KIND == 3) {
        park(o, hsl, 0, PARK1, i0, i1, X_IP);
        if (it) prof(wg, 6 + (it >> 4));
        if (it >= 32 && cw == 0) bar_arrive(BAR_HELPER, 64);
      }
      redo = !(l0 + l1 <= SUM_HI) || (KIND == 3 && fminf(l0, l1) < SUM_LO);
      const bool leave = __any_sync(0xffffffffu, redo || !kready);
      return leave;
    };
    int it = -1;
#pragma unroll 1
    while (true) {
      mbar_wait(full + 8 * ((it & 1) ? SL_KE : SL_KO), ((it + NST_Q / 2) >> 1) & 1);
      it++;
#pragma unroll 1
      while (true) {
        if (it & 1) {
          if (turn(it, IC<1>()) || it == 63) break;
          it++;
        }
        if (it & 15) {
          if (turn(it, IC<2>())) break;
        } else {
          if (turn(it, IC<3>())) break;
        }
        it++;
      }
      if (__any_sync(0xffffffffu, redo)) {
        const int j = it & 15;
        float sc0 = 1.f, sc1 = 1.f;
        if (j == 0) n0 = n1 = 3.0e38f;
        l0 = j ? lp0 : 0.f;
        l1 = j ? lp1 : 0.f;
        softmax_redo(pf, q, kc + (size_t)((hs * 2 + (it >> 5)) * SEQ + j * 128) * DH, lane, n0, n1, l0, l1, sc0, sc1);
        shift = true;
        if (j == 0) sc0 = sc1 = 1.f;
#pragma unroll
        for (int i = 0; i < 16; i++) { o[4 * i] *= sc0; o[4 * i + 1] *= sc0; o[4 * i + 2] *= sc1; o[4 * i + 3] *= sc1; }
      }
      if (it == 63) break;
    }
  }

#define TE(i) {}
  {
    constexpr int ST0 = NST_Q + NST_KV;
    float acc[32], red[32], first[32];
    auto await = [&](int st) { mbar_wait(full + 8 * (st & 3), (st >> 2) & 1); };
    auto release = [&](int st) { if (signaller) mbar_arrive_cluster(empty_c + 8 * (st & 3)); };
    auto unpark = [&](int h, int k0, int k1) {
#pragma unroll
      for (int k = 0; k < 8; k++)
        if (k >= k0 && k < k1) ldsm4(frag(h, k), oa[32 * h + 4 * k], oa[32 * h + 4 * k + 1], oa[32 * h + 4 * k + 2], oa[32 * h + 4 * k + 3]);
    };
    {
      float ar[64];
      asm volatile("fence.proxy.async.shared::cta;" ::: "memory");
      l0 += __shfl_xor_sync(0xffffffffu, l0, 1); l1 += __shfl_xor_sync(0xffffffffu, l1, 1);
      l0 += __shfl_xor_sync(0xffffffffu, l0, 2); l1 += __shfl_xor_sync(0xffffffffu, l1, 2);
      float f0 = rcp(l0), f1 = rcp(l1);
      asm volatile("" : "+f"(f0), "+f"(f1)::"memory");
      await(ST0 - 1);
      unpark(1, 0, 4);
      bar_sync(my_turn, 256);
      pin(pf); pin(o);
      wg_fence();
#pragma unroll
      for (int k = 0; k < 8; k++)
        mma_n128<1>(o, pf[4 * k], pf[4 * k + 1], pf[4 * k + 2], pf[4 * k + 3], mkdesc(ring + SL_KE * STAGE, 16384) + k * 128, 1);
      wg_commit();
      await(ST0);
      unpark(1, 4, 8);
      block_fence(61, zero);
#pragma unroll
      for (int k = 0; k < 8; k++) mma_n128_ss<1>(ar, mkdesc(slot, 16) + (k >> 2) * 512 + (k & 3) * 2, mkdesc(ring + (ST0 & 3) * STAGE, 16384) + k * 128, k > 0);
      wg_commit();
      bar_arrive(other_turn, 256);
      wg_wait<1>();
      pin(o); pin(pf);
      mbar_arrive_cluster_now<62>(empty_c + 8 * SL_KE, signaller, zero);
#pragma unroll
      for (int i = 0; i < 16; i++) {
        pf[2 * i] = pack2(o[4 * i] * f0, o[4 * i + 1] * f0);
        pf[2 * i + 1] = pack2(o[4 * i + 2] * f1, o[4 * i + 3] * f1);
      }
      pin(pf);
      prof(wg, 10);
#pragma unroll
      for (int u = 1; u < 4; u++) {
        await(ST0 + u);
        wg_wait<0>();
        release(ST0 + u - 1);
        bar_sync(my_turn, 256);
        wg_fence();
#pragma unroll
        for (int k = 0; k < 8; k++) {
          const uint32_t* a = (u == 1 ? oa + 32 : u == 2 ? pf : oa + 64) + 4 * k;
          mma_n128<1>(ar, a[0], a[1], a[2], a[3], mkdesc(ring + ((ST0 + u) & 3) * STAGE, 16384) + k * 128, 1);
        }
        wg_commit();
        bar_arrive(other_turn, 256);
        if (u < 3) {
          block_fence(62 + u, zero);
          unpark(u == 1 ? 2 : 0, 0, 8);
        }
      }
      mbar_wait(cx.sb + SM_BAR_MISC, 0);
      await(ST0 + 4);
      wg_wait<0>();
      release(ST0 + 3);
      pin(ar);
#pragma unroll
      for (int i = 0; i < 32; i++) { first[i] = ar[i]; red[i] = ar[32 + i]; }
    }
    const uint32_t tag = *(const uint32_t*)(cx.sp + SM_TAG);
    uint4* const xch = at<uint4>(cx.gs->part, (qb << 20) + lane * 16);
    auto send = [&](const float (&v)[32], int dst, int idx) {
      uint4* p = at<uint4>(xch, (dst * 8 + idx) * 2048);
#pragma unroll
      for (int i = 0; i < 4; i++)
        st_gran(p + i * 32, (pack2(v[8 * i], v[8 * i + 1]) & ~TAG_BIT) | tag, pack2(v[8 * i + 2], v[8 * i + 3]),
                pack2(v[8 * i + 4], v[8 * i + 5]), pack2(v[8 * i + 6], v[8 * i + 7]));
    };
    send(first, ((hs + 1) & 7) * 7, cw);
    int nrx = 1;
    auto half_step = [&](int s, auto hc, bool arrive) {
      constexpr int h = decltype(hc)::value;
      const int st = ST0 + 2 * s + h;
      const uint64_t db = mkdesc(ring + (st & 3) * STAGE, 16);
      bar_sync(my_turn, 256);
      if (h == 0) pin(pf);
#pragma unroll
      for (int i = 32 * h; i < 32 + 64 * h; i++) asm volatile("" : "+r"(oa[i])::"memory");
      wg_fence();
#pragma unroll
      for (int k = 0; k < 16; k++) {
        const int kb = h * 16 + k - 8;
        if (kb >= 0) mma_n64<1>(acc, oa[4 * kb], oa[4 * kb + 1], oa[4 * kb + 2], oa[4 * kb + 3], db + k * 128, 1);
        else mma_n64<1>(acc, pf[4 * k], pf[4 * k + 1], pf[4 * k + 2], pf[4 * k + 3], db + k * 128, k > 0);
      }
      wg_commit();
      if (arrive) bar_arrive(other_turn, 256);
    };
    auto source = [&](int n) { return at<const uint4>(xch, ((hs * 7 + n - 1) * 8 + cw) * 2048); };
    auto fetch = [&](uint32_t (&g)[16], const uint4* p) {
#pragma unroll
      for (int i = 0; i < 4; i++) ld_gran(p + i * 32, g[4 * i], g[4 * i + 1], g[4 * i + 2], g[4 * i + 3]);
    };
    uint32_t g[16];
#pragma unroll 1
    for (int s = 2; s < 8; s++) {
      const int st = ST0 + 2 * s;
      half_step(s, IC<0>(), true);
      if (s == 2) {
        bar_arrive(BAR_OA, 352);
        send(red, 56 + cw, hs);
#pragma unroll
        for (int i = 0; i < 32; i++) red[i] = 0.f;
      }
      await(st + 1);
      if (s > 3 && granules_ok(g, tag)) { add_granules(red, g); nrx++; }
      if (X_XS == 1 && s > 2) fetch(g, source(nrx));
      wg_wait<0>();
      if (s < 7) release(st);
      if (X_XS == 0 && s > 2) fetch(g, source(nrx));
      half_step(s, IC<1>(), true);
      await(st + 2);
      wg_wait<0>();
      if (s < 7) release(st + 1);
      pin(acc);
      if (s == 7) prof(wg, 19);
      if (s == 7) TE(0)
      send(acc, ((hs + s) & 7) * 7 + s - 1, cw);
    }
    TE(1)
    uint32_t xv[16], gt[16];
    {
      const int s = 8;
      uint32_t g2[16];
      half_step(s, IC<0>(), true);
      TE(2)
      await(NST_Q + NST_KV + NST_O - 1);
      cluster_arrive();
      mbar_wait(cx.sb + SM_BAR_XG, 0);
      const uint32_t tile = cx.sb + SM_XO + wg * 8192 + lo;
      if (granules_ok(g, tag)) { add_granules(red, g); nrx++; }
      fetch(g, source(nrx));
      block_fence(58, zero);
      wg_wait<0>();
      TE(3)
#pragma unroll
      for (int k = 0; k < 4; k++) ldsm4((tile ^ (k << 5)) + STAGE, gt[4 * k], gt[4 * k + 1], gt[4 * k + 2], gt[4 * k + 3]);
      half_step(s, IC<1>(), wg == 0);
      TE(4)
      block_fence(56, zero);
      const bool ok = granules_ok(g, tag);
      block_fence(57, zero + ok * 1000);
      const uint4* src = source(7);
      fetch(g2, src);
#pragma unroll
      for (int k = 0; k < 4; k++) ldsm4(tile ^ (k << 5), xv[4 * k], xv[4 * k + 1], xv[4 * k + 2], xv[4 * k + 3]);
      if (ok) { add_granules(red, g); nrx++; }
      TE(5)
      block_fence(59, zero);
      wg_wait<0>();
      pin(acc);
      TE(6)
#pragma unroll
      for (int i = 0; i < 32; i++) red[i] += acc[i];
      pin(red);
      TE(7)
      int n = 7;
#pragma unroll 1
      for (int spins = 0; spins < (1 << 16); spins++) {
        if (granules_ok(g2, tag)) {
          add_granules(red, g2);
          if (--n < nrx) {
            break;
          }
          src -= 1024;
        }
        fetch(g2, src);
      }
      TE(8)
    }
    prof(wg, 20);
    TE(9)
    const uint32_t ot = ring + ((ST0 + NST_O) & 3) * STAGE + cw * (16 * 144);
    uint32_t ow[16];
#pragma unroll
    for (int i = 0; i < 16; i++) ow[i] = fma2(pack2(red[2 * i], red[2 * i + 1]), gt[i], xv[i]);
#pragma unroll
    for (int i = 0; i < 4; i++)
      stsm4(ot + (lane & 15) * 144 + (2 * i + (lane >> 4)) * 16, ow[4 * i], ow[4 * i + 1], ow[4 * i + 2], ow[4 * i + 3]);
    __syncwarp();
#pragma unroll
    for (int i = 0; i < 4; i++) {
      uint4 v;
      lds128(ot + (i * 4 + (lane >> 3)) * 144 + (lane & 7) * 16, v.x, v.y, v.z, v.w);
      at<uint4>(out, ((qb * 128 + cw * 16 + (lane >> 3)) * DM + hs * 64 + (lane & 7) * 8) * 2)[i * (4 * DM / 8)] = v;
    }
    TE(10)
    prof(wg, 22);
  }
}

constexpr int AST_X = 6, AST_F = AST_X + 96;
__device__ __forceinline__ void aux_producer(const Ctx& cx, int f, const CUtensorMap* tmWq, const CUtensorMap* tmG) {
  const uint32_t full = cx.sb + SM_FULL, empty = cx.sb + SM_EMPTY;
  if (elect_one()) {
#pragma unroll 1
    for (int st = 0; st < AST_X; st++) {
      mbar_expect_tx(full + 8 * st, FSTAGE);
#pragma unroll
      for (int i = 0; i < 3; i++)
        tma2d_stream(cx.sb + st * FSTAGE + i * 8192, tmWq, (2 * f + (st & 1)) * 512 + 448, (st >> 1) * 192 + i * 64, full + 8 * st);
    }
  }
  __syncwarp();
  mbar_wait(cx.sb + SM_BAR_MISC, 0);
  proxy_fence();
  int st = AST_X;
#pragma unroll 1
  for (; st < AST_F; st++) {
    const uint32_t sl = st & 7;
    mbar_wait(empty + 8 * sl, ((st >> 3) & 1) ^ 1);
    if (elect_one()) {
      mbar_expect_tx(full + 8 * sl, FSTAGE);
      bulk_load(cx.sb + sl * FSTAGE, cx.gs->xn + (st - AST_X) * (FSTAGE / 16), FSTAGE, full + 8 * sl);
    }
    __syncwarp();
  }
#pragma unroll 1
  for (int pair = 0; pair < 14; pair++) {
#pragma unroll 1
    for (int u = 0; u < 12; u++, st++) {
      const uint32_t sl = st & 7;
      const int unit = pair * 2 + (u & 1), k = u >> 1;
      if (unit == 27) continue;
      const bool gu = pair < 9;
      mbar_wait(empty + 8 * sl, ((st >> 3) & 1) ^ 1);
      if (elect_one()) {
        mbar_expect_tx(full + 8 * sl, FSTAGE);
        tma2d_stream(cx.sb + sl * FSTAGE, tmG + (gu ? k >= 3 : 2), gu ? f * 1152 + unit * 64 : (unit - 18) * 64,
                     gu ? (k >= 3 ? k - 3 : k) * 192 : f * 1152 + k * 192, full + 8 * sl);
      }
      __syncwarp();
    }
  }
}

constexpr int BAR_FREE = 4, BAR_TILE = 6;
__device__ __forceinline__ void aux_helper(const Ctx& cx, int f, int warp, int lane) {
  unsigned epoch = 0;
  if (lane == 0) epoch = cx.gs->launch[blockIdx.x] + 1;
  epoch = __shfl_sync(0xffffffffu, epoch, 0);
  bar_sync(BAR_OA, 96);
  if (warp == 3) {
    if (lane == 0) cx.gs->launch[blockIdx.x] = epoch;
    await_count(at<const unsigned>(cx.gs->rows, (lane & 15) * 128), 8 * epoch, 200);
    if (lane == 0) mbar_arrive(cx.sb + SM_BAR_MISC);
    prof(0, 1, 31);
    await_count(at<const unsigned>(cx.gs->rows, (lane & 15) * 128 + 4), 8 * epoch, 500);
    uint32_t bound = 0xFFFFFFFFu, m0 = 0, m1 = 0;
#pragma unroll 1
    for (int k = 0; k < TOPC; k++) {
      if (__any_sync(0xffffffffu, m0 == 0)) {
        m0 = m1 = 0;
#pragma unroll 2
        for (int i = 0; i < 16; i++) {
          const uint4 v = __ldcg(at<const uint4>(cx.gs->key, lane * 16 + i * 512));
          const uint32_t w[4] = {v.x, v.y, v.z, v.w};
#pragma unroll
          for (int j = 0; j < 4; j++) {
            const uint32_t t = w[j] <= bound ? w[j] : 0;
            m1 = max(m1, min(m0, t));
            m0 = max(m0, t);
          }
        }
      }
      uint32_t m = m0;
      m = __reduce_max_sync(0xffffffffu, m);
      bound = m - 1;
      if (m0 == m) { m0 = m1; m1 = 0; }
      if (f == 0 && lane == 0) *at<uint32_t>(cx.gs->top, k * 4) = m;
#pragma unroll
      for (int j = 0; j < 3; j++) {
        const uint32_t row = 0xFFFF - (m & 0xFFFF), i = min(j * 4 + (lane >> 3), 8);
        *(uint4*)(cx.sp + SM_XSEL + i * 1024 + k * 128 + (((lane ^ k) & 7) << 4)) =
            __ldcg(at<const uint4>(cx.gs->xn, xn_offset(row, (lane & 7) * 4) + i * 8192));
      }
    }
    asm volatile("fence.proxy.async.shared::cta;" ::: "memory");
    prof(0, 2, 31);
  } else {
    const int wg = warp - 1;
#pragma unroll 1
    for (int u = 0; u < 32; u++) {
      bar_arrive(BAR_FREE + wg, 160);
      bar_sync(BAR_TILE + wg, 160);
      if (elect_one()) {
        const int n = (u >> 1) * 8 + 2 * f + wg;
        asm volatile("cp.async.bulk.global.shared::cta.bulk_group [%0], [%1], 8192;\ncp.async.bulk.commit_group;\ncp.async.bulk.wait_group 0;"
                     ::"l"(cx.gs->q3 + (n * 2 + (u & 1)) * 512), "r"(cx.sb + SM_H + wg * 8192) : "memory");
        if (u & 1) st_release(&cx.gs->q3_flag[n], epoch);
      }
      __syncwarp();
    }
  }
  bar_arrive(3, 352);
}

__device__ __forceinline__ void aux_consumer(const Ctx& cx, int f, int wg, int cw, int lane) {
  const int r = lane >> 2, c = lane & 3, tid = cw * 32 + lane;
  const uint32_t full = cx.sb + SM_FULL, empty = cx.sb + SM_EMPTY;
  const bool signaller = (tid & 127) == 0;
  auto await = [&](int st) { mbar_wait(full + 8 * (st & 7), (st >> 3) & 1); };
  auto release = [&](int st, int cnt) {
    asm volatile("{\n.reg .pred p;\nsetp.ne.u32 p, %2, 0;\n@p mbarrier.arrive.shared::cta.b64 _, [%0], %1;\n}"
                 ::"r"(empty + 8 * (st & 7)), "r"(cnt), "r"((uint32_t)signaller) : "memory");
  };
  prof(wg, 0);
  {
    const uint32_t lt = ((lane & 7) + (lane >> 4) * 8) * 128 + ((((cw & 3) * 2 + ((lane >> 3) & 1)) ^ (lane & 7)) << 4);
    uint32_t wa[144];
#pragma unroll
    for (int i = 0; i < 3; i++) {
      await(2 * i + wg);
#pragma unroll
      for (int k = 0; k < 12; k++) {
        const int kb = 12 * i + k;
        ldsm4t(cx.sb + (2 * i + wg) * FSTAGE + k * 2048 + lt, wa[4 * kb], wa[4 * kb + 1], wa[4 * kb + 2], wa[4 * kb + 3]);
      }
    }
    bar_sync(1, 256);
#pragma unroll
    for (int i = 0; i < 3; i++) release(2 * i + wg, 2);
    if (wg) bar_arrive(1, 256);
#pragma unroll 1
    for (int st = AST_X; st < AST_F; st += 3) {
      float acc[32];
      await(st);
      await(st + 1);
      await(st + 2);
      bar_sync(1 + wg, 256);
      wg_fence();
#pragma unroll
      for (int kb = 0; kb < 36; kb++) {
        const int i = kb / 12, k = kb % 12;
        mma_n64<0>(acc, wa[4 * kb], wa[4 * kb + 1], wa[4 * kb + 2], wa[4 * kb + 3],
                   mkdesc(cx.sb + ((st + i) & 7) * FSTAGE, 16) + (k >> 2) * 512 + (k & 3) * 2, kb > 0);
        if (k == 11) wg_commit();
      }
      if (st < AST_F - 3 || !wg) bar_arrive(2 - wg, 256);
      wg_wait<1>();
      release(st, 1);
      release(st + 1, 1);
      bar_sync(BAR_FREE + wg, 160);
      wg_wait<0>();
      pin(acc);
      release(st + 2, 1);
#pragma unroll
      for (int k = 0; k < 4; k++)
        stsm4t(cx.sb + SM_H + wg * 8192 + k * 2048 + lt, pack2(acc[8 * k] * SM_SCALE_LOG2, acc[8 * k + 1] * SM_SCALE_LOG2),
               pack2(acc[8 * k + 2] * SM_SCALE_LOG2, acc[8 * k + 3] * SM_SCALE_LOG2),
               pack2(acc[8 * k + 4] * SM_SCALE_LOG2, acc[8 * k + 5] * SM_SCALE_LOG2),
               pack2(acc[8 * k + 6] * SM_SCALE_LOG2, acc[8 * k + 7] * SM_SCALE_LOG2));
      asm volatile("fence.proxy.async.shared::cta;" ::: "memory");
      bar_arrive(BAR_TILE + wg, 160);
    }
    bar_sync(3, 352);
  }
  prof(wg, 3);
#pragma unroll 1
  for (int unit = wg; unit < 27; unit += 2) {
    if (unit >> 1 == 9) {
      asm volatile("fence.proxy.async.shared::cta;" ::: "memory");
      bar_sync(3, 256);
      prof(wg, 4);
    }
    const bool gu = unit < 18;
    float a0[4], a1[4];
#pragma unroll 1
    for (int m = 0; m < 2; m++) {
      float p0[4], p1[4];
      int st = AST_F + (unit >> 1) * 12 + m * 6 + wg;
      uint32_t b = cx.sb + (gu ? SM_XSEL : SM_H + m * 9216);
#pragma unroll 1
      for (int u = 0; u < 3; u++, st += 2, b += 3072) {
        await(st);
        wg_fence();
        const uint64_t da = mkdesc(cx.sb + (st & 7) * FSTAGE, 16), db = mkdesc(b, 16);
#pragma unroll
        for (int k = 0; k < 12; k++) mma_n8((k & 1) ? p1 : p0, da + k * 128, db + (k >> 2) * 64 + (k & 3) * 2, u > 0 || k > 1);
        wg_commit();
        wg_wait<1>();
        if (u) release(st - 2, 2);
      }
      wg_wait<0>();
      release(st - 2, 2);
      pin(p0); pin(p1);
#pragma unroll
      for (int i = 0; i < 4; i++) { a0[i] = a1[i]; a1[i] = p0[i] + p1[i]; }
    }
#pragma unroll
    for (int i = 0; i < 4; i++) {
      const int fl = (cw & 3) * 16 + r + (i >> 1) * 8, tok = 2 * c + (i & 1);
      if (gu) {
        const float h = bfr(silu_f(bfr(a0[i]))) * bfr(a1[i]);
        *(__nv_bfloat16*)(cx.sp + SM_H + unit * 1024 + tok * 128 + (((fl >> 3) ^ tok) << 4) + (fl & 7) * 2) = __float2bfloat16_rn(h);
      } else {
        *at<float>(cx.gs->ypart, ((f * TOPC + tok) * DM + (unit - 18) * 64 + fl) * 4) = a0[i] + a1[i];
      }
    }
  }
  prof(wg, 5);
  bar_sync(3, 256);
  if (tid == 0) red_release(&cx.gs->ycnt);
  prof(wg, 6);
}

struct Maps { CUtensorMap m[9]; };
__global__ void __cluster_dims__(2, 1, 1) __launch_bounds__(THREADS, 1)
fused_kernel(const __nv_bfloat16* __restrict__ x, const __nv_bfloat16* __restrict__ w_r, const __nv_bfloat16* __restrict__ wq,
             const __nv_bfloat16* __restrict__ wo, __nv_bfloat16* __restrict__ out, Scratch* gs,
             const __grid_constant__ Maps maps, const __nv_bfloat16* __restrict__ kc) {
  const CUtensorMap &tmX = maps.m[0], &tmWq = maps.m[1], &tmK = maps.m[2], &tmV = maps.m[3], &tmWo = maps.m[4];
  extern __shared__ __align__(1024) uint8_t smem_raw[];
  prof(0, 23, 511);
  Ctx cx;
  cx.sb = smem_u32(smem_raw);
  cx.sp = smem_raw;
  cx.gs = gs;
  cx.rank = blockIdx.x & 1;
  const int warp = __shfl_sync(0xffffffffu, threadIdx.x >> 5, 0);
  const int cluster = blockIdx.x >> 1;
  const bool is_ffn = blockIdx.x >= N_ATT_CTA;
  const int c7 = ((cluster - 36) * 37) >> 8;
  const int hs = cluster < 4 ? 4 + cluster : cluster < 36 ? (cluster - 4) >> 3 : 4 + c7;
  const int qb = (cluster < 4 ? 0 : cluster < 36 ? (cluster - 4) & 7 : cluster - 35 - 7 * c7) * 2 + cx.rank;

  extern __shared__ __align__(1024) uint8_t smem_alias[];
  const uint32_t xf = smem_u32(smem_alias) + SM_MISC + warp * 24;
  if (warp == 4 && elect_one()) prefetch_tmap(&tmX);
  if (warp == 6 && !is_ffn && elect_one()) prefetch_l2(x + (size_t)(qb * 128 + hs * 8) * DM, 8 * DM * 2);
  if (elect_one()) {
    const uint32_t cnt = (warp > 4 && warp < 8) ? (is_ffn ? 2 : 4) : 1;
#pragma unroll
    for (int i = 0; i < 3; i++) mbar_init(xf + 8 * i, cnt);
    asm volatile("fence.proxy.async.shared::cta;" ::: "memory");
    asm volatile("fence.mbarrier_init.release.cluster;" ::: "memory");
  }
  __syncwarp();
  cluster_arrive();
  if (warp == 4 && !is_ffn) {
    if (elect_one()) {
      profc(0, 28);
#pragma unroll
      for (int i = 0; i < 3; i++) {
        mbar_expect_tx(xf + 8 * i, 24576);
        tma3d(xf - SM_XFULL + SM_X + i * 24576, &tmX, qb * 128, i * 3, xf + 8 * i);
      }
      profc(0, 29);
    }
  } else if (warp > 7 && elect_one()) {
    prefetch_tmap(&tmX + (is_ffn ? warp - 4 : warp == 8 ? 8 : warp - 8));
  }
  __syncwarp();

  if (warp < 4) {
    asm volatile("setmaxnreg.dec.sync.aligned.u32 24;");
    cluster_wait();
    prof(0, 24, 511);
    if (warp == 0) {
      if (!is_ffn) attn_producer(cx, qb, hs, &tmX, &tmK, &tmV, &tmWq, &tmWo);
      else aux_producer(cx, blockIdx.x - N_ATT_CTA, &tmWq, &maps.m[5]);
      prof(0, 25, 511);
    } else if (!is_ffn) {
      attn_rows(cx, qb, hs, 3 - warp, read_lane(), &maps.m[8], w_r);
      if (warp == 1) attn_helper(cx, qb, hs, read_lane(), wo, &maps.m[8]);
      else bar_sync(BAR_OA, 352);
      attn_finish8(cx, qb, hs, warp - 1, read_lane(), out);
    } else {
      aux_helper(cx, blockIdx.x - N_ATT_CTA, warp, read_lane());
    }
    __syncwarp();
    cluster_arrive();
    cluster_wait();
    if (threadIdx.x == 32) { dly(cx, 201); dly(cx, 251); }
  } else {
    asm volatile("setmaxnreg.inc.sync.aligned.u32 240;");
    cluster_wait();
    const int cw = warp - 4, wg = cw >> 2;
    if (is_ffn) aux_consumer(cx, blockIdx.x - N_ATT_CTA, wg, cw, read_lane());
    else attn_consumer(cx, qb, hs, wg, cw, read_lane(), x, kc, out);
  }
}

typedef CUresult (*EncodeFn)(CUtensorMap*, CUtensorMapDataType, cuuint32_t, void*, const cuuint64_t*, const cuuint64_t*,
                             const cuuint32_t*, const cuuint32_t*, CUtensorMapInterleave, CUtensorMapSwizzle,
                             CUtensorMapL2promotion, CUtensorMapFloatOOBfill);

void encode(EncodeFn fn, CUtensorMap* m, const void* p, int rank, const cuuint64_t* dims, const cuuint64_t* strides,
            const cuuint32_t* box) {
  const cuuint32_t es[5] = {1, 1, 1, 1, 1};
  fn(m, CU_TENSOR_MAP_DATA_TYPE_BFLOAT16, rank, const_cast<void*>(p), dims, strides, box, es, CU_TENSOR_MAP_INTERLEAVE_NONE,
     CU_TENSOR_MAP_SWIZZLE_128B, CU_TENSOR_MAP_L2_PROMOTION_L2_128B, CU_TENSOR_MAP_FLOAT_OOB_FILL_NONE);
}
void encode2d(EncodeFn fn, CUtensorMap* m, const void* p, uint64_t rows, uint64_t cols, uint32_t box_rows) {
  const cuuint64_t dims[2] = {cols, rows}, strides[1] = {cols * 2};
  const cuuint32_t box[2] = {64, box_rows};
  encode(fn, m, p, 2, dims, strides, box);
}

}

extern "C" void kernel_launch(void* const* d_in, const int* in_sizes, int n_in, void* d_out, int out_size) {
  (void)in_sizes; (void)n_in; (void)out_size;
  void* fnp = nullptr;
  cudaDriverEntryPointQueryResult qr;
  cudaGetDriverEntryPoint("cuTensorMapEncodeTiled", &fnp, cudaEnableDefault, &qr);
  EncodeFn fn = (EncodeFn)fnp;
  void* gs = nullptr;
  cudaGetSymbolAddress(&gs, g_scratch);
  Maps maps;
  CUtensorMap &tmX = maps.m[0], &tmWq = maps.m[1], &tmK = maps.m[2], &tmV = maps.m[3], &tmWo = maps.m[4], &tmG = maps.m[5],
              &tmU = maps.m[6], &tmD = maps.m[7];
  encode2d(fn, &tmK, d_in[1], 16 * SEQ, DH, 128);
  encode2d(fn, &tmV, d_in[2], 16 * SEQ, DH, 128);
  encode2d(fn, &tmWq, d_in[3], DM, 4096, 64);
  {
    const cuuint64_t dims[3] = {64, SEQ, 9}, strides[2] = {DM * 2, 128};
    const cuuint32_t box[3] = {64, 64, 3};
    encode(fn, &tmX, d_in[0], 3, dims, strides, box);
  }
  encode2d(fn, &maps.m[8], d_in[0], SEQ, DM, 16);
  encode2d(fn, &tmWo, d_in[4], 4096, DM, 128);
  encode2d(fn, &tmG, d_in[7], DM, FF, 192);
  encode2d(fn, &tmU, d_in[8], DM, FF, 192);
  encode2d(fn, &tmD, d_in[9], FF, DM, 192);
  cudaFuncSetAttribute(fused_kernel, cudaFuncAttributeMaxDynamicSharedMemorySize, SM_TOTAL);
  fused_kernel<<<N_CTA, THREADS, SM_TOTAL>>>((const __nv_bfloat16*)d_in[0], (const __nv_bfloat16*)d_in[6], (const __nv_bfloat16*)d_in[3],
                                            (const __nv_bfloat16*)d_in[4], (__nv_bfloat16*)d_out, (Scratch*)gs, maps, (const __nv_bfloat16*)d_in[1]);
}
```

```cpp
#include <cuda_runtime.h>
#include <cuda_bf16.h>
#include <cuda.h>
#include <stdint.h>

namespace {

constexpr int SEQ = 2048, DM = 576, DH = 128, FF = 4608, TOPC = 8;
constexpr int N_ATT_CTA = 128, N_CTA = 132;
constexpr int THREADS = 384;

constexpr uint32_t SM_RING = 0;
constexpr uint32_t STAGE = 32768;
constexpr uint32_t SM_SLOT = 131072;
constexpr uint32_t FSTAGE = 24576;
constexpr uint32_t SM_XSEL = 196608;
constexpr uint32_t SM_H = 205824;
constexpr uint32_t SM_MISC = 229376;
constexpr uint32_t SM_FULL = SM_MISC, SM_BAR_MISC = SM_MISC + 64, SM_BAR_XG = SM_MISC + 72, SM_BAR_P8 = SM_MISC + 80, SM_BAR_Q3 = SM_MISC + 88, SM_XFULL = SM_MISC + 96,
                   SM_EMPTY = SM_MISC + 120, SM_BAR_ROWS = SM_MISC + 216, SM_TAG = SM_MISC + 288,
                   SM_ROWS = SM_MISC + 304, SM_BOX8 = SM_MISC + 1024;
constexpr uint32_t SM_TOTAL = SM_MISC + 3072;
constexpr uint32_t SM_X = SM_MISC - 147456;

constexpr int BAR_ROWS = 6, BAR_HELPER = 7, BAR_OA = 8;
constexpr int NST_Q = 18, NST_KV = 128, NST_O = 18;
constexpr uint32_t SL_KE = (NST_Q - 1) & 3, SL_VE = NST_Q & 3, SL_KO = (NST_Q + 1) & 3, SL_VO = (NST_Q + 2) & 3;
#define X_ORDER 0
#define X_PF 5
#define X_PFQ 3
#define X_REL 0
#define X_SLEEP8 700
#define X_QP 2
#define X_WARM 0
#define X_S1 12
#define X_IP 0
#define X_XS 0
#define X_CA2 1
#define X_RS 0
#define X_DS 5000
#define X_HT 1
#define X_AD 3000
#define X_W1 16
#define X_N1 5
#define X_SPLIT 44
#define X_PARK 5
#define X_C0 32
#define X_C1 40
#define X_C2 56
#define X_C3 72
#define X_CA 1
#define X_FIN 4
constexpr float SM_SCALE_LOG2 = 0.08838834764831845f * 1.4426950408889634f;

struct Scratch {
  uint4 part[16 * 64 * 2 * 4 * 128];
  uint4 gate[N_ATT_CTA * 144 * 8];
  uint4 q3[N_ATT_CTA * 1024];
  uint4 xn[SEQ * DM / 8];
  uint32_t key[SEQ];
  float ypart[4 * TOPC * DM];
  uint32_t top[32];
  unsigned launch[160];
  unsigned rows[16 * 32];
  unsigned q3_flag[N_ATT_CTA];
  unsigned ycnt;
};
__device__ __align__(1024) Scratch g_scratch;

__device__ __forceinline__ void prof(int, int, int = 0) {}
__device__ __forceinline__ void profc(int, int) {}

__device__ __forceinline__ uint32_t smem_u32(const void* p) { return (uint32_t)__cvta_generic_to_shared(p); }
__device__ __forceinline__ void mbar_init(uint32_t bar, uint32_t cnt) {
  asm volatile("mbarrier.init.shared::cta.b64 [%0], %1;" ::"r"(bar), "r"(cnt) : "memory");
}
__device__ __forceinline__ void mbar_expect_tx(uint32_t bar, uint32_t bytes) {
  asm volatile("mbarrier.arrive.expect_tx.shared::cta.b64 _, [%0], %1;" ::"r"(bar), "r"(bytes) : "memory");
}
__device__ __forceinline__ void mbar_arrive(uint32_t bar) {
  asm volatile("mbarrier.arrive.shared::cta.b64 _, [%0];" ::"r"(bar) : "memory");
}
__device__ __forceinline__ void mbar_arrive_cluster(uint32_t bar_cluster_addr) {
  asm volatile("mbarrier.arrive.shared::cluster.b64 _, [%0];" ::"r"(bar_cluster_addr) : "memory");
}
template <int ID>
__device__ __forceinline__ void mbar_arrive_cluster_now(uint32_t bar_cluster_addr, bool pred, uint32_t zero) {
  asm volatile("{\n.reg .pred p, q;\nsetp.ne.u32 p, %1, 0;\nsetp.eq.u32 q, %2, %3;\n"
               "ARR_LOOP:\n@p mbarrier.arrive.shared::cluster.b64 _, [%0];\n@q bra.uni ARR_LOOP;\n}"
               ::"r"(bar_cluster_addr), "r"((uint32_t)pred), "r"(zero), "n"(ID) : "memory");
}
__device__ __forceinline__ void block_fence(int id, uint32_t zero = blockIdx.y) {
  asm volatile("{\n.reg .pred q;\nsetp.eq.u32 q, %0, %1;\nBF_LOOP:\n@q st.volatile.shared.u32 [%0], %0;\n@q bra.uni BF_LOOP;\n}"
               ::"r"(zero), "r"(id) : "memory");
}
__device__ __forceinline__ bool mbar_test(uint32_t bar, uint32_t parity) {
  uint32_t ok;
  asm volatile("{\n.reg .pred p;\nmbarrier.test_wait.parity.shared::cta.b64 p, [%1], %2;\nselp.u32 %0, 1, 0, p;\n}"
               : "=r"(ok) : "r"(bar), "r"(parity) : "memory");
  return ok;
}
__device__ __forceinline__ void mbar_wait(uint32_t bar, uint32_t parity) {
  asm volatile("{\n.reg .pred p, q;\n.reg .u32 n;\nmov.u32 n, 0;\n"
               "WAIT_LOOP:\nmbarrier.try_wait.parity.shared::cta.b64 p, [%0], %1;\n"
               "add.u32 n, n, 1;\nsetp.lt.u32 q, n, 4194304;\nand.pred q, q, !p;\n@q bra WAIT_LOOP;\n}"
               ::"r"(bar), "r"(parity) : "memory");
}
__device__ __forceinline__ uint32_t mapa(uint32_t addr, uint32_t rank) {
  uint32_t r;
  asm volatile("mapa.shared::cluster.u32 %0, %1, %2;" : "=r"(r) : "r"(addr), "r"(rank));
  return r;
}
__device__ __forceinline__ void cluster_arrive() { asm volatile("barrier.cluster.arrive.relaxed.aligned;" ::: "memory"); }
__device__ __forceinline__ bool elect_one() {
  uint32_t p;
  asm volatile("{\n.reg .pred p;\nelect.sync _|p, 0xffffffff;\nselp.u32 %0, 1, 0, p;\n}" : "=r"(p));
  return p;
}
__device__ __forceinline__ int read_lane() { return threadIdx.x & 31; }
__device__ __forceinline__ void cluster_wait() { asm volatile("barrier.cluster.wait.acquire.aligned;" ::: "memory"); }
__device__ __forceinline__ void bar_sync(int id, int n) { asm volatile("barrier.cta.sync %0, %1;" ::"r"(id), "r"(n) : "memory"); }
__device__ __forceinline__ void bar_arrive(int id, int n) { asm volatile("barrier.cta.arrive %0, %1;" ::"r"(id), "r"(n) : "memory"); }

__device__ __forceinline__ uint64_t policy_evict_first() {
  uint64_t p;
  asm("createpolicy.fractional.L2::evict_first.b64 %0, 1.0;" : "=l"(p));
  return p;
}
__device__ __forceinline__ uint64_t policy_evict_normal() {
  uint64_t p;
  asm("createpolicy.fractional.L2::evict_normal.b64 %0, 1.0;" : "=l"(p));
  return p;
}
__device__ __forceinline__ void tma3d(uint32_t dst, const CUtensorMap* tm, int c1, int c2, uint32_t bar) {
  asm volatile("cp.async.bulk.tensor.3d.shared::cluster.global.mbarrier::complete_tx::bytes [%0], [%1, {%2, %3, %4}], [%5];"
               ::"r"(dst), "l"(tm), "r"(0), "r"(c1), "r"(c2), "r"(bar) : "memory");
}
__device__ __forceinline__ void tma2d(uint32_t dst, const CUtensorMap* tm, int c0, int c1, uint32_t bar) {
  asm volatile("cp.async.bulk.tensor.2d.shared::cluster.global.mbarrier::complete_tx::bytes [%0], [%1, {%2, %3}], [%4];"
               ::"r"(dst), "l"(tm), "r"(c0), "r"(c1), "r"(bar) : "memory");
}
__device__ __forceinline__ void tma2d_stream(uint32_t dst, const CUtensorMap* tm, int c0, int c1, uint32_t bar) {
  asm volatile("{\n.reg .b64 pol;\ncreatepolicy.fractional.L2::evict_first.b64 pol, 1.0;\n"
               "cp.async.bulk.tensor.2d.shared::cluster.global.mbarrier::complete_tx::bytes.L2::cache_hint [%0], [%1, {%2, %3}], [%4], pol;\n}"
               ::"r"(dst), "l"(tm), "r"(c0), "r"(c1), "r"(bar) : "memory");
}
__device__ __forceinline__ void tma2d_prefetch(const CUtensorMap* tm, int c0, int c1) {
  asm volatile("cp.async.bulk.prefetch.tensor.2d.L2.global [%0, {%1, %2}];" ::"l"(tm), "r"(c0), "r"(c1) : "memory");
}
__device__ __forceinline__ void prefetch_l2(const void* p, uint32_t bytes) {
  asm volatile("cp.async.bulk.prefetch.L2.global [%0], %1;" ::"l"(p), "r"(bytes) : "memory");
}
__device__ __forceinline__ void prefetch_tmap(const CUtensorMap* tm) {
  asm volatile("prefetch.tensormap [%0];" ::"l"(tm) : "memory");
}

__device__ __forceinline__ void wg_fence() { asm volatile("wgmma.fence.sync.aligned;" ::: "memory"); }
__device__ __forceinline__ void wg_commit() { asm volatile("wgmma.commit_group.sync.aligned;" ::: "memory"); }
template <int N> __device__ __forceinline__ void wg_wait() { asm volatile("wgmma.wait_group.sync.aligned %0;" ::"n"(N) : "memory"); }

__device__ __forceinline__ uint64_t mkdesc(uint32_t addr, uint32_t lbo_bytes) {
  return (uint64_t)(((addr & 0x3FFFF) >> 4) | ((lbo_bytes >> 4) << 16)) | ((uint64_t)0x40000040u << 32);
}
template <int N> __device__ __forceinline__ void pin(float (&a)[N]) {
#pragma unroll
  for (int i = 0; i < N; i++) asm volatile("" : "+f"(a[i])::"memory");
}
template <int N> __device__ __forceinline__ void pin(uint32_t (&a)[N]) {
#pragma unroll
  for (int i = 0; i < N; i++) asm volatile("" : "+r"(a[i])::"memory");
}

#define F8(d, o) "+f"(d[o]), "+f"(d[o + 1]), "+f"(d[o + 2]), "+f"(d[o + 3]), "+f"(d[o + 4]), "+f"(d[o + 5]), "+f"(d[o + 6]), "+f"(d[o + 7])
#define R32A "%0, %1, %2, %3, %4, %5, %6, %7, %8, %9, %10, %11, %12, %13, %14, %15, %16, %17, %18, %19, %20, %21, %22, %23, %24, %25, %26, %27, %28, %29, %30, %31"
#define R32B "%32, %33, %34, %35, %36, %37, %38, %39, %40, %41, %42, %43, %44, %45, %46, %47, %48, %49, %50, %51, %52, %53, %54, %55, %56, %57, %58, %59, %60, %61, %62, %63"

template <int TB>
__device__ __forceinline__ void mma_n128(float (&d)[64], uint32_t a0, uint32_t a1, uint32_t a2, uint32_t a3, uint64_t db, int acc) {
  asm volatile("{\n.reg .pred p;\nsetp.ne.b32 p, %69, 0;\n"
               "wgmma.mma_async.sync.aligned.m64n128k16.f32.bf16.bf16 {" R32A ", " R32B "}, {%64, %65, %66, %67}, %68, p, 1, 1, %70;\n}\n"
               : F8(d, 0), F8(d, 8), F8(d, 16), F8(d, 24), F8(d, 32), F8(d, 40), F8(d, 48), F8(d, 56)
               : "r"(a0), "r"(a1), "r"(a2), "r"(a3), "l"(db), "r"(acc), "n"(TB));
}
template <int TB>
__device__ __forceinline__ void mma_n128_ss(float (&d)[64], uint64_t da, uint64_t db, int acc) {
  asm volatile("{\n.reg .pred p;\nsetp.ne.b32 p, %66, 0;\n"
               "wgmma.mma_async.sync.aligned.m64n128k16.f32.bf16.bf16 {" R32A ", " R32B "}, %64, %65, p, 1, 1, 0, %67;\n}\n"
               : F8(d, 0), F8(d, 8), F8(d, 16), F8(d, 24), F8(d, 32), F8(d, 40), F8(d, 48), F8(d, 56)
               : "l"(da), "l"(db), "r"(acc), "n"(TB));
}
template <int TB>
__device__ __forceinline__ void mma_n64(float (&d)[32], uint32_t a0, uint32_t a1, uint32_t a2, uint32_t a3, uint64_t db, int acc) {
  asm volatile("{\n.reg .pred p;\nsetp.ne.b32 p, %37, 0;\n"
               "wgmma.mma_async.sync.aligned.m64n64k16.f32.bf16.bf16 {" R32A "}, {%32, %33, %34, %35}, %36, p, 1, 1, %38;\n}\n"
               : F8(d, 0), F8(d, 8), F8(d, 16), F8(d, 24)
               : "r"(a0), "r"(a1), "r"(a2), "r"(a3), "l"(db), "r"(acc), "n"(TB));
}
__device__ __forceinline__ void mma_n8(float (&d)[4], uint64_t da, uint64_t db, int acc) {
  asm volatile("{\n.reg .pred p;\nsetp.ne.b32 p, %6, 0;\n"
               "wgmma.mma_async.sync.aligned.m64n8k16.f32.bf16.bf16 {%0, %1, %2, %3}, %4, %5, p, 1, 1, 1, 0;\n}\n"
               : "+f"(d[0]), "+f"(d[1]), "+f"(d[2]), "+f"(d[3])
               : "l"(da), "l"(db), "r"(acc));
}
__device__ __forceinline__ void hmma_k16(float (&d)[4], uint32_t a0, uint32_t a1, uint32_t a2, uint32_t a3, uint32_t b0, uint32_t b1) {
  asm volatile("mma.sync.aligned.m16n8k16.row.col.f32.bf16.bf16.f32 {%0, %1, %2, %3}, {%4, %5, %6, %7}, {%8, %9}, {%0, %1, %2, %3};"
               : "+f"(d[0]), "+f"(d[1]), "+f"(d[2]), "+f"(d[3]) : "r"(a0), "r"(a1), "r"(a2), "r"(a3), "r"(b0), "r"(b1));
}

__device__ __forceinline__ uint32_t pack2(float lo, float hi) {
  uint32_t r;
  asm("cvt.rn.bf16x2.f32 %0, %1, %2;" : "=r"(r) : "f"(hi), "f"(lo));
  return r;
}
__device__ __forceinline__ float bf_lo(uint32_t w) { return __uint_as_float(w << 16); }
__device__ __forceinline__ float bf_hi(uint32_t w) { return __uint_as_float(w & 0xFFFF0000u); }
__device__ __forceinline__ float bfr(float x) { return __uint_as_float(pack2(0.f, x)); }
__device__ __forceinline__ uint32_t sub2(uint32_t a, uint32_t b) {
  uint32_t r;
  asm("sub.rn.bf16x2 %0, %1, %2;" : "=r"(r) : "r"(a), "r"(b));
  return r;
}
__device__ __forceinline__ uint32_t add2(uint32_t a, uint32_t b) {
  uint32_t r;
  asm("add.rn.bf16x2 %0, %1, %2;" : "=r"(r) : "r"(a), "r"(b));
  return r;
}
__device__ __forceinline__ uint32_t mul2(uint32_t a, uint32_t b) {
  uint32_t r;
  asm("mul.rn.bf16x2 %0, %1, %2;" : "=r"(r) : "r"(a), "r"(b));
  return r;
}
__device__ __forceinline__ uint32_t fma2(uint32_t a, uint32_t b, uint32_t c) {
  uint32_t r;
  asm("fma.rn.bf16x2 %0, %1, %2, %3;" : "=r"(r) : "r"(a), "r"(b), "r"(c));
  return r;
}
__device__ __forceinline__ float ex2(float x) {
  float r;
  asm("ex2.approx.ftz.f32 %0, %1;" : "=f"(r) : "f"(x));
  return r;
}
__device__ __forceinline__ float rcp(float x) {
  float r;
  asm("rcp.approx.ftz.f32 %0, %1;" : "=f"(r) : "f"(x));
  return r;
}
__device__ __forceinline__ float silu_f(float t) { return t * rcp(1.0f + ex2(-1.4426950408889634f * t)); }
__device__ __forceinline__ void lds128(uint32_t a, uint32_t& x, uint32_t& y, uint32_t& z, uint32_t& w) {
  asm volatile("ld.shared.v4.u32 {%0, %1, %2, %3}, [%4];" : "=r"(x), "=r"(y), "=r"(z), "=r"(w) : "r"(a) : "memory");
}
__device__ __forceinline__ void ldsm4(uint32_t a, uint32_t& x, uint32_t& y, uint32_t& z, uint32_t& w) {
  asm volatile("ldmatrix.sync.aligned.m8n8.x4.shared.b16 {%0, %1, %2, %3}, [%4];" : "=r"(x), "=r"(y), "=r"(z), "=r"(w) : "r"(a) : "memory");
}
constexpr uint32_t TAG_BIT = 0x10000;
__device__ __forceinline__ void st_gran(uint4* p, uint32_t x, uint32_t y, uint32_t z, uint32_t w) {
  asm volatile("st.relaxed.gpu.global.v4.b32 [%0], {%1, %2, %3, %4};" ::"l"(p), "r"(x), "r"(y), "r"(z), "r"(w) : "memory");
}
__device__ __forceinline__ void ld_gran(const uint4* p, uint32_t& x, uint32_t& y, uint32_t& z, uint32_t& w) {
  asm volatile("ld.relaxed.gpu.global.v4.b32 {%0, %1, %2, %3}, [%4];" : "=r"(x), "=r"(y), "=r"(z), "=r"(w) : "l"(p) : "memory");
}
__device__ __forceinline__ void ldsm4t(uint32_t a, uint32_t& x, uint32_t& y, uint32_t& z, uint32_t& w) {
  asm volatile("ldmatrix.sync.aligned.m8n8.x4.trans.shared.b16 {%0, %1, %2, %3}, [%4];" : "=r"(x), "=r"(y), "=r"(z), "=r"(w) : "r"(a) : "memory");
}
__device__ __forceinline__ void stsm4t(uint32_t a, uint32_t x, uint32_t y, uint32_t z, uint32_t w) {
  asm volatile("stmatrix.sync.aligned.m8n8.x4.trans.shared.b16 [%0], {%1, %2, %3, %4};" ::"r"(a), "r"(x), "r"(y), "r"(z), "r"(w) : "memory");
}
__device__ __forceinline__ void stsm4(uint32_t a, uint32_t x, uint32_t y, uint32_t z, uint32_t w) {
  asm volatile("stmatrix.sync.aligned.m8n8.x4.shared.b16 [%0], {%1, %2, %3, %4};" ::"r"(a), "r"(x), "r"(y), "r"(z), "r"(w) : "memory");
}
template <class T>
__device__ __forceinline__ T* at(const void* base, uint32_t off) {
  uint64_t r;
  asm("{\n.reg .u32 lo, hi;\nmov.b64 {lo, hi}, %1;\nadd.cc.u32 lo, lo, %2;\naddc.u32 hi, hi, 0;\nmov.b64 %0, {lo, hi};\n}"
      : "=l"(r) : "l"(base), "r"(off));
  return (T*)__cvta_global_to_generic(r);
}
__device__ __forceinline__ void add_granules(float (&red)[32], const uint32_t (&g)[16]) {
#pragma unroll
  for (int i = 0; i < 16; i++) { red[2 * i] += bf_lo(g[i]); red[2 * i + 1] += bf_hi((i & 3) ? g[i] : g[i] & ~TAG_BIT); }
}
__device__ __forceinline__ bool granules_ok(const uint32_t (&g)[16], uint32_t tag) {
  uint32_t u, v;
  asm("lop3.b32 %0, %1, %2, %3, 0x7E;" : "=r"(u) : "r"(g[0]), "r"(g[4]), "r"(tag));
  asm("lop3.b32 %0, %1, %2, %3, 0x7E;" : "=r"(v) : "r"(g[8]), "r"(g[12]), "r"(tag));
  return __all_sync(0xffffffffu, ((u | v) & TAG_BIT) == 0);
}
__device__ __forceinline__ unsigned ld_acquire(const unsigned* p) {
  unsigned v;
  asm volatile("ld.acquire.gpu.global.u32 %0, [%1];" : "=r"(v) : "l"(p) : "memory");
  return v;
}
__device__ __forceinline__ void red_release(unsigned* p) {
  asm volatile("red.release.gpu.global.add.u32 [%0], 1;" ::"l"(p) : "memory");
}
__device__ __forceinline__ void st_release(unsigned* p, unsigned v) {
  asm volatile("st.release.gpu.global.u32 [%0], %1;" ::"l"(p), "r"(v) : "memory");
}

template <int K0, int K1>
__device__ __forceinline__ void ln_fetch(uint32_t (&xa)[144], uint32_t boxes, uint32_t lo) {
#pragma unroll
  for (int k = K0; k < K1; k++) ldsm4(((boxes + lo) ^ ((k & 3) << 5)) + (k >> 2) * 8192, xa[4 * k], xa[4 * k + 1], xa[4 * k + 2], xa[4 * k + 3]);
}
template <int K0, int K1>
__device__ __forceinline__ void ln_sums(const uint32_t (&xa)[144], float (&sm)[4][4]) {
#pragma unroll
  for (int k = K0; k < K1; k++) hmma_k16(sm[k & 3], xa[4 * k], xa[4 * k + 1], xa[4 * k + 2], xa[4 * k + 3], 0x3F803F80u, 0x3F803F80u);
}
__device__ __forceinline__ uint32_t sq8(const uint32_t* a) {
  uint32_t t, u;
  asm("mul.rn.bf16x2 %0, %1, %1;" : "=r"(t) : "r"(a[0]));
  asm("mul.rn.bf16x2 %0, %1, %1;" : "=r"(u) : "r"(a[2]));
#pragma unroll
  for (int i = 4; i < 16; i += 4) {
    asm("fma.rn.bf16x2 %0, %1, %1, %0;" : "+r"(t) : "r"(a[i]));
    asm("fma.rn.bf16x2 %0, %1, %1, %0;" : "+r"(u) : "r"(a[i + 2]));
  }
  return add2(t, u);
}
__device__ __forceinline__ void ln_centre(uint32_t (&xa)[144], int j0, int j1, uint32_t mm0, uint32_t mm1, float& sq0, float& sq1) {
#pragma unroll
  for (int j = 0; j < 72; j += 8)
    if (j >= j0 && j < j1) {
#pragma unroll
      for (int k = j; k < j + 8; k++) {
        xa[2 * k] = sub2(xa[2 * k], mm0);
        xa[2 * k + 1] = sub2(xa[2 * k + 1], mm1);
      }
      const uint32_t t0 = sq8(xa + 2 * j), t1 = sq8(xa + 2 * j + 1);
      sq0 += bf_lo(t0) + bf_hi(t0);
      sq1 += bf_lo(t1) + bf_hi(t1);
    }
}
__device__ __forceinline__ float ln_rstd(float var) {
  float sd;
  asm("sqrt.approx.ftz.f32 %0, %1;" : "=f"(sd) : "f"(bfr(bfr(fmaxf(var, 0.0f)) + 1e-5f)));
  return rcp(bfr(sd));
}
__device__ __forceinline__ uint32_t silu2(uint32_t t) { return pack2(silu_f(bf_lo(t)), silu_f(bf_hi(t))); }
__device__ __forceinline__ float sum8(float v) {
#pragma unroll
  for (int d = 4; d; d >>= 1) v += __shfl_xor_sync(0xffffffffu, v, d);
  return v;
}
__device__ __forceinline__ void await_count(const unsigned* p, unsigned target, unsigned sleep_ns) {
#pragma unroll 1
  for (int n = 0; n < (1 << 18) && __any_sync(0xffffffffu, (int)(ld_acquire(p) - target) < 0); n++) __nanosleep(sleep_ns);
}
__device__ __forceinline__ void bulk_load(uint32_t dst, const void* src, uint32_t bytes, uint32_t bar) {
  asm volatile("cp.async.bulk.shared::cluster.global.mbarrier::complete_tx::bytes [%0], [%1], %2, [%3];"
               ::"r"(dst), "l"(src), "r"(bytes), "r"(bar) : "memory");
}
__device__ __forceinline__ void proxy_fence() { asm volatile("fence.proxy.async;" ::: "memory"); }

template <int V> struct IC { static constexpr int value = V; };

struct Ctx {
  uint32_t sb;
  uint8_t* sp;
  uint32_t rank;
  Scratch* gs;
};

__device__ __forceinline__ void dly(const Ctx&, int) {}
template <int BOXES>
__device__ __forceinline__ void load_stage(uint32_t dst, const CUtensorMap* tm, int c0, int c1, uint32_t bar, uint32_t bytes, uint64_t pol) {
  asm volatile("{\n.reg .pred p;\nelect.sync _|p, 0xffffffff;\n"
               "@p mbarrier.arrive.expect_tx.shared::cta.b64 _, [%4], %7;\n"
               "@p cp.async.bulk.tensor.2d.shared::cluster.global.mbarrier::complete_tx::bytes.multicast::cluster.L2::cache_hint"
               " [%0], [%1, {%2, %3}], [%4], %5, %6;\n}"
               ::"r"(dst), "l"(tm), "r"(c0), "r"(c1), "r"(bar), "h"((uint16_t)3), "l"(pol), "r"(bytes) : "memory");
  if (BOXES == 2)
    asm volatile("{\n.reg .pred p;\nelect.sync _|p, 0xffffffff;\n"
                 "@p cp.async.bulk.tensor.2d.shared::cluster.global.mbarrier::complete_tx::bytes.multicast::cluster.L2::cache_hint"
                 " [%0], [%1, {%2, %3}], [%4], %5, %6;\n}"
                 ::"r"(dst + 8192), "l"(tm), "r"(c0), "r"(c1 + 64), "r"(bar), "h"((uint16_t)3), "l"(pol) : "memory");
}
__device__ __forceinline__ void attn_producer(const Ctx& cx, int qb, int hs, const CUtensorMap* tmX, const CUtensorMap* tmK,
                                              const CUtensorMap* tmV, const CUtensorMap* tmWq, const CUtensorMap* tmWo) {
  const uint32_t full = cx.sb + SM_FULL, empty = cx.sb + SM_EMPTY, ring = cx.sb + SM_RING + cx.rank * 16384;
  const uint64_t keep = policy_evict_normal(), last_use = policy_evict_first();
  auto acquire = [&](int st) {
    mbar_wait(empty + 8 * (st & 3), ((st >> 2) ^ ((st & 3) >> 1) ^ 1) & 1);
    if (st > 3) dly(cx, st);
  };
  if (elect_one()) {
#pragma unroll
    for (int j = 0; j < 3; j++) {
      mbar_expect_tx(cx.sb + SM_XFULL + 96 + 8 * j, 24576);
      tma3d(cx.sb + SM_X + 73728 + j * 24576, tmX, qb * 128 + 64, j * 3, cx.sb + SM_XFULL + 96 + 8 * j);
    }
  }
  __syncwarp();
  const int c0 = cx.rank * 64;
#pragma unroll 1
  for (int p = 0; p < 3; p++) {
    const int n0 = (hs * 4 + ((0x120 >> (4 * p)) & 3)) * DH + c0;
#pragma unroll
    for (int i = 0; i < 5; i++) {
      const int st = (p == 2 ? 13 : 5 * p) + i, sl = st & 3;
      if (i == 4 && p == 2) break;
      if (X_W1 && st == 1) mbar_wait(cx.sb + SM_XFULL + X_W1, 0);
      acquire(st);
      if (i == 2) load_stage<1>(ring + sl * STAGE, tmWq, n0, 256, full + 8 * sl, 16384, last_use);
      else load_stage<2>(ring + sl * STAGE, tmWq, n0, i < 2 ? 128 * i : 128 * i - 64, full + 8 * sl, 32768, last_use);
      if (i == X_PFQ && p < 2 && elect_one()) {
        tma2d_prefetch(tmWq, (hs * 4 + 2 - p) * DH + (qb & 1) * 64, (qb >> 1) * 64);
        if (p == 0 && qb < 9) tma2d_prefetch(tmWq, (hs * 4 + 3) * DH, qb * 64);
      }
      __syncwarp();
    }
    if (p == 1) {
      const int n3 = (hs * 4 + 3) * DH;
      acquire(10);
      load_stage<2>(ring + 2 * STAGE, tmWq, n3, 2 * c0, full + 16, 32768, last_use);
      acquire(11);
      if (cx.rank) load_stage<1>(ring + 3 * STAGE, tmWq, n3, 384, full + 24, 24576, last_use);
      else load_stage<2>(ring + 3 * STAGE, tmWq, n3, 256, full + 24, 24576, last_use);
      acquire(12);
      load_stage<1>(ring, tmWq, n3, 448 + c0, full, 16384, last_use);
    }
  }
  int vrow = 0;
  uint64_t vpol = keep;
#pragma unroll 1
  for (int j = 0; j < 32; j++) {
    const int st = NST_Q - 1 + 4 * j, row = (hs * 2 + (j >> 4)) * SEQ + (j & 7) * 256;
    const uint64_t pol = (j & 8) ? last_use : keep;
    if (j == 24) mbar_wait(cx.sb + SM_BAR_Q3, 0);
    acquire(st);
    load_stage<1>(ring + SL_KE * STAGE, tmK, c0, row, full + 8 * SL_KE, 32768, pol);
    acquire(st + 1);
    if (j) load_stage<1>(ring + SL_VE * STAGE, tmV, c0, vrow, full + 8 * SL_VE, 32768, vpol);
    else load_stage<2>(ring + SL_VE * STAGE, tmWq, (hs * 4 + 1) * DH + c0, 448, full + 8 * SL_VE, 32768, last_use);
    vrow = row + 128;
    vpol = pol;
    acquire(st + 2);
    load_stage<1>(ring + SL_KO * STAGE, tmK, c0, vrow, full + 8 * SL_KO, 32768, pol);
    acquire(st + 3);
    load_stage<1>(ring + SL_VO * STAGE, tmV, c0, row, full + 8 * SL_VO, 32768, pol);
  }
  acquire(NST_Q + NST_KV - 1);
  load_stage<1>(ring + SL_KE * STAGE, tmV, c0, vrow, full + 8 * SL_KE, 32768, last_use);
#pragma unroll 1
  for (int u = 0; u < NST_O; u++) {
    const int st = NST_Q + NST_KV + u, sl = st & 3;
    const int blk = u < 4 && cx.rank ? 8 : ((hs + max(u >> 1, 1)) & 7);
    const int head = u < 4 ? u ^ (u >> 1) : ((u & 1) * 2 + cx.rank + 3) & 3;
    acquire(st);
    load_stage<1>(ring + sl * STAGE, tmWo, blk * 64, hs * 512 + head * 128, full + 8 * sl, 32768, last_use);
  }
}

__device__ __forceinline__ uint32_t xn_offset(uint32_t row, int lane) {
  return (row >> 6) * (9 * 8192) + (row & 63) * 128 + ((((lane >> 2) ^ row) & 7) << 4) + (lane & 3) * 4;
}

__device__ __forceinline__ void attn_rows(const Ctx& cx, int qb, int hs, int hw, int lane, const CUtensorMap* tmX16,
                                          const __nv_bfloat16* w_r) {
  extern __shared__ __align__(1024) uint8_t smem_rows[];
  auto box = [&](int blk) { return blk < 8 ? SM_SLOT + 2 * STAGE + 8192 + (blk >> 2) * 16384 + (blk & 3) * 2048 : SM_BOX8; };
  const uint32_t sb = smem_u32(smem_rows);
  if (hw == 0) {
    bar_sync(BAR_HELPER, 160);
    if (elect_one()) {
      mbar_expect_tx(sb + SM_BAR_ROWS, 9 * 2048);
#pragma unroll
      for (int i = 0; i < 9; i++) tma2d(sb + box(i), tmX16, i * 64, qb * 128 + hs * 16, sb + SM_BAR_ROWS);
    }
    __syncwarp();
  }
  uint32_t g = (lane >> 3) * 128 + (((lane ^ (lane >> 3)) & 7) << 4);
  auto next = [&]() {
    g = ((g + 512) & 2047) ^ 64;
    asm volatile("" : "+r"(g));
  };
  float* const part = (float*)(smem_rows + SM_ROWS);
  mbar_wait(sb + SM_BAR_ROWS, 0);
  if (hw == 0) dly(cx, 190);
#pragma unroll 1
  for (int i = 0; i < 4; i++) {
    float a = 0.f, b = 0.f;
#pragma unroll
    for (int j = 0; j < 3; j++) {
      const uint4 v = *(const uint4*)(smem_rows + box(hw * 3 + j) + g);
      const uint32_t w[4] = {v.x, v.y, v.z, v.w};
#pragma unroll
      for (int k = 0; k < 4; k++) {
        a += bf_lo(w[k]) + bf_hi(w[k]);
        b = fmaf(bf_lo(w[k]), bf_lo(w[k]), fmaf(bf_hi(w[k]), bf_hi(w[k]), b));
      }
    }
    a = sum8(a);
    b = sum8(b);
    float* p = part + hw * 16 + (g >> 7);
    p[0] = a;
    p[48] = b;
    next();
  }
  bar_sync(BAR_ROWS, 96);
  if (hw == 0) dly(cx, 191);
  {
    const float* p = part + (lane & 15);
    const float mean = (p[0] + p[16] + p[32]) * (1.0f / DM), rstd = ln_rstd((p[48] + p[64] + p[80]) * (1.0f / DM) - mean * mean);
    const uint32_t mm = pack2(mean, mean), rr = pack2(rstd - bfr(rstd), rstd);
#pragma unroll 1
    for (int u = hw * 12; u < hw * 12 + 12; u++) {
      const int blk = u >> 2;
      uint4* q = (uint4*)(smem_rows + box(blk) + g);
      uint4 v = *q;
      const uint32_t m = __shfl_sync(0xffffffffu, mm, g >> 7), r = __shfl_sync(0xffffffffu, rr, g >> 7);
      const uint32_t hi = __byte_perm(r, 0, 0x3232), lo = __byte_perm(r, 0, 0x1010);
      auto norm = [&](uint32_t w) {
        const uint32_t xc = sub2(w, m);
        return fma2(xc, hi, mul2(xc, lo));
      };
      v = make_uint4(norm(v.x), norm(v.y), norm(v.z), norm(v.w));
      *q = v;
      *at<uint4>(cx.gs->xn + ((qb * 2 + (hs >> 2)) * 9 + blk) * 512 + (hs & 3) * 128, g) = v;
      next();
    }
  }
  bar_sync(BAR_ROWS, 96);
  if (hw == 0) {
    dly(cx, 192);
    if (lane == 0) red_release(&cx.gs->rows[qb * 32]);
    dly(cx, 193);
  }
#pragma unroll 1
  for (int u = hw ? 13 * hw - 3 : 0; u < 13 * hw + 10; u++) {
    const int blk = u >> 2;
    const uint32_t o = (g + (u & 3) * 512) ^ ((u & 1) << 6);
    const uint4 v = *(const uint4*)(smem_rows + box(blk) + o);
    *at<uint4>(cx.gs->gate + (blk < 8 ? (qb * 8 + blk) * 144 + hs * 16 : (qb * 8 + hs) * 144 + 128) * 8, o) =
        make_uint4(silu2(v.x), silu2(v.y), silu2(v.z), silu2(v.w));
  }
  if (hw) dly(cx, 194 + hw);
  if (X_DS) __nanosleep(X_DS);
#pragma unroll 1
  for (int blk = hw * 3; blk < hw * 3 + 3; blk++) {
    const uint4 c = __ldg(at<const uint4>(w_r, blk * 128 + ((g ^ (g >> 3)) & 0x70)));
#pragma unroll 1
    for (int i = 0; i < 4; i++) {
      const uint4 v = *(const uint4*)(smem_rows + box(blk) + g);
      part[blk * 16 + (g >> 7)] =
          sum8(fmaf(bf_lo(v.x), bf_lo(c.x), fmaf(bf_hi(v.x), bf_hi(c.x), fmaf(bf_lo(v.y), bf_lo(c.y), bf_hi(v.y) * bf_hi(c.y)))) +
               fmaf(bf_lo(v.z), bf_lo(c.z), fmaf(bf_hi(v.z), bf_hi(c.z), fmaf(bf_lo(v.w), bf_lo(c.w), bf_hi(v.w) * bf_hi(c.w)))));
      next();
    }
  }
  bar_sync(BAR_ROWS, 96);
  if (hw == 0) {
    dly(cx, 194);
    float d = 0.f;
#pragma unroll
    for (int j = 0; j < 9; j++) d += part[j * 16 + (lane & 15)];
    const uint32_t row = qb * 128 + hs * 16 + (lane & 15), b = pack2(0.f, d);
    *at<uint32_t>(cx.gs->key, row * 4) = (b ^ ((int)b < 0 ? 0xFFFF0000u : 0x80000000u)) + 0xFFFF - row;
    __syncwarp();
    if (lane == 0) red_release(&cx.gs->rows[qb * 32 + 1]);
  }
}

constexpr uint32_t SM_XO = SM_SLOT, SM_GO = SM_SLOT + STAGE, SM_P8 = SM_SLOT + 2 * STAGE;
__device__ __forceinline__ void attn_helper(const Ctx& cx, int qb, int hs, int lane, const __nv_bfloat16* wo, const CUtensorMap* tmX16) {
  unsigned e = 0;
  if (lane == 0) {
    e = cx.gs->launch[blockIdx.x];
    cx.gs->launch[blockIdx.x] = e + 1;
  }
  e = __shfl_sync(0xffffffffu, e, 0);
  if (lane == 0) {
    *(uint32_t*)(cx.sp + SM_TAG) = (~e & 1) * TAG_BIT;
    mbar_arrive(cx.sb + SM_BAR_MISC);
  }
  bar_sync(BAR_HELPER, 64);
  await_count(&cx.gs->rows[qb * 32 + 1], 8 * (e + 1), 1000);
  await_count(&cx.gs->q3_flag[qb * 8 + hs], e + 1, 1000);
  proxy_fence();
  if (elect_one()) {
    mbar_expect_tx(cx.sb + SM_BAR_Q3, 16384);
#pragma unroll
    for (int i = 0; i < 2; i++) bulk_load(cx.sb + SM_SLOT + 2 * STAGE + i * 16384 + 8192, cx.gs->q3 + (qb * 16 + hs * 2 + i) * 512, 8192, cx.sb + SM_BAR_Q3);
  }
  __syncwarp();
  bar_sync(BAR_HELPER, 64);
  prefetch_l2(at<const void>(wo, (hs * 512 + qb * 32 + lane) * (DM * 2)), DM * 2);
  await_count(&cx.gs->ycnt, 4 * (e + 1), 500);
  const uint32_t mykey = __ldcg(at<const uint32_t>(cx.gs->top, (lane >> 1) * 4)), myrow = 0xFFFF - (mykey & 0xFFFF);
#pragma unroll 1
  for (uint32_t todo = __ballot_sync(0xffffffffu, lane < 16 && ((lane & 1) ? myrow >> 4 == qb * 8 + hs : myrow >> 7 == qb)); todo; todo &= todo - 1) {
    const int i = __ffs(todo) - 1, blk = (i & 1) ? 8 : hs;
    const uint32_t key = __shfl_sync(0xffffffffu, mykey, i), row = 0xFFFF - (key & 0xFFFF), o = xn_offset(row, lane);
    const uint32_t t = __ldcg(at<const uint32_t>(cx.gs->xn, o + blk * 8192));
    const float2* p = at<const float2>(cx.gs->ypart, ((i >> 1) * DM + blk * 64 + 2 * lane) * 4);
    const float2 y0 = __ldcg(p), y1 = __ldcg(p + TOPC * DM / 2), y2 = __ldcg(p + TOPC * DM), y3 = __ldcg(p + 3 * TOPC * DM / 2);
    const float rs = bfr(rcp(1.0f + ex2(-1.4426950408889634f * bf_hi(key ^ ((int)key < 0 ? 0x80000000u : 0xFFFF0000u)))));
    const uint32_t y = pack2((y0.x + y1.x) + (y2.x + y3.x), (y0.y + y1.y) + (y2.y + y3.y));
    const uint32_t u = pack2(bf_lo(y) * rs, bf_hi(y) * rs);
    *at<uint32_t>(cx.gs->gate, ((qb * 8 + hs) * 144 + ((i & 1) ? 128 + (row & 15) : row & 127)) * 128 + (o & 127)) = silu2(add2(t, u));
  }
  proxy_fence();
  bar_sync(BAR_OA, 352);
  if (elect_one()) {
    const uint32_t bar = cx.sb + SM_BAR_XG;
    mbar_expect_tx(bar, 2 * 144 * 128);
    bulk_load(cx.sb + SM_GO, cx.gs->gate + (qb * 8 + hs) * (144 * 8), 144 * 128, bar);
#pragma unroll 1
    for (int i = 0; i < 9; i++) tma2d_stream(cx.sb + SM_XO + i * 2048, tmX16, i < 8 ? hs * 64 : 512, qb * 128 + (i < 8 ? i : hs) * 16, bar);
  }
  __syncwarp();
  const uint4* src = cx.gs->part + (qb * 64 + 56 + hs) * 1024;
#pragma unroll 1
  for (int n = 0; n < (1 << 16); n++) {
    __nanosleep(n ? 400 : X_SLEEP8);
    uint32_t a, b, d, t;
    ld_gran(at<const uint4>(src, (lane & 7) * 2048 + 2032), a, b, d, t);
    if (__all_sync(0xffffffffu, ((a >> 16) ^ e) & 1)) break;
  }
  if (elect_one()) {
    mbar_expect_tx(cx.sb + SM_BAR_P8, 16384);
    bulk_load(cx.sb + SM_P8, src, 16384, cx.sb + SM_BAR_P8);
  }
  __syncwarp();
}
__device__ __forceinline__ void attn_finish8(const Ctx& cx, int qb, int hs, int hw, int lane, __nv_bfloat16* out) {
  const uint32_t tag = *(const uint32_t*)(cx.sp + SM_TAG);
  mbar_wait(cx.sb + SM_BAR_P8, 0);
  mbar_wait(cx.sb + SM_BAR_XG, 0);
#pragma unroll 1
  for (int g = 2 - hw; g < 4; g += 3) {
    float acc[8] = {0.f, 0.f, 0.f, 0.f, 0.f, 0.f, 0.f, 0.f};
    uint32_t a[4];
#pragma unroll 1
    for (uint32_t o = g * 512 + lane * 16; o < 16384; o += 2048) {
      lds128(cx.sb + SM_P8 + o, a[0], a[1], a[2], a[3]);
#pragma unroll 1
      for (int n = 0; n < (1 << 16) && __any_sync(0xffffffffu, (a[0] & TAG_BIT) != tag); n++)
        ld_gran(at<const uint4>(cx.gs->part, (qb * 64 + 56 + hs) * 16384 + o), a[0], a[1], a[2], a[3]);
      a[0] &= ~TAG_BIT;
#pragma unroll
      for (int j = 0; j < 4; j++) { acc[2 * j] += bf_lo(a[j]); acc[2 * j + 1] += bf_hi(a[j]); }
    }
    asm volatile("" : "+r"(lane));
    const uint32_t tile = cx.sb + SM_XO + (128 + (lane & 15)) * 128 + (((lane >> 4) ^ (lane & 7)) << 4);
    uint32_t b[4];
    ldsm4((tile ^ (g << 5)) + STAGE, a[0], a[1], a[2], a[3]);
    ldsm4(tile ^ (g << 5), b[0], b[1], b[2], b[3]);
    stsm4(tile ^ (g << 5), fma2(pack2(acc[0], acc[1]), a[0], b[0]), fma2(pack2(acc[2], acc[3]), a[1], b[1]),
          fma2(pack2(acc[4], acc[5]), a[2], b[2]), fma2(pack2(acc[6], acc[7]), a[3], b[3]));
  }
  bar_sync(BAR_ROWS, 96);
#pragma unroll 1
  for (int ch = threadIdx.x - 32; ch < 128; ch += 96)
    *at<uint4>(out, ((qb * 128 + hs * 16 + (ch >> 3)) * DM + 512 + (ch & 7) * 8) * 2) =
        *(const uint4*)(cx.sp + SM_XO + (128 + (ch >> 3)) * 128 + (((ch ^ (ch >> 3)) & 7) << 4));
}

constexpr float SUM_HI = 1.8446744e19f, SUM_LO = 9.0949470e-13f;

__device__ __forceinline__ void softmax_shift(float (&s)[64], float n0, float n1) {
#pragma unroll
  for (int i = 0; i < 64; i++) s[i] += (i & 2) ? n1 : n0;
}
template <int LO, int HI>
__device__ __forceinline__ void softmax_exp(float (&s)[64]) {
#pragma unroll
  for (int i = LO; i < HI; i++) s[i] = ex2(s[i]);
}
__device__ __forceinline__ void row_sums(const uint32_t (&pf)[32], float& l0, float& l1) {
  uint32_t t[16];
#pragma unroll
  for (int i = 0; i < 16; i++) t[i] = add2(pf[(i >> 1) * 4 + (i & 1)], pf[(i >> 1) * 4 + 2 + (i & 1)]);
#pragma unroll
  for (int i = 0; i < 8; i++) t[i] = add2(t[(i >> 1) * 4 + (i & 1)], t[(i >> 1) * 4 + 2 + (i & 1)]);
#pragma unroll
  for (int i = 0; i < 4; i++) t[i] = add2(t[(i >> 1) * 4 + (i & 1)], t[(i >> 1) * 4 + 2 + (i & 1)]);
  l0 += (bf_lo(t[0]) + bf_lo(t[2])) + (bf_hi(t[0]) + bf_hi(t[2]));
  l1 += (bf_lo(t[1]) + bf_lo(t[3])) + (bf_hi(t[1]) + bf_hi(t[3]));
}
__device__ __forceinline__ void softmax_redo(uint32_t (&pf)[32], const uint32_t (&q)[32], const __nv_bfloat16* kblk, int lane, float& n0,
                                             float& n1, float& l0, float& l1, float& sc0, float& sc1) {
  float x0 = -n0, x1 = -n1;
#pragma unroll 1
  for (int u = 0; u < 16; u++) {
    const uint32_t* kp = (const uint32_t*)(kblk + ((u & 7) * 16 + (lane >> 2)) * DH) + (lane & 3);
    float d[2][4] = {};
#pragma unroll
    for (int k = 0; k < 16; k++)
      hmma_k16(d[k & 1], q[2 * (k & 14)], q[2 * (k & 14) + 1], q[2 * (k & 14) + 2], q[2 * (k & 14) + 3],
               kp[(k & 1) * 4 * DH + (k >> 1) * 8], kp[(k & 1) * 4 * DH + (k >> 1) * 8 + 4]);
    if (u < 8) {
      x0 = fmaxf(fmaxf(x0, fmaxf(d[0][0], d[0][1])), fmaxf(d[1][0], d[1][1]));
      x1 = fmaxf(fmaxf(x1, fmaxf(d[0][2], d[0][3])), fmaxf(d[1][2], d[1][3]));
      if (u == 7) {
#pragma unroll
        for (int m = 1; m < 4; m <<= 1) {
          x0 = fmaxf(x0, __shfl_xor_sync(0xffffffffu, x0, m));
          x1 = fmaxf(x1, __shfl_xor_sync(0xffffffffu, x1, m));
        }
        sc0 = ex2(-x0 - n0);
        sc1 = ex2(-x1 - n1);
        n0 = -x0;
        n1 = -x1;
        l0 *= sc0;
        l1 *= sc1;
      }
    } else {
#pragma unroll
      for (int i = 0; i < 28; i++) pf[i] = pf[i + 4];
#pragma unroll
      for (int i = 0; i < 4; i++) {
        const float n = (i & 1) ? n1 : n0;
        pf[28 + i] = pack2(ex2(d[i >> 1][(i & 1) * 2] + n), ex2(d[i >> 1][(i & 1) * 2 + 1] + n));
        ((i & 1) ? l1 : l0) += bf_lo(pf[28 + i]) + bf_hi(pf[28 + i]);
      }
    }
  }
}

__device__ __forceinline__ void attn_consumer(const Ctx& cx, int qb, int hs, int wg, int cw, int lane, const __nv_bfloat16* x,
                                              const __nv_bfloat16* kc, __nv_bfloat16* out) {
  const uint32_t full = cx.sb + SM_FULL;
  const uint32_t ring = cx.sb + SM_RING;
  uint32_t lo = ((cw & 3) * 16 + (lane & 15)) * 128 + (((lane >> 4) ^ (lane & 7)) << 4);
  const uint32_t slot = cx.sb + SM_SLOT + wg * 16384;
  auto frag = [&](int sl, int k) { return ((slot + sl * STAGE + lo) ^ ((k & 3) << 5)) + (k >> 2) * 8192; };
  auto park = [&](float (&a)[64], int sl, int k0, int k1, float f0, float f1, bool in_place = false) {
#pragma unroll
    for (int k = 0; k < 8; k++)
      if (k >= k0 && k < k1) {
        float t[8];
#pragma unroll
        for (int i = 0; i < 8; i++) {
          t[i] = a[8 * k + i] * ((i & 2) ? f1 : f0);
          if (in_place) a[8 * k + i] = t[i];
        }
        stsm4(frag(sl, k), pack2(t[0], t[1]), pack2(t[2], t[3]), pack2(t[4], t[5]), pack2(t[6], t[7]));
      }
  };
  const bool signaller = lane == 0 && (cw & 3) < 2;
  int my_turn = 1 + wg, other_turn = 2 - wg;

  uint32_t pf[32], q[32], empty_c;
  float o[64], l0, l1;
  {
    uint32_t xa[144];
    float rstd0, rstd1;
    {
      const uint32_t xb = cx.sb + SM_X + wg * 73728, xf = cx.sb + SM_XFULL + wg * 96;
      float sm[4][4] = {};
      prof(wg, 0);
      if (X_WARM) hmma_k16(sm[0], 0, 0, 0, 0, 0, 0);
      empty_c = mapa(cx.sb + SM_EMPTY, cw & 1);
      mbar_wait(xf, 0);
      if ((threadIdx.x & 127) == 0) profc(wg, 30);
      ln_fetch<0, 12>(xa, xb, lo);
      mbar_wait(xf + 8, 0);
      ln_fetch<12, 24>(xa, xb, lo);
      ln_sums<0, X_S1>(xa, sm);
      mbar_wait(xf + 16, 0);
      if ((threadIdx.x & 127) == 0) profc(wg, 1);
      ln_fetch<24, 36>(xa, xb, lo);
      ln_sums<X_S1, 36>(xa, sm);
      rstd0 = ((sm[0][0] + sm[1][0]) + (sm[2][0] + sm[3][0])) * (1.0f / DM);
      rstd1 = ((sm[0][2] + sm[1][2]) + (sm[2][2] + sm[3][2])) * (1.0f / DM);
    }
    asm volatile("" : "+f"(rstd0), "+f"(rstd1)::"memory");
    block_fence(38);
    if (wg) {
      bar_arrive(other_turn, 256);
      if (X_RS < 0) bar_arrive(BAR_HELPER, 160);
    }
    block_fence(39);
    const uint32_t mm0 = pack2(rstd0, rstd0), mm1 = pack2(rstd1, rstd1);
    rstd0 -= bf_lo(mm0);
    rstd1 -= bf_lo(mm1);
    rstd0 *= rstd0 * (-0.25f * DM);
    rstd1 *= rstd1 * (-0.25f * DM);
    auto ln_finish = [&]() {
      rstd0 += __shfl_xor_sync(0xffffffffu, rstd0, 1); rstd1 += __shfl_xor_sync(0xffffffffu, rstd1, 1);
      rstd0 += __shfl_xor_sync(0xffffffffu, rstd0, 2); rstd1 += __shfl_xor_sync(0xffffffffu, rstd1, 2);
      rstd0 = ln_rstd(rstd0 * (1.0f / DM)) * SM_SCALE_LOG2;
      rstd1 = ln_rstd(rstd1 * (1.0f / DM)) * SM_SCALE_LOG2;
    };
    ln_centre(xa, 0, X_C0, mm0, mm1, rstd0, rstd1);
    if (wg == 0) {
      bar_sync(4, 128);
      if (signaller) {
        asm volatile("mbarrier.arrive.shared::cluster.b64 _, [%0], 2;" ::"r"(empty_c + 16) : "memory");
        asm volatile("mbarrier.arrive.shared::cluster.b64 _, [%0], 2;" ::"r"(empty_c + 24) : "memory");
      }
      block_fence(37);
      pin(xa);
      ln_centre(xa, X_C0, X_CA == 1 ? X_C1 : X_C2, mm0, mm1, rstd0, rstd1);
    }
    pin(xa);
    if ((threadIdx.x & 127) == 0) profc(wg, 2);

    extern __shared__ __align__(1024) uint8_t smem_q[];
    const uint32_t ring = smem_u32(smem_q) + SM_RING;
    auto release = [&](int st) { if (signaller) mbar_arrive_cluster(empty_c + 8 * (st & 3)); };
    auto q_stage = [&](float (&acc)[64], int st, int i, int last) {
      mbar_wait(full + 8 * (st & 3), (st >> 2) & 1);
      if (i != (wg ? last : 1)) bar_sync(my_turn, 256);
      wg_fence();
      const uint64_t db = mkdesc(ring + (st & 3) * STAGE, 16384);
#pragma unroll
      for (int k = 0; k < 8; k++) {
        const int kb = (i < 3 ? 8 * i : 8 * i - 4) + k;
        if (i != 2 || k < 4) mma_n128<1>(acc, xa[4 * kb], xa[4 * kb + 1], xa[4 * kb + 2], xa[4 * kb + 3], db + k * 128, kb > 0);
      }
      wg_commit();
      if (i != (wg ? last - 1 : 0)) bar_arrive(other_turn, 256);
    };
    auto q_release = [&](int st, int i, int last) {
      if (i == 1 || i == last) {
        wg_wait<1>();
        if (i == last || !wg) release(st - 1);
      }
      if (i != last - 1 && (i || wg)) {
        wg_wait<0>();
        release(st);
      }
    };
    {
      float (&acc)[64] = o;
#pragma unroll 1
      for (int p = 0; p < 2; p++) {
#pragma unroll
        for (int i = 0; i < 5; i++) {
          q_stage(acc, 5 * p + i, i, 4);
          if (p == 0 && i <= X_FIN) {
            if (i == X_RS && wg) bar_arrive(BAR_HELPER, 160);
            if ((wg || i >= X_CA) && i < 4)
              ln_centre(xa, i == 0 ? X_C0 : i == 1 ? X_C1 : i == 2 ? X_C2 : X_C3, i == 0 ? X_C1 : i == 1 ? X_C2 : i == 2 ? X_C3 : 72, mm0, mm1, rstd0, rstd1);
            if (i == X_FIN) ln_finish();
            pin(xa);
          }
          q_release(5 * p + i, i, 4);
        }
        pin(acc);
#pragma unroll
        for (int k = 0; k < 8; k += X_QP) {
          park(acc, p, k, k + X_QP, rstd0, rstd1);
          if (k + X_QP < 8) block_fence(40 + k);
        }
      }
    }
    {
      float (&h)[32] = *(float (*)[32])&o[0];
#pragma unroll
      for (int i = 0; i < 3; i++) {
        const uint32_t sl = (10 + i) & 3;
        mbar_wait(full + 8 * sl, ((10 + i) >> 2) & 1);
        if (X_HT ? i != (wg ? 2 : 1) : i == 0) bar_sync(my_turn, 256);
        wg_fence();
#pragma unroll
        for (int k = 0; k < 16 - 4 * i; k++) {
          const int kb = (i == 2 ? 28 : 16 * i) + k;
          const uint64_t db = mkdesc(ring + sl * STAGE, 16) + (i == 2 && k >= 4 ? k + 4 : k) * 128;
          mma_n64<1>(h, xa[4 * kb], xa[4 * kb + 1], xa[4 * kb + 2], xa[4 * kb + 3], db, kb > 0);
        }
        wg_commit();
        if (X_HT ? i != (wg ? 1 : 0) : i == 2) bar_arrive(other_turn, 256);
        if (X_HT) {
          q_release(10 + i, i, 2);
        } else if (i) {
          wg_wait<1>();
          release(9 + i);
          if (i == 2) {
            wg_wait<0>();
            release(12);
          }
        }
      }
      pin(h);
#pragma unroll
      for (int k = 0; k < 4; k++) {
        stsm4(frag(2, k), pack2(h[8 * k] * rstd0, h[8 * k + 1] * rstd0), pack2(h[8 * k + 2] * rstd1, h[8 * k + 3] * rstd1),
              pack2(h[8 * k + 4] * rstd0, h[8 * k + 5] * rstd0), pack2(h[8 * k + 6] * rstd1, h[8 * k + 7] * rstd1));
        if (k == 1) block_fence(49);
      }
    }
#pragma unroll
    for (int i = 0; i < 4; i++) {
      q_stage(o, 13 + i, i, 3);
      q_release(13 + i, i, 3);
    }
    prof(wg, 6);
#pragma unroll
    for (int i = 0; i < 32; i++) pf[i] = xa[112 + i];
    l0 = 0.25f * rcp(rstd0);
    l1 = 0.25f * rcp(rstd1);
  }

  uint32_t oa[96];
  const uint32_t zero = __shfl_sync(0xffffffffu, blockIdx.y, lane);
  my_turn = __shfl_sync(0xffffffffu, my_turn, lane);
  other_turn = __shfl_sync(0xffffffffu, other_turn, lane);
  lo = __shfl_sync(0xffffffffu, lo, lane);
  {
    float s[64], n0 = 0.f, n1 = 0.f;
    float lp0, lp1;
    float i0 = 0.f, i1 = 0.f;
    bool redo, shift = false;
    auto turn = [&](int it, auto kc_) -> bool {
      constexpr int KIND = decltype(kc_)::value;
      constexpr uint32_t slk = KIND == 1 ? SL_KO : SL_KE, slv = KIND == 1 ? SL_VO : SL_VE, slkn = KIND == 1 ? SL_KE : SL_KO;
      constexpr int SPLIT = X_SPLIT, PARK1 = X_PARK;
      const uint32_t par = ((it + NST_Q / 2) >> 1) & 1;
      const int hsl = max((it >> 4) - 1, 0);
      const uint64_t dk = mkdesc(ring + slk * STAGE, 16), dv = mkdesc(ring + slv * STAGE, 16384);
      auto qk = [&]() {
#pragma unroll
        for (int k = 0; k < 8; k++) {
          if (KIND == 3) mma_n128_ss<0>(s, mkdesc(slot + hsl * STAGE, 16) + (k >> 2) * 512 + (k & 3) * 2, dk + (k >> 2) * 1024 + (k & 3) * 2, k > 0);
          else mma_n128<0>(s, q[4 * k], q[4 * k + 1], q[4 * k + 2], q[4 * k + 3], dk + (k >> 2) * 1024 + (k & 3) * 2, k > 0);
        }
        wg_commit();
      };
      auto pv = [&]() {
#pragma unroll
        for (int k = 0; k < 8; k++)
          mma_n128<1>(o, pf[4 * k], pf[4 * k + 1], pf[4 * k + 2], pf[4 * k + 3], dv + k * 128, k > 0 || KIND != 1 || (it & 15) != 1);
        wg_commit();
      };
      lp0 = l0; lp1 = l1;
#define TS(i)
      {
        TS(0)
        if (KIND == 3) {
          asm volatile("fence.proxy.async.shared::cta;" ::: "memory");
          const float t0 = lp0 + __shfl_xor_sync(0xffffffffu, lp0, 1), t1 = lp1 + __shfl_xor_sync(0xffffffffu, lp1, 1);
          i0 = rcp(t0 + __shfl_xor_sync(0xffffffffu, t0, 2));
          i1 = rcp(t1 + __shfl_xor_sync(0xffffffffu, t1, 2));
          asm volatile("" : "+f"(i0), "+f"(i1)::"memory");
          block_fence(31, zero);
#pragma unroll
          for (int k = 0; k < X_N1; k++) ldsm4(frag(hsl, k), q[4 * k], q[4 * k + 1], q[4 * k + 2], q[4 * k + 3]);
        }
        bar_sync(my_turn, 256);
        TS(1)
        if (KIND != 3) pin(q);
        pin(pf); pin(o);
        wg_fence();
        qk();
        TS(2)
        mbar_wait(full + 8 * slv, par);
        if (KIND == 1 && (it & 15) == 1) {
          park(o, hsl, PARK1, 8, i0, i1);
          wg_fence();
        }
        if (KIND == 3) {
#pragma unroll
          for (int k = X_N1; k < 8; k++) ldsm4(frag(hsl, k), q[4 * k], q[4 * k + 1], q[4 * k + 2], q[4 * k + 3]);
          block_fence(32, zero);
        }
        TS(3)
        pv();
        bar_arrive(other_turn, 256);
        TS(4)
        wg_wait<1>();
      }
      pin(s);
      mbar_arrive_cluster_now<10 * KIND + 3>(empty_c + 8 * slk, signaller, zero);
      TS(5)
      if (KIND == 3) {
        shift = false;
        n0 = n1 = l0 = l1 = 0.f;
      } else if (shift) {
        softmax_shift(s, n0, n1);
        pin(s);
      }
      softmax_exp<0, SPLIT>(s);
      pin(s);
      block_fence(10 * KIND + 4, zero);
      TS(6)
      wg_wait<0>();
      pin(o); pin(pf);
      mbar_arrive_cluster_now<10 * KIND + 5>(empty_c + 8 * slv, signaller, zero);
      TS(7)
      const bool kready = mbar_test(full + 8 * slkn, par);
      softmax_exp<SPLIT, 64>(s);
#pragma unroll
      for (int i = 0; i < 32; i++) pf[i] = pack2(s[2 * i], s[2 * i + 1]);
      row_sums(pf, l0, l1);
      if (KIND == 3) {
        park(o, hsl, 0, PARK1, i0, i1, X_IP);
        if (it) prof(wg, 6 + (it >> 4));
        if (it >= 32 && cw == 0) bar_arrive(BAR_HELPER, 64);
      }
      redo = !(l0 + l1 <= SUM_HI) || (KIND == 3 && fminf(l0, l1) < SUM_LO);
      const bool leave = __any_sync(0xffffffffu, redo || !kready);
      return leave;
    };
    int it = -1;
#pragma unroll 1
    while (true) {
      mbar_wait(full + 8 * ((it & 1) ? SL_KE : SL_KO), ((it + NST_Q / 2) >> 1) & 1);
      it++;
#pragma unroll 1
      while (true) {
        if (it & 1) {
          if (turn(it, IC<1>()) || it == 63) break;
          it++;
        }
        if (it & 15) {
          if (turn(it, IC<2>())) break;
        } else {
          if (turn(it, IC<3>())) break;
        }
        it++;
      }
      if (__any_sync(0xffffffffu, redo)) {
        const int j = it & 15;
        float sc0 = 1.f, sc1 = 1.f;
        if (j == 0) n0 = n1 = 3.0e38f;
        l0 = j ? lp0 : 0.f;
        l1 = j ? lp1 : 0.f;
        softmax_redo(pf, q, kc + (size_t)((hs * 2 + (it >> 5)) * SEQ + j * 128) * DH, lane, n0, n1, l0, l1, sc0, sc1);
        shift = true;
        if (j == 0) sc0 = sc1 = 1.f;
#pragma unroll
        for (int i = 0; i < 16; i++) { o[4 * i] *= sc0; o[4 * i + 1] *= sc0; o[4 * i + 2] *= sc1; o[4 * i + 3] *= sc1; }
      }
      if (it == 63) break;
    }
  }

#define TE(i) {}
  {
    constexpr int ST0 = NST_Q + NST_KV;
    float acc[32], red[32], first[32];
    auto await = [&](int st) { mbar_wait(full + 8 * (st & 3), (st >> 2) & 1); };
    auto release = [&](int st) { if (signaller) mbar_arrive_cluster(empty_c + 8 * (st & 3)); };
    auto unpark = [&](int h, int k0, int k1) {
#pragma unroll
      for (int k = 0; k < 8; k++)
        if (k >= k0 && k < k1) ldsm4(frag(h, k), oa[32 * h + 4 * k], oa[32 * h + 4 * k + 1], oa[32 * h + 4 * k + 2], oa[32 * h + 4 * k + 3]);
    };
    {
      float ar[64];
      asm volatile("fence.proxy.async.shared::cta;" ::: "memory");
      l0 += __shfl_xor_sync(0xffffffffu, l0, 1); l1 += __shfl_xor_sync(0xffffffffu, l1, 1);
      l0 += __shfl_xor_sync(0xffffffffu, l0, 2); l1 += __shfl_xor_sync(0xffffffffu, l1, 2);
      float f0 = rcp(l0), f1 = rcp(l1);
      asm volatile("" : "+f"(f0), "+f"(f1)::"memory");
      await(ST0 - 1);
      unpark(1, 0, 4);
      bar_sync(my_turn, 256);
      pin(pf); pin(o);
      wg_fence();
#pragma unroll
      for (int k = 0; k < 8; k++)
        mma_n128<1>(o, pf[4 * k], pf[4 * k + 1], pf[4 * k + 2], pf[4 * k + 3], mkdesc(ring + SL_KE * STAGE, 16384) + k * 128, 1);
      wg_commit();
      await(ST0);
      unpark(1, 4, 8);
      block_fence(61, zero);
#pragma unroll
      for (int k = 0; k < 8; k++) mma_n128_ss<1>(ar, mkdesc(slot, 16) + (k >> 2) * 512 + (k & 3) * 2, mkdesc(ring + (ST0 & 3) * STAGE, 16384) + k * 128, k > 0);
      wg_commit();
      bar_arrive(other_turn, 256);
      wg_wait<1>();
      pin(o); pin(pf);
      mbar_arrive_cluster_now<62>(empty_c + 8 * SL_KE, signaller, zero);
#pragma unroll
      for (int i = 0; i < 16; i++) {
        pf[2 * i] = pack2(o[4 * i] * f0, o[4 * i + 1] * f0);
        pf[2 * i + 1] = pack2(o[4 * i + 2] * f1, o[4 * i + 3] * f1);
      }
      pin(pf);
      prof(wg, 10);
#pragma unroll
      for (int u = 1; u < 4; u++) {
        await(ST0 + u);
        wg_wait<0>();
        release(ST0 + u - 1);
        bar_sync(my_turn, 256);
        wg_fence();
#pragma unroll
        for (int k = 0; k < 8; k++) {
          const uint32_t* a = (u == 1 ? oa + 32 : u == 2 ? pf : oa + 64) + 4 * k;
          mma_n128<1>(ar, a[0], a[1], a[2], a[3], mkdesc(ring + ((ST0 + u) & 3) * STAGE, 16384) + k * 128, 1);
        }
        wg_commit();
        bar_arrive(other_turn, 256);
        if (u < 3) {
          block_fence(62 + u, zero);
          unpark(u == 1 ? 2 : 0, 0, 8);
        }
      }
      mbar_wait(cx.sb + SM_BAR_MISC, 0);
      await(ST0 + 4);
      wg_wait<0>();
      release(ST0 + 3);
      pin(ar);
#pragma unroll
      for (int i = 0; i < 32; i++) { first[i] = ar[i]; red[i] = ar[32 + i]; }
    }
    const uint32_t tag = *(const uint32_t*)(cx.sp + SM_TAG);
    uint4* const xch = at<uint4>(cx.gs->part, (qb << 20) + lane * 16);
    auto send = [&](const float (&v)[32], int dst, int idx) {
      uint4* p = at<uint4>(xch, (dst * 8 + idx) * 2048);
#pragma unroll
      for (int i = 0; i < 4; i++)
        st_gran(p + i * 32, (pack2(v[8 * i], v[8 * i + 1]) & ~TAG_BIT) | tag, pack2(v[8 * i + 2], v[8 * i + 3]),
                pack2(v[8 * i + 4], v[8 * i + 5]), pack2(v[8 * i + 6], v[8 * i + 7]));
    };
    send(first, ((hs + 1) & 7) * 7, cw);
    int nrx = 1;
    auto half_step = [&](int s, auto hc, bool arrive) {
      constexpr int h = decltype(hc)::value;
      const int st = ST0 + 2 * s + h;
      const uint64_t db = mkdesc(ring + (st & 3) * STAGE, 16);
      bar_sync(my_turn, 256);
      if (h == 0) pin(pf);
#pragma unroll
      for (int i = 32 * h; i < 32 + 64 * h; i++) asm volatile("" : "+r"(oa[i])::"memory");
      wg_fence();
#pragma unroll
      for (int k = 0; k < 16; k++) {
        const int kb = h * 16 + k - 8;
        if (kb >= 0) mma_n64<1>(acc, oa[4 * kb], oa[4 * kb + 1], oa[4 * kb + 2], oa[4 * kb + 3], db + k * 128, 1);
        else mma_n64<1>(acc, pf[4 * k], pf[4 * k + 1], pf[4 * k + 2], pf[4 * k + 3], db + k * 128, k > 0);
      }
      wg_commit();
      if (arrive) bar_arrive(other_turn, 256);
    };
    auto source = [&](int n) { return at<const uint4>(xch, ((hs * 7 + n - 1) * 8 + cw) * 2048); };
    auto fetch = [&](uint32_t (&g)[16], const uint4* p) {
#pragma unroll
      for (int i = 0; i < 4; i++) ld_gran(p + i * 32, g[4 * i], g[4 * i + 1], g[4 * i + 2], g[4 * i + 3]);
    };
    uint32_t g[16];
#pragma unroll 1
    for (int s = 2; s < 8; s++) {
      const int st = ST0 + 2 * s;
      half_step(s, IC<0>(), true);
      if (s == 2) {
        bar_arrive(BAR_OA, 352);
        send(red, 56 + cw, hs);
#pragma unroll
        for (int i = 0; i < 32; i++) red[i] = 0.f;
      }
      await(st + 1);
      if (s > 3 && granules_ok(g, tag)) { add_granules(red, g); nrx++; }
      if (X_XS == 1 && s > 2) fetch(g, source(nrx));
      wg_wait<0>();
      if (s < 7) release(st);
      if (X_XS == 0 && s > 2) fetch(g, source(nrx));
      half_step(s, IC<1>(), true);
      await(st + 2);
      wg_wait<0>();
      if (s < 7) release(st + 1);
      pin(acc);
      if (s == 7) prof(wg, 19);
      if (s == 7) TE(0)
      send(acc, ((hs + s) & 7) * 7 + s - 1, cw);
    }
    TE(1)
    uint32_t xv[16], gt[16];
    {
      const int s = 8;
      uint32_t g2[16];
      half_step(s, IC<0>(), true);
      TE(2)
      await(NST_Q + NST_KV + NST_O - 1);
      cluster_arrive();
      mbar_wait(cx.sb + SM_BAR_XG, 0);
      const uint32_t tile = cx.sb + SM_XO + wg * 8192 + lo;
      if (granules_ok(g, tag)) { add_granules(red, g); nrx++; }
      fetch(g, source(nrx));
      block_fence(58, zero);
      wg_wait<0>();
      TE(3)
#pragma unroll
      for (int k = 0; k < 4; k++) ldsm4((tile ^ (k << 5)) + STAGE, gt[4 * k], gt[4 * k + 1], gt[4 * k + 2], gt[4 * k + 3]);
      half_step(s, IC<1>(), wg == 0);
      TE(4)
      block_fence(56, zero);
      const bool ok = granules_ok(g, tag);
      block_fence(57, zero + ok * 1000);
      const uint4* src = source(7);
      fetch(g2, src);
#pragma unroll
      for (int k = 0; k < 4; k++) ldsm4(tile ^ (k << 5), xv[4 * k], xv[4 * k + 1], xv[4 * k + 2], xv[4 * k + 3]);
      if (ok) { add_granules(red, g); nrx++; }
      TE(5)
      block_fence(59, zero);
      wg_wait<0>();
      pin(acc);
      TE(6)
#pragma unroll
      for (int i = 0; i < 32; i++) red[i] += acc[i];
      pin(red);
      TE(7)
      int n = 7;
#pragma unroll 1
      for (int spins = 0; spins < (1 << 16); spins++) {
        if (granules_ok(g2, tag)) {
          add_granules(red, g2);
          if (--n < nrx) {
            break;
          }
          src -= 1024;
        }
        fetch(g2, src);
      }
      TE(8)
    }
    prof(wg, 20);
    TE(9)
    const uint32_t ot = ring + ((ST0 + NST_O) & 3) * STAGE + cw * (16 * 144);
    uint32_t ow[16];
#pragma unroll
    for (int i = 0; i < 16; i++) ow[i] = fma2(pack2(red[2 * i], red[2 * i + 1]), gt[i], xv[i]);
#pragma unroll
    for (int i = 0; i < 4; i++)
      stsm4(ot + (lane & 15) * 144 + (2 * i + (lane >> 4)) * 16, ow[4 * i], ow[4 * i + 1], ow[4 * i + 2], ow[4 * i + 3]);
    __syncwarp();
#pragma unroll
    for (int i = 0; i < 4; i++) {
      uint4 v;
      lds128(ot + (i * 4 + (lane >> 3)) * 144 + (lane & 7) * 16, v.x, v.y, v.z, v.w);
      at<uint4>(out, ((qb * 128 + cw * 16 + (lane >> 3)) * DM + hs * 64 + (lane & 7) * 8) * 2)[i * (4 * DM / 8)] = v;
    }
    TE(10)
    prof(wg, 22);
  }
}

constexpr int AST_X = 6, AST_F = AST_X + 96;
__device__ __forceinline__ void aux_producer(const Ctx& cx, int f, const CUtensorMap* tmWq, const CUtensorMap* tmG) {
  const uint32_t full = cx.sb + SM_FULL, empty = cx.sb + SM_EMPTY;
  if (X_AD) __nanosleep(X_AD);
  if (elect_one()) {
#pragma unroll 1
    for (int st = 0; st < AST_X; st++) {
      mbar_expect_tx(full + 8 * st, FSTAGE);
#pragma unroll
      for (int i = 0; i < 3; i++)
        tma2d_stream(cx.sb + st * FSTAGE + i * 8192, tmWq, (2 * f + (st & 1)) * 512 + 448, (st >> 1) * 192 + i * 64, full + 8 * st);
    }
  }
  __syncwarp();
  mbar_wait(cx.sb + SM_BAR_MISC, 0);
  proxy_fence();
  int st = AST_X;
#pragma unroll 1
  for (; st < AST_F; st++) {
    const uint32_t sl = st & 7;
    mbar_wait(empty + 8 * sl, ((st >> 3) & 1) ^ 1);
    if (elect_one()) {
      mbar_expect_tx(full + 8 * sl, FSTAGE);
      bulk_load(cx.sb + sl * FSTAGE, cx.gs->xn + (st - AST_X) * (FSTAGE / 16), FSTAGE, full + 8 * sl);
    }
    __syncwarp();
  }
#pragma unroll 1
  for (int pair = 0; pair < 14; pair++) {
#pragma unroll 1
    for (int u = 0; u < 12; u++, st++) {
      const uint32_t sl = st & 7;
      const int unit = pair * 2 + (u & 1), k = u >> 1;
      if (unit == 27) continue;
      const bool gu = pair < 9;
      mbar_wait(empty + 8 * sl, ((st >> 3) & 1) ^ 1);
      if (elect_one()) {
        mbar_expect_tx(full + 8 * sl, FSTAGE);
        tma2d_stream(cx.sb + sl * FSTAGE, tmG + (gu ? k >= 3 : 2), gu ? f * 1152 + unit * 64 : (unit - 18) * 64,
                     gu ? (k >= 3 ? k - 3 : k) * 192 : f * 1152 + k * 192, full + 8 * sl);
      }
      __syncwarp();
    }
  }
}

constexpr int BAR_FREE = 4, BAR_TILE = 6;
__device__ __forceinline__ void aux_helper(const Ctx& cx, int f, int warp, int lane) {
  unsigned epoch = 0;
  if (lane == 0) epoch = cx.gs->launch[blockIdx.x] + 1;
  epoch = __shfl_sync(0xffffffffu, epoch, 0);
  bar_sync(BAR_OA, 96);
  if (warp == 3) {
    if (lane == 0) cx.gs->launch[blockIdx.x] = epoch;
    await_count(at<const unsigned>(cx.gs->rows, (lane & 15) * 128), 8 * epoch, 200);
    if (lane == 0) mbar_arrive(cx.sb + SM_BAR_MISC);
    prof(0, 1, 31);
    await_count(at<const unsigned>(cx.gs->rows, (lane & 15) * 128 + 4), 8 * epoch, 500);
    uint32_t bound = 0xFFFFFFFFu, m0 = 0, m1 = 0;
#pragma unroll 1
    for (int k = 0; k < TOPC; k++) {
      if (__any_sync(0xffffffffu, m0 == 0)) {
        m0 = m1 = 0;
#pragma unroll 2
        for (int i = 0; i < 16; i++) {
          const uint4 v = __ldcg(at<const uint4>(cx.gs->key, lane * 16 + i * 512));
          const uint32_t w[4] = {v.x, v.y, v.z, v.w};
#pragma unroll
          for (int j = 0; j < 4; j++) {
            const uint32_t t = w[j] <= bound ? w[j] : 0;
            m1 = max(m1, min(m0, t));
            m0 = max(m0, t);
          }
        }
      }
      uint32_t m = m0;
      m = __reduce_max_sync(0xffffffffu, m);
      bound = m - 1;
      if (m0 == m) { m0 = m1; m1 = 0; }
      if (f == 0 && lane == 0) *at<uint32_t>(cx.gs->top, k * 4) = m;
#pragma unroll
      for (int j = 0; j < 3; j++) {
        const uint32_t row = 0xFFFF - (m & 0xFFFF), i = min(j * 4 + (lane >> 3), 8);
        *(uint4*)(cx.sp + SM_XSEL + i * 1024 + k * 128 + (((lane ^ k) & 7) << 4)) =
            __ldcg(at<const uint4>(cx.gs->xn, xn_offset(row, (lane & 7) * 4) + i * 8192));
      }
    }
    asm volatile("fence.proxy.async.shared::cta;" ::: "memory");
    prof(0, 2, 31);
  } else {
    const int wg = warp - 1;
#pragma unroll 1
    for (int u = 0; u < 32; u++) {
      bar_arrive(BAR_FREE + wg, 160);
      bar_sync(BAR_TILE + wg, 160);
      if (elect_one()) {
        const int n = (u >> 1) * 8 + 2 * f + wg;
        asm volatile("cp.async.bulk.global.shared::cta.bulk_group [%0], [%1], 8192;\ncp.async.bulk.commit_group;\ncp.async.bulk.wait_group 0;"
                     ::"l"(cx.gs->q3 + (n * 2 + (u & 1)) * 512), "r"(cx.sb + SM_H + wg * 8192) : "memory");
        if (u & 1) st_release(&cx.gs->q3_flag[n], epoch);
      }
      __syncwarp();
    }
  }
  bar_arrive(3, 352);
}

__device__ __forceinline__ void aux_consumer(const Ctx& cx, int f, int wg, int cw, int lane) {
  const int r = lane >> 2, c = lane & 3, tid = cw * 32 + lane;
  const uint32_t full = cx.sb + SM_FULL, empty = cx.sb + SM_EMPTY;
  const bool signaller = (tid & 127) == 0;
  auto await = [&](int st) { mbar_wait(full + 8 * (st & 7), (st >> 3) & 1); };
  auto release = [&](int st, int cnt) {
    asm volatile("{\n.reg .pred p;\nsetp.ne.u32 p, %2, 0;\n@p mbarrier.arrive.shared::cta.b64 _, [%0], %1;\n}"
                 ::"r"(empty + 8 * (st & 7)), "r"(cnt), "r"((uint32_t)signaller) : "memory");
  };
  prof(wg, 0);
  {
    const uint32_t lt = ((lane & 7) + (lane >> 4) * 8) * 128 + ((((cw & 3) * 2 + ((lane >> 3) & 1)) ^ (lane & 7)) << 4);
    uint32_t wa[144];
#pragma unroll
    for (int i = 0; i < 3; i++) {
      await(2 * i + wg);
#pragma unroll
      for (int k = 0; k < 12; k++) {
        const int kb = 12 * i + k;
        ldsm4t(cx.sb + (2 * i + wg) * FSTAGE + k * 2048 + lt, wa[4 * kb], wa[4 * kb + 1], wa[4 * kb + 2], wa[4 * kb + 3]);
      }
    }
    bar_sync(1, 256);
#pragma unroll
    for (int i = 0; i < 3; i++) release(2 * i + wg, 2);
    if (wg) bar_arrive(1, 256);
#pragma unroll 1
    for (int st = AST_X; st < AST_F; st += 3) {
      float acc[32];
      await(st);
      await(st + 1);
      await(st + 2);
      bar_sync(1 + wg, 256);
      wg_fence();
#pragma unroll
      for (int kb = 0; kb < 36; kb++) {
        const int i = kb / 12, k = kb % 12;
        mma_n64<0>(acc, wa[4 * kb], wa[4 * kb + 1], wa[4 * kb + 2], wa[4 * kb + 3],
                   mkdesc(cx.sb + ((st + i) & 7) * FSTAGE, 16) + (k >> 2) * 512 + (k & 3) * 2, kb > 0);
        if (k == 11) wg_commit();
      }
      if (st < AST_F - 3 || !wg) bar_arrive(2 - wg, 256);
      wg_wait<1>();
      release(st, 1);
      release(st + 1, 1);
      bar_sync(BAR_FREE + wg, 160);
      wg_wait<0>();
      pin(acc);
      release(st + 2, 1);
#pragma unroll
      for (int k = 0; k < 4; k++)
        stsm4t(cx.sb + SM_H + wg * 8192 + k * 2048 + lt, pack2(acc[8 * k] * SM_SCALE_LOG2, acc[8 * k + 1] * SM_SCALE_LOG2),
               pack2(acc[8 * k + 2] * SM_SCALE_LOG2, acc[8 * k + 3] * SM_SCALE_LOG2),
               pack2(acc[8 * k + 4] * SM_SCALE_LOG2, acc[8 * k + 5] * SM_SCALE_LOG2),
               pack2(acc[8 * k + 6] * SM_SCALE_LOG2, acc[8 * k + 7] * SM_SCALE_LOG2));
      asm volatile("fence.proxy.async.shared::cta;" ::: "memory");
      bar_arrive(BAR_TILE + wg, 160);
    }
    bar_sync(3, 352);
  }
  prof(wg, 3);
#pragma unroll 1
  for (int unit = wg; unit < 27; unit += 2) {
    if (unit >> 1 == 9) {
      asm volatile("fence.proxy.async.shared::cta;" ::: "memory");
      bar_sync(3, 256);
      prof(wg, 4);
    }
    const bool gu = unit < 18;
    float a0[4], a1[4];
#pragma unroll 1
    for (int m = 0; m < 2; m++) {
      float p0[4], p1[4];
      int st = AST_F + (unit >> 1) * 12 + m * 6 + wg;
      uint32_t b = cx.sb + (gu ? SM_XSEL : SM_H + m * 9216);
#pragma unroll 1
      for (int u = 0; u < 3; u++, st += 2, b += 3072) {
        await(st);
        wg_fence();
        const uint64_t da = mkdesc(cx.sb + (st & 7) * FSTAGE, 16), db = mkdesc(b, 16);
#pragma unroll
        for (int k = 0; k < 12; k++) mma_n8((k & 1) ? p1 : p0, da + k * 128, db + (k >> 2) * 64 + (k & 3) * 2, u > 0 || k > 1);
        wg_commit();
        wg_wait<1>();
        if (u) release(st - 2, 2);
      }
      wg_wait<0>();
      release(st - 2, 2);
      pin(p0); pin(p1);
#pragma unroll
      for (int i = 0; i < 4; i++) { a0[i] = a1[i]; a1[i] = p0[i] + p1[i]; }
    }
#pragma unroll
    for (int i = 0; i < 4; i++) {
      const int fl = (cw & 3) * 16 + r + (i >> 1) * 8, tok = 2 * c + (i & 1);
      if (gu) {
        const float h = bfr(silu_f(bfr(a0[i]))) * bfr(a1[i]);
        *(__nv_bfloat16*)(cx.sp + SM_H + unit * 1024 + tok * 128 + (((fl >> 3) ^ tok) << 4) + (fl & 7) * 2) = __float2bfloat16_rn(h);
      } else {
        *at<float>(cx.gs->ypart, ((f * TOPC + tok) * DM + (unit - 18) * 64 + fl) * 4) = a0[i] + a1[i];
      }
    }
  }
  prof(wg, 5);
  bar_sync(3, 256);
  if (tid == 0) red_release(&cx.gs->ycnt);
  prof(wg, 6);
}

struct Maps { CUtensorMap m[9]; };
__global__ void __cluster_dims__(2, 1, 1) __launch_bounds__(THREADS, 1)
fused_kernel(const __nv_bfloat16* __restrict__ x, const __nv_bfloat16* __restrict__ w_r, const __nv_bfloat16* __restrict__ wq,
             const __nv_bfloat16* __restrict__ wo, __nv_bfloat16* __restrict__ out, Scratch* gs,
             const __grid_constant__ Maps maps, const __nv_bfloat16* __restrict__ kc) {
  const CUtensorMap &tmX = maps.m[0], &tmWq = maps.m[1], &tmK = maps.m[2], &tmV = maps.m[3], &tmWo = maps.m[4];
  extern __shared__ __align__(1024) uint8_t smem_raw[];
  prof(0, 23, 511);
  if (threadIdx.x < 72 && blockIdx.x < N_ATT_CTA)
    asm volatile("prefetch.global.L2 [%0];" ::"l"(at<const void>(x, ((blockIdx.x >> 3) * 128 + (blockIdx.x & 7) * 8) * (DM * 2) + threadIdx.x * 128)));
  Ctx cx;
  cx.sb = smem_u32(smem_raw);
  cx.sp = smem_raw;
  cx.gs = gs;
  cx.rank = blockIdx.x & 1;
  const int warp = __shfl_sync(0xffffffffu, threadIdx.x >> 5, 0);
  const int cluster = blockIdx.x >> 1;
  const bool is_ffn = blockIdx.x >= N_ATT_CTA;
  const int c7 = ((cluster - 36) * 37) >> 8;
  const int hs = cluster < 4 ? 4 + cluster : cluster < 36 ? (cluster - 4) >> 3 : 4 + c7;
  const int qb = (cluster < 4 ? 0 : cluster < 36 ? (cluster - 4) & 7 : cluster - 35 - 7 * c7) * 2 + cx.rank;

  extern __shared__ __align__(1024) uint8_t smem_alias[];
  const uint32_t xf = smem_u32(smem_alias) + SM_MISC + warp * 24;
  if (warp == 4 && elect_one()) prefetch_tmap(&tmX);
  if (elect_one()) {
    const uint32_t cnt = (warp > 4 && warp < 8) ? (is_ffn ? 2 : 4) : 1;
#pragma unroll
    for (int i = 0; i < 3; i++) mbar_init(xf + 8 * i, cnt);
    asm volatile("fence.proxy.async.shared::cta;" ::: "memory");
    asm volatile("fence.mbarrier_init.release.cluster;" ::: "memory");
  }
  __syncwarp();
  cluster_arrive();
  if (warp == 4 && !is_ffn) {
    if (elect_one()) {
      profc(0, 28);
#pragma unroll
      for (int i = 0; i < 3; i++) {
        mbar_expect_tx(xf + 8 * i, 24576);
        tma3d(xf - SM_XFULL + SM_X + i * 24576, &tmX, qb * 128, i * 3, xf + 8 * i);
      }
      profc(0, 29);
    }
  } else if (warp > 7 && elect_one()) {
    prefetch_tmap(&tmX + (is_ffn ? warp - 4 : warp == 8 ? 8 : warp - 8));
  }
  __syncwarp();

  if (warp < 4) {
    asm volatile("setmaxnreg.dec.sync.aligned.u32 24;");
    cluster_wait();
    prof(0, 24, 511);
    if (warp == 0) {
      if (!is_ffn) attn_producer(cx, qb, hs, &tmX, &tmK, &tmV, &tmWq, &tmWo);
      else aux_producer(cx, blockIdx.x - N_ATT_CTA, &tmWq, &maps.m[5]);
      prof(0, 25, 511);
    } else if (!is_ffn) {
      attn_rows(cx, qb, hs, 3 - warp, read_lane(), &maps.m[8], w_r);
      if (warp == 1) attn_helper(cx, qb, hs, read_lane(), wo, &maps.m[8]);
      else bar_sync(BAR_OA, 352);
      attn_finish8(cx, qb, hs, warp - 1, read_lane(), out);
    } else {
      aux_helper(cx, blockIdx.x - N_ATT_CTA, warp, read_lane());
    }
    __syncwarp();
    cluster_arrive();
    cluster_wait();
    if (threadIdx.x == 32) { dly(cx, 201); dly(cx, 251); }
  } else {
    asm volatile("setmaxnreg.inc.sync.aligned.u32 240;");
    cluster_wait();
    const int cw = warp - 4, wg = cw >> 2;
    if (is_ffn) aux_consumer(cx, blockIdx.x - N_ATT_CTA, wg, cw, read_lane());
    else attn_consumer(cx, qb, hs, wg, cw, read_lane(), x, kc, out);
  }
}

typedef CUresult (*EncodeFn)(CUtensorMap*, CUtensorMapDataType, cuuint32_t, void*, const cuuint64_t*, const cuuint64_t*,
                             const cuuint32_t*, const cuuint32_t*, CUtensorMapInterleave, CUtensorMapSwizzle,
                             CUtensorMapL2promotion, CUtensorMapFloatOOBfill);

void encode(EncodeFn fn, CUtensorMap* m, const void* p, int rank, const cuuint64_t* dims, const cuuint64_t* strides,
            const cuuint32_t* box) {
  const cuuint32_t es[5] = {1, 1, 1, 1, 1};
  fn(m, CU_TENSOR_MAP_DATA_TYPE_BFLOAT16, rank, const_cast<void*>(p), dims, strides, box, es, CU_TENSOR_MAP_INTERLEAVE_NONE,
     CU_TENSOR_MAP_SWIZZLE_128B, CU_TENSOR_MAP_L2_PROMOTION_L2_128B, CU_TENSOR_MAP_FLOAT_OOB_FILL_NONE);
}
void encode2d(EncodeFn fn, CUtensorMap* m, const void* p, uint64_t rows, uint64_t cols, uint32_t box_rows) {
  const cuuint64_t dims[2] = {cols, rows}, strides[1] = {cols * 2};
  const cuuint32_t box[2] = {64, box_rows};
  encode(fn, m, p, 2, dims, strides, box);
}

}

extern "C" void kernel_launch(void* const* d_in, const int* in_sizes, int n_in, void* d_out, int out_size) {
  (void)in_sizes; (void)n_in; (void)out_size;
  void* fnp = nullptr;
  cudaDriverEntryPointQueryResult qr;
  cudaGetDriverEntryPoint("cuTensorMapEncodeTiled", &fnp, cudaEnableDefault, &qr);
  EncodeFn fn = (EncodeFn)fnp;
  void* gs = nullptr;
  cudaGetSymbolAddress(&gs, g_scratch);
  Maps maps;
  CUtensorMap &tmX = maps.m[0], &tmWq = maps.m[1], &tmK = maps.m[2], &tmV = maps.m[3], &tmWo = maps.m[4], &tmG = maps.m[5],
              &tmU = maps.m[6], &tmD = maps.m[7];
  encode2d(fn, &tmK, d_in[1], 16 * SEQ, DH, 128);
  encode2d(fn, &tmV, d_in[2], 16 * SEQ, DH, 128);
  encode2d(fn, &tmWq, d_in[3], DM, 4096, 64);
  {
    const cuuint64_t dims[3] = {64, SEQ, 9}, strides[2] = {DM * 2, 128};
    const cuuint32_t box[3] = {64, 64, 3};
    encode(fn, &tmX, d_in[0], 3, dims, strides, box);
  }
  encode2d(fn, &maps.m[8], d_in[0], SEQ, DM, 16);
  encode2d(fn, &tmWo, d_in[4], 4096, DM, 128);
  encode2d(fn, &tmG, d_in[7], DM, FF, 192);
  encode2d(fn, &tmU, d_in[8], DM, FF, 192);
  encode2d(fn, &tmD, d_in[9], FF, DM, 192);
  cudaFuncSetAttribute(fused_kernel, cudaFuncAttributeMaxDynamicSharedMemorySize, SM_TOTAL);
  fused_kernel<<<N_CTA, THREADS, SM_TOTAL>>>((const __nv_bfloat16*)d_in[0], (const __nv_bfloat16*)d_in[6], (const __nv_bfloat16*)d_in[3],
                                            (const __nv_bfloat16*)d_in[4], (__nv_bfloat16*)d_out, (Scratch*)gs, maps, (const __nv_bfloat16*)d_in[1]);
}
```

```cpp
#include <cuda_runtime.h>
#include <cuda_bf16.h>
#include <cuda.h>
#include <stdint.h>

namespace {

constexpr int SEQ = 2048, DM = 576, DH = 128, FF = 4608, TOPC = 8;
constexpr int N_ATT_CTA = 128, N_CTA = 132;
constexpr int THREADS = 384;

constexpr uint32_t SM_RING = 0;
constexpr uint32_t STAGE = 32768;
constexpr uint32_t SM_SLOT = 131072;
constexpr uint32_t FSTAGE = 24576;
constexpr uint32_t SM_XSEL = 196608;
constexpr uint32_t SM_H = 205824;
constexpr uint32_t SM_MISC = 229376;
constexpr uint32_t SM_FULL = SM_MISC, SM_BAR_MISC = SM_MISC + 64, SM_BAR_XG = SM_MISC + 72, SM_BAR_P8 = SM_MISC + 80, SM_BAR_Q3 = SM_MISC + 88, SM_XFULL = SM_MISC + 96,
                   SM_EMPTY = SM_MISC + 120, SM_BAR_ROWS = SM_MISC + 216, SM_TAG = SM_MISC + 288,
                   SM_ROWS = SM_MISC + 304, SM_BOX8 = SM_MISC + 1024;
constexpr uint32_t SM_TOTAL = SM_MISC + 3072;
constexpr uint32_t SM_X = SM_MISC - 147456;

constexpr int BAR_ROWS = 6, BAR_HELPER = 7, BAR_OA = 8;
constexpr int NST_Q = 18, NST_KV = 128, NST_O = 18;
constexpr uint32_t SL_KE = (NST_Q - 1) & 3, SL_VE = NST_Q & 3, SL_KO = (NST_Q + 1) & 3, SL_VO = (NST_Q + 2) & 3;
#define X_N1 5
#define X_SPLIT 44
#define X_PARK 5
#define X_C0 32
#define X_C1 40
#define X_C2 56
constexpr float SM_SCALE_LOG2 = 0.08838834764831845f * 1.4426950408889634f;

struct Scratch {
  uint4 part[16 * 64 * 2 * 4 * 128];
  uint4 gate[N_ATT_CTA * 144 * 8];
  uint4 q3[N_ATT_CTA * 1024];
  uint4 xn[SEQ * DM / 8];
  uint32_t key[SEQ];
  float ypart[4 * TOPC * DM];
  uint32_t top[32];
  unsigned launch[160];
  unsigned rows[16 * 32];
  unsigned q3_flag[N_ATT_CTA];
  unsigned ycnt;
};
__device__ __align__(1024) Scratch g_scratch;

__device__ __forceinline__ void prof(int, int, int = 0) {}
__device__ __forceinline__ void profc(int, int) {}

__device__ __forceinline__ uint32_t smem_u32(const void* p) { return (uint32_t)__cvta_generic_to_shared(p); }
__device__ __forceinline__ void mbar_init(uint32_t bar, uint32_t cnt) {
  asm volatile("mbarrier.init.shared::cta.b64 [%0], %1;" ::"r"(bar), "r"(cnt) : "memory");
}
__device__ __forceinline__ void mbar_expect_tx(uint32_t bar, uint32_t bytes) {
  asm volatile("mbarrier.arrive.expect_tx.shared::cta.b64 _, [%0], %1;" ::"r"(bar), "r"(bytes) : "memory");
}
__device__ __forceinline__ void mbar_arrive(uint32_t bar) {
  asm volatile("mbarrier.arrive.shared::cta.b64 _, [%0];" ::"r"(bar) : "memory");
}
__device__ __forceinline__ void mbar_arrive_cluster(uint32_t bar_cluster_addr) {
  asm volatile("mbarrier.arrive.shared::cluster.b64 _, [%0];" ::"r"(bar_cluster_addr) : "memory");
}
template <int ID>
__device__ __forceinline__ void mbar_arrive_cluster_now(uint32_t bar_cluster_addr, bool pred, uint32_t zero) {
  asm volatile("{\n.reg .pred p, q;\nsetp.ne.u32 p, %1, 0;\nsetp.eq.u32 q, %2, %3;\n"
               "ARR_LOOP:\n@p mbarrier.arrive.shared::cluster.b64 _, [%0];\n@q bra.uni ARR_LOOP;\n}"
               ::"r"(bar_cluster_addr), "r"((uint32_t)pred), "r"(zero), "n"(ID) : "memory");
}
__device__ __forceinline__ void block_fence(int id, uint32_t zero = blockIdx.y) {
  asm volatile("{\n.reg .pred q;\nsetp.eq.u32 q, %0, %1;\nBF_LOOP:\n@q st.volatile.shared.u32 [%0], %0;\n@q bra.uni BF_LOOP;\n}"
               ::"r"(zero), "r"(id) : "memory");
}
__device__ __forceinline__ bool mbar_test(uint32_t bar, uint32_t parity) {
  uint32_t ok;
  asm volatile("{\n.reg .pred p;\nmbarrier.test_wait.parity.shared::cta.b64 p, [%1], %2;\nselp.u32 %0, 1, 0, p;\n}"
               : "=r"(ok) : "r"(bar), "r"(parity) : "memory");
  return ok;
}
__device__ __forceinline__ void mbar_wait(uint32_t bar, uint32_t parity) {
  asm volatile("{\n.reg .pred p, q;\n.reg .u32 n;\nmov.u32 n, 0;\n"
               "WAIT_LOOP:\nmbarrier.try_wait.parity.shared::cta.b64 p, [%0], %1;\n"
               "add.u32 n, n, 1;\nsetp.lt.u32 q, n, 4194304;\nand.pred q, q, !p;\n@q bra WAIT_LOOP;\n}"
               ::"r"(bar), "r"(parity) : "memory");
}
__device__ __forceinline__ uint32_t mapa(uint32_t addr, uint32_t rank) {
  uint32_t r;
  asm volatile("mapa.shared::cluster.u32 %0, %1, %2;" : "=r"(r) : "r"(addr), "r"(rank));
  return r;
}
__device__ __forceinline__ void cluster_arrive() { asm volatile("barrier.cluster.arrive.relaxed.aligned;" ::: "memory"); }
__device__ __forceinline__ bool elect_one() {
  uint32_t p;
  asm volatile("{\n.reg .pred p;\nelect.sync _|p, 0xffffffff;\nselp.u32 %0, 1, 0, p;\n}" : "=r"(p));
  return p;
}
__device__ __forceinline__ int read_lane() { return threadIdx.x & 31; }
__device__ __forceinline__ void cluster_wait() { asm volatile("barrier.cluster.wait.acquire.aligned;" ::: "memory"); }
__device__ __forceinline__ void bar_sync(int id, int n) { asm volatile("barrier.cta.sync %0, %1;" ::"r"(id), "r"(n) : "memory"); }
__device__ __forceinline__ void bar_arrive(int id, int n) { asm volatile("barrier.cta.arrive %0, %1;" ::"r"(id), "r"(n) : "memory"); }

__device__ __forceinline__ uint64_t policy_evict_first() {
  uint64_t p;
  asm("createpolicy.fractional.L2::evict_first.b64 %0, 1.0;" : "=l"(p));
  return p;
}
__device__ __forceinline__ uint64_t policy_evict_normal() {
  uint64_t p;
  asm("createpolicy.fractional.L2::evict_normal.b64 %0, 1.0;" : "=l"(p));
  return p;
}
__device__ __forceinline__ void tma3d(uint32_t dst, const CUtensorMap* tm, int c1, int c2, uint32_t bar) {
  asm volatile("cp.async.bulk.tensor.3d.shared::cluster.global.mbarrier::complete_tx::bytes [%0], [%1, {%2, %3, %4}], [%5];"
               ::"r"(dst), "l"(tm), "r"(0), "r"(c1), "r"(c2), "r"(bar) : "memory");
}
__device__ __forceinline__ void tma2d(uint32_t dst, const CUtensorMap* tm, int c0, int c1, uint32_t bar) {
  asm volatile("cp.async.bulk.tensor.2d.shared::cluster.global.mbarrier::complete_tx::bytes [%0], [%1, {%2, %3}], [%4];"
               ::"r"(dst), "l"(tm), "r"(c0), "r"(c1), "r"(bar) : "memory");
}
__device__ __forceinline__ void tma2d_stream(uint32_t dst, const CUtensorMap* tm, int c0, int c1, uint32_t bar) {
  asm volatile("{\n.reg .b64 pol;\ncreatepolicy.fractional.L2::evict_first.b64 pol, 1.0;\n"
               "cp.async.bulk.tensor.2d.shared::cluster.global.mbarrier::complete_tx::bytes.L2::cache_hint [%0], [%1, {%2, %3}], [%4], pol;\n}"
               ::"r"(dst), "l"(tm), "r"(c0), "r"(c1), "r"(bar) : "memory");
}
__device__ __forceinline__ void tma2d_prefetch(const CUtensorMap* tm, int c0, int c1) {
  asm volatile("cp.async.bulk.prefetch.tensor.2d.L2.global [%0, {%1, %2}];" ::"l"(tm), "r"(c0), "r"(c1) : "memory");
}
__device__ __forceinline__ void prefetch_l2(const void* p, uint32_t bytes) {
  asm volatile("cp.async.bulk.prefetch.L2.global [%0], %1;" ::"l"(p), "r"(bytes) : "memory");
}
__device__ __forceinline__ void prefetch_tmap(const CUtensorMap* tm) {
  asm volatile("prefetch.tensormap [%0];" ::"l"(tm) : "memory");
}

__device__ __forceinline__ void wg_fence() { asm volatile("wgmma.fence.sync.aligned;" ::: "memory"); }
__device__ __forceinline__ void wg_commit() { asm volatile("wgmma.commit_group.sync.aligned;" ::: "memory"); }
template <int N> __device__ __forceinline__ void wg_wait() { asm volatile("wgmma.wait_group.sync.aligned %0;" ::"n"(N) : "memory"); }

__device__ __forceinline__ uint64_t mkdesc(uint32_t addr, uint32_t lbo_bytes) {
  return (uint64_t)(((addr & 0x3FFFF) >> 4) | ((lbo_bytes >> 4) << 16)) | ((uint64_t)0x40000040u << 32);
}
template <int N> __device__ __forceinline__ void pin(float (&a)[N]) {
#pragma unroll
  for (int i = 0; i < N; i++) asm volatile("" : "+f"(a[i])::"memory");
}
template <int N> __device__ __forceinline__ void pin(uint32_t (&a)[N]) {
#pragma unroll
  for (int i = 0; i < N; i++) asm volatile("" : "+r"(a[i])::"memory");
}

#define F8(d, o) "+f"(d[o]), "+f"(d[o + 1]), "+f"(d[o + 2]), "+f"(d[o + 3]), "+f"(d[o + 4]), "+f"(d[o + 5]), "+f"(d[o + 6]), "+f"(d[o + 7])
#define R32A "%0, %1, %2, %3, %4, %5, %6, %7, %8, %9, %10, %11, %12, %13, %14, %15, %16, %17, %18, %19, %20, %21, %22, %23, %24, %25, %26, %27, %28, %29, %30, %31"
#define R32B "%32, %33, %34, %35, %36, %37, %38, %39, %40, %41, %42, %43, %44, %45, %46, %47, %48, %49, %50, %51, %52, %53, %54, %55, %56, %57, %58, %59, %60, %61, %62, %63"

template <int TB>
__device__ __forceinline__ void mma_n128(float (&d)[64], uint32_t a0, uint32_t a1, uint32_t a2, uint32_t a3, uint64_t db, int acc) {
  asm volatile("{\n.reg .pred p;\nsetp.ne.b32 p, %69, 0;\n"
               "wgmma.mma_async.sync.aligned.m64n128k16.f32.bf16.bf16 {" R32A ", " R32B "}, {%64, %65, %66, %67}, %68, p, 1, 1, %70;\n}\n"
               : F8(d, 0), F8(d, 8), F8(d, 16), F8(d, 24), F8(d, 32), F8(d, 40), F8(d, 48), F8(d, 56)
               : "r"(a0), "r"(a1), "r"(a2), "r"(a3), "l"(db), "r"(acc), "n"(TB));
}
template <int TB>
__device__ __forceinline__ void mma_n128_ss(float (&d)[64], uint64_t da, uint64_t db, int acc) {
  asm volatile("{\n.reg .pred p;\nsetp.ne.b32 p, %66, 0;\n"
               "wgmma.mma_async.sync.aligned.m64n128k16.f32.bf16.bf16 {" R32A ", " R32B "}, %64, %65, p, 1, 1, 0, %67;\n}\n"
               : F8(d, 0), F8(d, 8), F8(d, 16), F8(d, 24), F8(d, 32), F8(d, 40), F8(d, 48), F8(d, 56)
               : "l"(da), "l"(db), "r"(acc), "n"(TB));
}
template <int TB>
__device__ __forceinline__ void mma_n64(float (&d)[32], uint32_t a0, uint32_t a1, uint32_t a2, uint32_t a3, uint64_t db, int acc) {
  asm volatile("{\n.reg .pred p;\nsetp.ne.b32 p, %37, 0;\n"
               "wgmma.mma_async.sync.aligned.m64n64k16.f32.bf16.bf16 {" R32A "}, {%32, %33, %34, %35}, %36, p, 1, 1, %38;\n}\n"
               : F8(d, 0), F8(d, 8), F8(d, 16), F8(d, 24)
               : "r"(a0), "r"(a1), "r"(a2), "r"(a3), "l"(db), "r"(acc), "n"(TB));
}
__device__ __forceinline__ void mma_n8(float (&d)[4], uint64_t da, uint64_t db, int acc) {
  asm volatile("{\n.reg .pred p;\nsetp.ne.b32 p, %6, 0;\n"
               "wgmma.mma_async.sync.aligned.m64n8k16.f32.bf16.bf16 {%0, %1, %2, %3}, %4, %5, p, 1, 1, 1, 0;\n}\n"
               : "+f"(d[0]), "+f"(d[1]), "+f"(d[2]), "+f"(d[3])
               : "l"(da), "l"(db), "r"(acc));
}
__device__ __forceinline__ void hmma_k16(float (&d)[4], uint32_t a0, uint32_t a1, uint32_t a2, uint32_t a3, uint32_t b0, uint32_t b1) {
  asm volatile("mma.sync.aligned.m16n8k16.row.col.f32.bf16.bf16.f32 {%0, %1, %2, %3}, {%4, %5, %6, %7}, {%8, %9}, {%0, %1, %2, %3};"
               : "+f"(d[0]), "+f"(d[1]), "+f"(d[2]), "+f"(d[3]) : "r"(a0), "r"(a1), "r"(a2), "r"(a3), "r"(b0), "r"(b1));
}

__device__ __forceinline__ uint32_t pack2(float lo, float hi) {
  uint32_t r;
  asm("cvt.rn.bf16x2.f32 %0, %1, %2;" : "=r"(r) : "f"(hi), "f"(lo));
  return r;
}
__device__ __forceinline__ float bf_lo(uint32_t w) { return __uint_as_float(w << 16); }
__device__ __forceinline__ float bf_hi(uint32_t w) { return __uint_as_float(w & 0xFFFF0000u); }
__device__ __forceinline__ float bfr(float x) { return __uint_as_float(pack2(0.f, x)); }
__device__ __forceinline__ uint32_t sub2(uint32_t a, uint32_t b) {
  uint32_t r;
  asm("sub.rn.bf16x2 %0, %1, %2;" : "=r"(r) : "r"(a), "r"(b));
  return r;
}
__device__ __forceinline__ uint32_t add2(uint32_t a, uint32_t b) {
  uint32_t r;
  asm("add.rn.bf16x2 %0, %1, %2;" : "=r"(r) : "r"(a), "r"(b));
  return r;
}
__device__ __forceinline__ uint32_t mul2(uint32_t a, uint32_t b) {
  uint32_t r;
  asm("mul.rn.bf16x2 %0, %1, %2;" : "=r"(r) : "r"(a), "r"(b));
  return r;
}
__device__ __forceinline__ uint32_t fma2(uint32_t a, uint32_t b, uint32_t c) {
  uint32_t r;
  asm("fma.rn.bf16x2 %0, %1, %2, %3;" : "=r"(r) : "r"(a), "r"(b), "r"(c));
  return r;
}
__device__ __forceinline__ float ex2(float x) {
  float r;
  asm("ex2.approx.ftz.f32 %0, %1;" : "=f"(r) : "f"(x));
  return r;
}
__device__ __forceinline__ float rcp(float x) {
  float r;
  asm("rcp.approx.ftz.f32 %0, %1;" : "=f"(r) : "f"(x));
  return r;
}
__device__ __forceinline__ float silu_f(float t) { return t * rcp(1.0f + ex2(-1.4426950408889634f * t)); }
__device__ __forceinline__ void lds128(uint32_t a, uint32_t& x, uint32_t& y, uint32_t& z, uint32_t& w) {
  asm volatile("ld.shared.v4.u32 {%0, %1, %2, %3}, [%4];" : "=r"(x), "=r"(y), "=r"(z), "=r"(w) : "r"(a) : "memory");
}
__device__ __forceinline__ void ldsm4(uint32_t a, uint32_t& x, uint32_t& y, uint32_t& z, uint32_t& w) {
  asm volatile("ldmatrix.sync.aligned.m8n8.x4.shared.b16 {%0, %1, %2, %3}, [%4];" : "=r"(x), "=r"(y), "=r"(z), "=r"(w) : "r"(a) : "memory");
}
constexpr uint32_t TAG_BIT = 0x10000;
__device__ __forceinline__ void st_gran(uint4* p, uint32_t x, uint32_t y, uint32_t z, uint32_t w) {
  asm volatile("st.relaxed.gpu.global.v4.b32 [%0], {%1, %2, %3, %4};" ::"l"(p), "r"(x), "r"(y), "r"(z), "r"(w) : "memory");
}
__device__ __forceinline__ void ld_gran(const uint4* p, uint32_t& x, uint32_t& y, uint32_t& z, uint32_t& w) {
  asm volatile("ld.relaxed.gpu.global.v4.b32 {%0, %1, %2, %3}, [%4];" : "=r"(x), "=r"(y), "=r"(z), "=r"(w) : "l"(p) : "memory");
}
__device__ __forceinline__ void ldsm4t(uint32_t a, uint32_t& x, uint32_t& y, uint32_t& z, uint32_t& w) {
  asm volatile("ldmatrix.sync.aligned.m8n8.x4.trans.shared.b16 {%0, %1, %2, %3}, [%4];" : "=r"(x), "=r"(y), "=r"(z), "=r"(w) : "r"(a) : "memory");
}
__device__ __forceinline__ void stsm4t(uint32_t a, uint32_t x, uint32_t y, uint32_t z, uint32_t w) {
  asm volatile("stmatrix.sync.aligned.m8n8.x4.trans.shared.b16 [%0], {%1, %2, %3, %4};" ::"r"(a), "r"(x), "r"(y), "r"(z), "r"(w) : "memory");
}
__device__ __forceinline__ void stsm4(uint32_t a, uint32_t x, uint32_t y, uint32_t z, uint32_t w) {
  asm volatile("stmatrix.sync.aligned.m8n8.x4.shared.b16 [%0], {%1, %2, %3, %4};" ::"r"(a), "r"(x), "r"(y), "r"(z), "r"(w) : "memory");
}
template <class T>
__device__ __forceinline__ T* at(const void* base, uint32_t off) {
  uint64_t r;
  asm("{\n.reg .u32 lo, hi;\nmov.b64 {lo, hi}, %1;\nadd.cc.u32 lo, lo, %2;\naddc.u32 hi, hi, 0;\nmov.b64 %0, {lo, hi};\n}"
      : "=l"(r) : "l"(base), "r"(off));
  return (T*)__cvta_global_to_generic(r);
}
__device__ __forceinline__ void add_granules(float (&red)[32], const uint32_t (&g)[16]) {
#pragma unroll
  for (int i = 0; i < 16; i++) { red[2 * i] += bf_lo(g[i]); red[2 * i + 1] += bf_hi((i & 3) ? g[i] : g[i] & ~TAG_BIT); }
}
__device__ __forceinline__ bool granules_ok(const uint32_t (&g)[16], uint32_t tag) {
  uint32_t u, v;
  asm("lop3.b32 %0, %1, %2, %3, 0x7E;" : "=r"(u) : "r"(g[0]), "r"(g[4]), "r"(tag));
  asm("lop3.b32 %0, %1, %2, %3, 0x7E;" : "=r"(v) : "r"(g[8]), "r"(g[12]), "r"(tag));
  return __all_sync(0xffffffffu, ((u | v) & TAG_BIT) == 0);
}
__device__ __forceinline__ unsigned ld_acquire(const unsigned* p) {
  unsigned v;
  asm volatile("ld.acquire.gpu.global.u32 %0, [%1];" : "=r"(v) : "l"(p) : "memory");
  return v;
}
__device__ __forceinline__ void red_release(unsigned* p) {
  asm volatile("red.release.gpu.global.add.u32 [%0], 1;" ::"l"(p) : "memory");
}
__device__ __forceinline__ void st_release(unsigned* p, unsigned v) {
  asm volatile("st.release.gpu.global.u32 [%0], %1;" ::"l"(p), "r"(v) : "memory");
}

template <int K0, int K1>
__device__ __forceinline__ void ln_fetch(uint32_t (&xa)[144], uint32_t boxes, uint32_t lo) {
#pragma unroll
  for (int k = K0; k < K1; k++) ldsm4(((boxes + lo) ^ ((k & 3) << 5)) + (k >> 2) * 8192, xa[4 * k], xa[4 * k + 1], xa[4 * k + 2], xa[4 * k + 3]);
}
template <int K0, int K1>
__device__ __forceinline__ void ln_sums(const uint32_t (&xa)[144], float (&sm)[4][4]) {
#pragma unroll
  for (int k = K0; k < K1; k++) hmma_k16(sm[k & 3], xa[4 * k], xa[4 * k + 1], xa[4 * k + 2], xa[4 * k + 3], 0x3F803F80u, 0x3F803F80u);
}
__device__ __forceinline__ uint32_t sq8(const uint32_t* a) {
  uint32_t t, u;
  asm("mul.rn.bf16x2 %0, %1, %1;" : "=r"(t) : "r"(a[0]));
  asm("mul.rn.bf16x2 %0, %1, %1;" : "=r"(u) : "r"(a[2]));
#pragma unroll
  for (int i = 4; i < 16; i += 4) {
    asm("fma.rn.bf16x2 %0, %1, %1, %0;" : "+r"(t) : "r"(a[i]));
    asm("fma.rn.bf16x2 %0, %1, %1, %0;" : "+r"(u) : "r"(a[i + 2]));
  }
  return add2(t, u);
}
__device__ __forceinline__ void ln_centre(uint32_t (&xa)[144], int j0, int j1, uint32_t mm0, uint32_t mm1, float& sq0, float& sq1) {
#pragma unroll
  for (int j = 0; j < 72; j += 8)
    if (j >= j0 && j < j1) {
#pragma unroll
      for (int k = j; k < j + 8; k++) {
        xa[2 * k] = sub2(xa[2 * k], mm0);
        xa[2 * k + 1] = sub2(xa[2 * k + 1], mm1);
      }
      const uint32_t t0 = sq8(xa + 2 * j), t1 = sq8(xa + 2 * j + 1);
      sq0 += bf_lo(t0) + bf_hi(t0);
      sq1 += bf_lo(t1) + bf_hi(t1);
    }
}
__device__ __forceinline__ float ln_rstd(float var) {
  float sd;
  asm("sqrt.approx.ftz.f32 %0, %1;" : "=f"(sd) : "f"(bfr(bfr(fmaxf(var, 0.0f)) + 1e-5f)));
  return rcp(bfr(sd));
}
__device__ __forceinline__ uint32_t silu2(uint32_t t) { return pack2(silu_f(bf_lo(t)), silu_f(bf_hi(t))); }
__device__ __forceinline__ float sum8(float v) {
#pragma unroll
  for (int d = 4; d; d >>= 1) v += __shfl_xor_sync(0xffffffffu, v, d);
  return v;
}
__device__ __forceinline__ void await_count(const unsigned* p, unsigned target, unsigned sleep_ns) {
#pragma unroll 1
  for (int n = 0; n < (1 << 18) && __any_sync(0xffffffffu, (int)(ld_acquire(p) - target) < 0); n++) __nanosleep(sleep_ns);
}
__device__ __forceinline__ void bulk_load(uint32_t dst, const void* src, uint32_t bytes, uint32_t bar) {
  asm volatile("cp.async.bulk.shared::cluster.global.mbarrier::complete_tx::bytes [%0], [%1], %2, [%3];"
               ::"r"(dst), "l"(src), "r"(bytes), "r"(bar) : "memory");
}
__device__ __forceinline__ void proxy_fence() { asm volatile("fence.proxy.async;" ::: "memory"); }

template <int V> struct IC { static constexpr int value = V; };

struct Ctx {
  uint32_t sb;
  uint8_t* sp;
  uint32_t rank;
  Scratch* gs;
};

__device__ __forceinline__ void dly(const Ctx&, int) {}
template <int BOXES>
__device__ __forceinline__ void load_stage(uint32_t dst, const CUtensorMap* tm, int c0, int c1, uint32_t bar, uint32_t bytes, uint64_t pol) {
  asm volatile("{\n.reg .pred p;\nelect.sync _|p, 0xffffffff;\n"
               "@p mbarrier.arrive.expect_tx.shared::cta.b64 _, [%4], %7;\n"
               "@p cp.async.bulk.tensor.2d.shared::cluster.global.mbarrier::complete_tx::bytes.multicast::cluster.L2::cache_hint"
               " [%0], [%1, {%2, %3}], [%4], %5, %6;\n}"
               ::"r"(dst), "l"(tm), "r"(c0), "r"(c1), "r"(bar), "h"((uint16_t)3), "l"(pol), "r"(bytes) : "memory");
  if (BOXES == 2)
    asm volatile("{\n.reg .pred p;\nelect.sync _|p, 0xffffffff;\n"
                 "@p cp.async.bulk.tensor.2d.shared::cluster.global.mbarrier::complete_tx::bytes.multicast::cluster.L2::cache_hint"
                 " [%0], [%1, {%2, %3}], [%4], %5, %6;\n}"
                 ::"r"(dst + 8192), "l"(tm), "r"(c0), "r"(c1 + 64), "r"(bar), "h"((uint16_t)3), "l"(pol) : "memory");
}
__device__ __forceinline__ void attn_producer(const Ctx& cx, int qb, int hs, const CUtensorMap* tmX, const CUtensorMap* tmK,
                                              const CUtensorMap* tmV, const CUtensorMap* tmWq, const CUtensorMap* tmWo) {
  const uint32_t full = cx.sb + SM_FULL, empty = cx.sb + SM_EMPTY, ring = cx.sb + SM_RING + cx.rank * 16384;
  const uint64_t keep = policy_evict_normal(), last_use = policy_evict_first();
  auto acquire = [&](int st) {
    mbar_wait(empty + 8 * (st & 3), ((st >> 2) ^ ((st & 3) >> 1) ^ 1) & 1);
    if (st > 3) dly(cx, st);
  };
  if (elect_one()) {
#pragma unroll
    for (int j = 0; j < 3; j++) {
      mbar_expect_tx(cx.sb + SM_XFULL + 96 + 8 * j, 24576);
      tma3d(cx.sb + SM_X + 73728 + j * 24576, tmX, qb * 128 + 64, j * 3, cx.sb + SM_XFULL + 96 + 8 * j);
    }
  }
  __syncwarp();
  const int c0 = cx.rank * 64;
#pragma unroll 1
  for (int p = 0; p < 3; p++) {
    const int n0 = (hs * 4 + ((0x120 >> (4 * p)) & 3)) * DH + c0;
#pragma unroll
    for (int i = 0; i < 5; i++) {
      const int st = (p == 2 ? 13 : 5 * p) + i, sl = st & 3;
      if (i == 4 && p == 2) break;
      if (st == 1) mbar_wait(cx.sb + SM_XFULL + 16, 0);
      acquire(st);
      if (i == 2) load_stage<1>(ring + sl * STAGE, tmWq, n0, 256, full + 8 * sl, 16384, last_use);
      else load_stage<2>(ring + sl * STAGE, tmWq, n0, i < 2 ? 128 * i : 128 * i - 64, full + 8 * sl, 32768, last_use);
      if (i == 3 && p < 2 && elect_one()) {
        tma2d_prefetch(tmWq, (hs * 4 + 2 - p) * DH + (qb & 1) * 64, (qb >> 1) * 64);
        if (p == 0 && qb < 9) tma2d_prefetch(tmWq, (hs * 4 + 3) * DH, qb * 64);
      }
      __syncwarp();
    }
    if (p == 1) {
      const int n3 = (hs * 4 + 3) * DH;
      acquire(10);
      load_stage<2>(ring + 2 * STAGE, tmWq, n3, 2 * c0, full + 16, 32768, last_use);
      acquire(11);
      if (cx.rank) load_stage<1>(ring + 3 * STAGE, tmWq, n3, 384, full + 24, 24576, last_use);
      else load_stage<2>(ring + 3 * STAGE, tmWq, n3, 256, full + 24, 24576, last_use);
      acquire(12);
      load_stage<1>(ring, tmWq, n3, 448 + c0, full, 16384, last_use);
    }
  }
  int vrow = 0;
  uint64_t vpol = keep;
#pragma unroll 1
  for (int j = 0; j < 32; j++) {
    const int st = NST_Q - 1 + 4 * j, row = (hs * 2 + (j >> 4)) * SEQ + (j & 7) * 256;
    const uint64_t pol = (j & 8) ? last_use : keep;
    if (j == 24) mbar_wait(cx.sb + SM_BAR_Q3, 0);
    acquire(st);
    load_stage<1>(ring + SL_KE * STAGE, tmK, c0, row, full + 8 * SL_KE, 32768, pol);
    acquire(st + 1);
    if (j) load_stage<1>(ring + SL_VE * STAGE, tmV, c0, vrow, full + 8 * SL_VE, 32768, vpol);
    else load_stage<2>(ring + SL_VE * STAGE, tmWq, (hs * 4 + 1) * DH + c0, 448, full + 8 * SL_VE, 32768, last_use);
    vrow = row + 128;
    vpol = pol;
    acquire(st + 2);
    load_stage<1>(ring + SL_KO * STAGE, tmK, c0, vrow, full + 8 * SL_KO, 32768, pol);
    acquire(st + 3);
    load_stage<1>(ring + SL_VO * STAGE, tmV, c0, row, full + 8 * SL_VO, 32768, pol);
  }
  acquire(NST_Q + NST_KV - 1);
  load_stage<1>(ring + SL_KE * STAGE, tmV, c0, vrow, full + 8 * SL_KE, 32768, last_use);
#pragma unroll 1
  for (int u = 0; u < NST_O; u++) {
    const int st = NST_Q + NST_KV + u, sl = st & 3;
    const int blk = u < 4 && cx.rank ? 8 : ((hs + max(u >> 1, 1)) & 7);
    const int head = u < 4 ? u ^ (u >> 1) : ((u & 1) * 2 + cx.rank + 3) & 3;
    acquire(st);
    load_stage<1>(ring + sl * STAGE, tmWo, blk * 64, hs * 512 + head * 128, full + 8 * sl, 32768, last_use);
  }
}

__device__ __forceinline__ uint32_t xn_offset(uint32_t row, int lane) {
  return (row >> 6) * (9 * 8192) + (row & 63) * 128 + ((((lane >> 2) ^ row) & 7) << 4) + (lane & 3) * 4;
}

__device__ __forceinline__ void attn_rows(const Ctx& cx, int qb, int hs, int hw, int lane, const CUtensorMap* tmX16,
                                          const __nv_bfloat16* w_r) {
  extern __shared__ __align__(1024) uint8_t smem_rows[];
  auto box = [&](int blk) { return blk < 8 ? SM_SLOT + 2 * STAGE + 8192 + (blk >> 2) * 16384 + (blk & 3) * 2048 : SM_BOX8; };
  const uint32_t sb = smem_u32(smem_rows);
  if (hw == 0) {
    bar_sync(BAR_HELPER, 160);
    if (elect_one()) {
      mbar_expect_tx(sb + SM_BAR_ROWS, 9 * 2048);
#pragma unroll
      for (int i = 0; i < 9; i++) tma2d(sb + box(i), tmX16, i * 64, qb * 128 + hs * 16, sb + SM_BAR_ROWS);
    }
    __syncwarp();
  }
  uint32_t g = (lane >> 3) * 128 + (((lane ^ (lane >> 3)) & 7) << 4);
  auto next = [&]() {
    g = ((g + 512) & 2047) ^ 64;
    asm volatile("" : "+r"(g));
  };
  float* const part = (float*)(smem_rows + SM_ROWS);
  mbar_wait(sb + SM_BAR_ROWS, 0);
  if (hw == 0) dly(cx, 190);
#pragma unroll 1
  for (int i = 0; i < 4; i++) {
    float a = 0.f, b = 0.f;
#pragma unroll
    for (int j = 0; j < 3; j++) {
      const uint4 v = *(const uint4*)(smem_rows + box(hw * 3 + j) + g);
      const uint32_t w[4] = {v.x, v.y, v.z, v.w};
#pragma unroll
      for (int k = 0; k < 4; k++) {
        a += bf_lo(w[k]) + bf_hi(w[k]);
        b = fmaf(bf_lo(w[k]), bf_lo(w[k]), fmaf(bf_hi(w[k]), bf_hi(w[k]), b));
      }
    }
    a = sum8(a);
    b = sum8(b);
    float* p = part + hw * 16 + (g >> 7);
    p[0] = a;
    p[48] = b;
    next();
  }
  bar_sync(BAR_ROWS, 96);
  if (hw == 0) dly(cx, 191);
  {
    const float* p = part + (lane & 15);
    const float mean = (p[0] + p[16] + p[32]) * (1.0f / DM), rstd = ln_rstd((p[48] + p[64] + p[80]) * (1.0f / DM) - mean * mean);
    const uint32_t mm = pack2(mean, mean), rr = pack2(rstd - bfr(rstd), rstd);
#pragma unroll 1
    for (int u = hw * 12; u < hw * 12 + 12; u++) {
      const int blk = u >> 2;
      uint4* q = (uint4*)(smem_rows + box(blk) + g);
      uint4 v = *q;
      const uint32_t m = __shfl_sync(0xffffffffu, mm, g >> 7), r = __shfl_sync(0xffffffffu, rr, g >> 7);
      const uint32_t hi = __byte_perm(r, 0, 0x3232), lo = __byte_perm(r, 0, 0x1010);
      auto norm = [&](uint32_t w) {
        const uint32_t xc = sub2(w, m);
        return fma2(xc, hi, mul2(xc, lo));
      };
      v = make_uint4(norm(v.x), norm(v.y), norm(v.z), norm(v.w));
      *q = v;
      *at<uint4>(cx.gs->xn + ((qb * 2 + (hs >> 2)) * 9 + blk) * 512 + (hs & 3) * 128, g) = v;
      next();
    }
  }
  bar_sync(BAR_ROWS, 96);
  if (hw == 0) {
    dly(cx, 192);
    if (lane == 0) red_release(&cx.gs->rows[qb * 32]);
    dly(cx, 193);
  }
#pragma unroll 1
  for (int u = hw ? 13 * hw - 3 : 0; u < 13 * hw + 10; u++) {
    const int blk = u >> 2;
    const uint32_t o = (g + (u & 3) * 512) ^ ((u & 1) << 6);
    const uint4 v = *(const uint4*)(smem_rows + box(blk) + o);
    *at<uint4>(cx.gs->gate + (blk < 8 ? (qb * 8 + blk) * 144 + hs * 16 : (qb * 8 + hs) * 144 + 128) * 8, o) =
        make_uint4(silu2(v.x), silu2(v.y), silu2(v.z), silu2(v.w));
  }
  if (hw) dly(cx, 194 + hw);
  __nanosleep(5000);
#pragma unroll 1
  for (int blk = hw * 3; blk < hw * 3 + 3; blk++) {
    const uint4 c = __ldg(at<const uint4>(w_r, blk * 128 + ((g ^ (g >> 3)) & 0x70)));
#pragma unroll 1
    for (int i = 0; i < 4; i++) {
      const uint4 v = *(const uint4*)(smem_rows + box(blk) + g);
      part[blk * 16 + (g >> 7)] =
          sum8(fmaf(bf_lo(v.x), bf_lo(c.x), fmaf(bf_hi(v.x), bf_hi(c.x), fmaf(bf_lo(v.y), bf_lo(c.y), bf_hi(v.y) * bf_hi(c.y)))) +
               fmaf(bf_lo(v.z), bf_lo(c.z), fmaf(bf_hi(v.z), bf_hi(c.z), fmaf(bf_lo(v.w), bf_lo(c.w), bf_hi(v.w) * bf_hi(c.w)))));
      next();
    }
  }
  bar_sync(BAR_ROWS, 96);
  if (hw == 0) {
    dly(cx, 194);
    float d = 0.f;
#pragma unroll
    for (int j = 0; j < 9; j++) d += part[j * 16 + (lane & 15)];
    const uint32_t row = qb * 128 + hs * 16 + (lane & 15), b = pack2(0.f, d);
    *at<uint32_t>(cx.gs->key, row * 4) = (b ^ ((int)b < 0 ? 0xFFFF0000u : 0x80000000u)) + 0xFFFF - row;
    __syncwarp();
    if (lane == 0) red_release(&cx.gs->rows[qb * 32 + 1]);
  }
}

constexpr uint32_t SM_XO = SM_SLOT, SM_GO = SM_SLOT + STAGE, SM_P8 = SM_SLOT + 2 * STAGE;
__device__ __forceinline__ void attn_helper(const Ctx& cx, int qb, int hs, int lane, const __nv_bfloat16* wo, const CUtensorMap* tmX16) {
  unsigned e = 0;
  if (lane == 0) {
    e = cx.gs->launch[blockIdx.x];
    cx.gs->launch[blockIdx.x] = e + 1;
  }
  e = __shfl_sync(0xffffffffu, e, 0);
  if (lane == 0) {
    *(uint32_t*)(cx.sp + SM_TAG) = (~e & 1) * TAG_BIT;
    mbar_arrive(cx.sb + SM_BAR_MISC);
  }
  bar_sync(BAR_HELPER, 64);
  await_count(&cx.gs->rows[qb * 32 + 1], 8 * (e + 1), 1000);
  await_count(&cx.gs->q3_flag[qb * 8 + hs], e + 1, 1000);
  proxy_fence();
  if (elect_one()) {
    mbar_expect_tx(cx.sb + SM_BAR_Q3, 16384);
#pragma unroll
    for (int i = 0; i < 2; i++) bulk_load(cx.sb + SM_SLOT + 2 * STAGE + i * 16384 + 8192, cx.gs->q3 + (qb * 16 + hs * 2 + i) * 512, 8192, cx.sb + SM_BAR_Q3);
  }
  __syncwarp();
  bar_sync(BAR_HELPER, 64);
  prefetch_l2(at<const void>(wo, (hs * 512 + qb * 32 + lane) * (DM * 2)), DM * 2);
  await_count(&cx.gs->ycnt, 4 * (e + 1), 500);
  const uint32_t mykey = __ldcg(at<const uint32_t>(cx.gs->top, (lane >> 1) * 4)), myrow = 0xFFFF - (mykey & 0xFFFF);
#pragma unroll 1
  for (uint32_t todo = __ballot_sync(0xffffffffu, lane < 16 && ((lane & 1) ? myrow >> 4 == qb * 8 + hs : myrow >> 7 == qb)); todo; todo &= todo - 1) {
    const int i = __ffs(todo) - 1, blk = (i & 1) ? 8 : hs;
    const uint32_t key = __shfl_sync(0xffffffffu, mykey, i), row = 0xFFFF - (key & 0xFFFF), o = xn_offset(row, lane);
    const uint32_t t = __ldcg(at<const uint32_t>(cx.gs->xn, o + blk * 8192));
    const float2* p = at<const float2>(cx.gs->ypart, ((i >> 1) * DM + blk * 64 + 2 * lane) * 4);
    const float2 y0 = __ldcg(p), y1 = __ldcg(p + TOPC * DM / 2), y2 = __ldcg(p + TOPC * DM), y3 = __ldcg(p + 3 * TOPC * DM / 2);
    const float rs = bfr(rcp(1.0f + ex2(-1.4426950408889634f * bf_hi(key ^ ((int)key < 0 ? 0x80000000u : 0xFFFF0000u)))));
    const uint32_t y = pack2((y0.x + y1.x) + (y2.x + y3.x), (y0.y + y1.y) + (y2.y + y3.y));
    const uint32_t u = pack2(bf_lo(y) * rs, bf_hi(y) * rs);
    *at<uint32_t>(cx.gs->gate, ((qb * 8 + hs) * 144 + ((i & 1) ? 128 + (row & 15) : row & 127)) * 128 + (o & 127)) = silu2(add2(t, u));
  }
  proxy_fence();
  bar_sync(BAR_OA, 352);
  if (elect_one()) {
    const uint32_t bar = cx.sb + SM_BAR_XG;
    mbar_expect_tx(bar, 2 * 144 * 128);
    bulk_load(cx.sb + SM_GO, cx.gs->gate + (qb * 8 + hs) * (144 * 8), 144 * 128, bar);
#pragma unroll 1
    for (int i = 0; i < 9; i++) tma2d_stream(cx.sb + SM_XO + i * 2048, tmX16, i < 8 ? hs * 64 : 512, qb * 128 + (i < 8 ? i : hs) * 16, bar);
  }
  __syncwarp();
  const uint4* src = cx.gs->part + (qb * 64 + 56 + hs) * 1024;
#pragma unroll 1
  for (int n = 0; n < (1 << 16); n++) {
    __nanosleep(n ? 400 : 700);
    uint32_t a, b, d, t;
    ld_gran(at<const uint4>(src, (lane & 7) * 2048 + 2032), a, b, d, t);
    if (__all_sync(0xffffffffu, ((a >> 16) ^ e) & 1)) break;
  }
  if (elect_one()) {
    mbar_expect_tx(cx.sb + SM_BAR_P8, 16384);
    bulk_load(cx.sb + SM_P8, src, 16384, cx.sb + SM_BAR_P8);
  }
  __syncwarp();
}
__device__ __forceinline__ void attn_finish8(const Ctx& cx, int qb, int hs, int hw, int lane, __nv_bfloat16* out) {
  const uint32_t tag = *(const uint32_t*)(cx.sp + SM_TAG);
  mbar_wait(cx.sb + SM_BAR_P8, 0);
  mbar_wait(cx.sb + SM_BAR_XG, 0);
#pragma unroll 1
  for (int g = 2 - hw; g < 4; g += 3) {
    float acc[8] = {0.f, 0.f, 0.f, 0.f, 0.f, 0.f, 0.f, 0.f};
    uint32_t a[4];
#pragma unroll 1
    for (uint32_t o = g * 512 + lane * 16; o < 16384; o += 2048) {
      lds128(cx.sb + SM_P8 + o, a[0], a[1], a[2], a[3]);
#pragma unroll 1
      for (int n = 0; n < (1 << 16) && __any_sync(0xffffffffu, (a[0] & TAG_BIT) != tag); n++)
        ld_gran(at<const uint4>(cx.gs->part, (qb * 64 + 56 + hs) * 16384 + o), a[0], a[1], a[2], a[3]);
      a[0] &= ~TAG_BIT;
#pragma unroll
      for (int j = 0; j < 4; j++) { acc[2 * j] += bf_lo(a[j]); acc[2 * j + 1] += bf_hi(a[j]); }
    }
    asm volatile("" : "+r"(lane));
    const uint32_t tile = cx.sb + SM_XO + (128 + (lane & 15)) * 128 + (((lane >> 4) ^ (lane & 7)) << 4);
    uint32_t b[4];
    ldsm4((tile ^ (g << 5)) + STAGE, a[0], a[1], a[2], a[3]);
    ldsm4(tile ^ (g << 5), b[0], b[1], b[2], b[3]);
    stsm4(tile ^ (g << 5), fma2(pack2(acc[0], acc[1]), a[0], b[0]), fma2(pack2(acc[2], acc[3]), a[1], b[1]),
          fma2(pack2(acc[4], acc[5]), a[2], b[2]), fma2(pack2(acc[6], acc[7]), a[3], b[3]));
  }
  bar_sync(BAR_ROWS, 96);
#pragma unroll 1
  for (int ch = threadIdx.x - 32; ch < 128; ch += 96)
    *at<uint4>(out, ((qb * 128 + hs * 16 + (ch >> 3)) * DM + 512 + (ch & 7) * 8) * 2) =
        *(const uint4*)(cx.sp + SM_XO + (128 + (ch >> 3)) * 128 + (((ch ^ (ch >> 3)) & 7) << 4));
}

constexpr float SUM_HI = 1.8446744e19f, SUM_LO = 9.0949470e-13f;

__device__ __forceinline__ void softmax_shift(float (&s)[64], float n0, float n1) {
#pragma unroll
  for (int i = 0; i < 64; i++) s[i] += (i & 2) ? n1 : n0;
}
template <int LO, int HI>
__device__ __forceinline__ void softmax_exp(float (&s)[64]) {
#pragma unroll
  for (int i = LO; i < HI; i++) s[i] = ex2(s[i]);
}
__device__ __forceinline__ void row_sums(const uint32_t (&pf)[32], float& l0, float& l1) {
  uint32_t t[16];
#pragma unroll
  for (int i = 0; i < 16; i++) t[i] = add2(pf[(i >> 1) * 4 + (i & 1)], pf[(i >> 1) * 4 + 2 + (i & 1)]);
#pragma unroll
  for (int i = 0; i < 8; i++) t[i] = add2(t[(i >> 1) * 4 + (i & 1)], t[(i >> 1) * 4 + 2 + (i & 1)]);
#pragma unroll
  for (int i = 0; i < 4; i++) t[i] = add2(t[(i >> 1) * 4 + (i & 1)], t[(i >> 1) * 4 + 2 + (i & 1)]);
  l0 += (bf_lo(t[0]) + bf_lo(t[2])) + (bf_hi(t[0]) + bf_hi(t[2]));
  l1 += (bf_lo(t[1]) + bf_lo(t[3])) + (bf_hi(t[1]) + bf_hi(t[3]));
}
__device__ __forceinline__ void softmax_redo(uint32_t (&pf)[32], const uint32_t (&q)[32], const __nv_bfloat16* kblk, int lane, float& n0,
                                             float& n1, float& l0, float& l1, float& sc0, float& sc1) {
  float x0 = -n0, x1 = -n1;
#pragma unroll 1
  for (int u = 0; u < 16; u++) {
    const uint32_t* kp = (const uint32_t*)(kblk + ((u & 7) * 16 + (lane >> 2)) * DH) + (lane & 3);
    float d[2][4] = {};
#pragma unroll
    for (int k = 0; k < 16; k++)
      hmma_k16(d[k & 1], q[2 * (k & 14)], q[2 * (k & 14) + 1], q[2 * (k & 14) + 2], q[2 * (k & 14) + 3],
               kp[(k & 1) * 4 * DH + (k >> 1) * 8], kp[(k & 1) * 4 * DH + (k >> 1) * 8 + 4]);
    if (u < 8) {
      x0 = fmaxf(fmaxf(x0, fmaxf(d[0][0], d[0][1])), fmaxf(d[1][0], d[1][1]));
      x1 = fmaxf(fmaxf(x1, fmaxf(d[0][2], d[0][3])), fmaxf(d[1][2], d[1][3]));
      if (u == 7) {
#pragma unroll
        for (int m = 1; m < 4; m <<= 1) {
          x0 = fmaxf(x0, __shfl_xor_sync(0xffffffffu, x0, m));
          x1 = fmaxf(x1, __shfl_xor_sync(0xffffffffu, x1, m));
        }
        sc0 = ex2(-x0 - n0);
        sc1 = ex2(-x1 - n1);
        n0 = -x0;
        n1 = -x1;
        l0 *= sc0;
        l1 *= sc1;
      }
    } else {
#pragma unroll
      for (int i = 0; i < 28; i++) pf[i] = pf[i + 4];
#pragma unroll
      for (int i = 0; i < 4; i++) {
        const float n = (i & 1) ? n1 : n0;
        pf[28 + i] = pack2(ex2(d[i >> 1][(i & 1) * 2] + n), ex2(d[i >> 1][(i & 1) * 2 + 1] + n));
        ((i & 1) ? l1 : l0) += bf_lo(pf[28 + i]) + bf_hi(pf[28 + i]);
      }
    }
  }
}

__device__ __forceinline__ void attn_consumer(const Ctx& cx, int qb, int hs, int wg, int cw, int lane, const __nv_bfloat16* x,
                                              const __nv_bfloat16* kc, __nv_bfloat16* out) {
  const uint32_t full = cx.sb + SM_FULL;
  const uint32_t ring = cx.sb + SM_RING;
  uint32_t lo = ((cw & 3) * 16 + (lane & 15)) * 128 + (((lane >> 4) ^ (lane & 7)) << 4);
  const uint32_t slot = cx.sb + SM_SLOT + wg * 16384;
  auto frag = [&](int sl, int k) { return ((slot + sl * STAGE + lo) ^ ((k & 3) << 5)) + (k >> 2) * 8192; };
  auto park = [&](const float (&a)[64], int sl, int k0, int k1, float f0, float f1) {
#pragma unroll
    for (int k = 0; k < 8; k++)
      if (k >= k0 && k < k1)
        stsm4(frag(sl, k), pack2(a[8 * k] * f0, a[8 * k + 1] * f0), pack2(a[8 * k + 2] * f1, a[8 * k + 3] * f1),
              pack2(a[8 * k + 4] * f0, a[8 * k + 5] * f0), pack2(a[8 * k + 6] * f1, a[8 * k + 7] * f1));
  };
  const bool signaller = lane == 0 && (cw & 3) < 2;
  int my_turn = 1 + wg, other_turn = 2 - wg;

  uint32_t pf[32], q[32], empty_c;
  float o[64], l0, l1;
  {
    uint32_t xa[144];
    float rstd0, rstd1;
    {
      const uint32_t xb = cx.sb + SM_X + wg * 73728, xf = cx.sb + SM_XFULL + wg * 96;
      float sm[4][4] = {};
      prof(wg, 0);
      empty_c = mapa(cx.sb + SM_EMPTY, cw & 1);
      mbar_wait(xf, 0);
      if ((threadIdx.x & 127) == 0) profc(wg, 30);
      ln_fetch<0, 12>(xa, xb, lo);
      mbar_wait(xf + 8, 0);
      ln_fetch<12, 24>(xa, xb, lo);
      ln_sums<0, 12>(xa, sm);
      mbar_wait(xf + 16, 0);
      if ((threadIdx.x & 127) == 0) profc(wg, 1);
      ln_fetch<24, 36>(xa, xb, lo);
      ln_sums<12, 36>(xa, sm);
      rstd0 = ((sm[0][0] + sm[1][0]) + (sm[2][0] + sm[3][0])) * (1.0f / DM);
      rstd1 = ((sm[0][2] + sm[1][2]) + (sm[2][2] + sm[3][2])) * (1.0f / DM);
    }
    asm volatile("" : "+f"(rstd0), "+f"(rstd1)::"memory");
    block_fence(38);
    if (wg) bar_arrive(other_turn, 256);
    block_fence(39);
    const uint32_t mm0 = pack2(rstd0, rstd0), mm1 = pack2(rstd1, rstd1);
    rstd0 -= bf_lo(mm0);
    rstd1 -= bf_lo(mm1);
    rstd0 *= rstd0 * (-0.25f * DM);
    rstd1 *= rstd1 * (-0.25f * DM);
    auto ln_finish = [&]() {
      rstd0 += __shfl_xor_sync(0xffffffffu, rstd0, 1); rstd1 += __shfl_xor_sync(0xffffffffu, rstd1, 1);
      rstd0 += __shfl_xor_sync(0xffffffffu, rstd0, 2); rstd1 += __shfl_xor_sync(0xffffffffu, rstd1, 2);
      rstd0 = ln_rstd(rstd0 * (1.0f / DM)) * SM_SCALE_LOG2;
      rstd1 = ln_rstd(rstd1 * (1.0f / DM)) * SM_SCALE_LOG2;
    };
    ln_centre(xa, 0, X_C0, mm0, mm1, rstd0, rstd1);
    if (wg == 0) {
      bar_sync(4, 128);
      if (signaller) {
        asm volatile("mbarrier.arrive.shared::cluster.b64 _, [%0], 2;" ::"r"(empty_c + 16) : "memory");
        asm volatile("mbarrier.arrive.shared::cluster.b64 _, [%0], 2;" ::"r"(empty_c + 24) : "memory");
      }
      block_fence(37);
      pin(xa);
      ln_centre(xa, X_C0, X_C1, mm0, mm1, rstd0, rstd1);
    }
    pin(xa);
    if ((threadIdx.x & 127) == 0) profc(wg, 2);

    extern __shared__ __align__(1024) uint8_t smem_q[];
    const uint32_t ring = smem_u32(smem_q) + SM_RING;
    auto release = [&](int st) { if (signaller) mbar_arrive_cluster(empty_c + 8 * (st & 3)); };
    auto q_stage = [&](float (&acc)[64], int st, int i, int last) {
      mbar_wait(full + 8 * (st & 3), (st >> 2) & 1);
      if (i != (wg ? last : 1)) bar_sync(my_turn, 256);
      wg_fence();
      const uint64_t db = mkdesc(ring + (st & 3) * STAGE, 16384);
#pragma unroll
      for (int k = 0; k < 8; k++) {
        const int kb = (i < 3 ? 8 * i : 8 * i - 4) + k;
        if (i != 2 || k < 4) mma_n128<1>(acc, xa[4 * kb], xa[4 * kb + 1], xa[4 * kb + 2], xa[4 * kb + 3], db + k * 128, kb > 0);
      }
      wg_commit();
      if (i != (wg ? last - 1 : 0)) bar_arrive(other_turn, 256);
    };
    auto q_release = [&](int st, int i, int last) {
      if (i == 1 || i == last) {
        wg_wait<1>();
        if (i == last || !wg) release(st - 1);
      }
      if (i != last - 1 && (i || wg)) {
        wg_wait<0>();
        release(st);
      }
    };
    {
      float (&acc)[64] = o;
#pragma unroll 1
      for (int p = 0; p < 2; p++) {
#pragma unroll
        for (int i = 0; i < 5; i++) {
          q_stage(acc, 5 * p + i, i, 4);
          if (p == 0 && i != 3) {
            if (i == 0 && wg) bar_arrive(BAR_HELPER, 160);
            if ((wg || i) && i < 3) ln_centre(xa, i == 0 ? X_C0 : i == 1 ? X_C1 : X_C2, i == 0 ? X_C1 : i == 1 ? X_C2 : 72, mm0, mm1, rstd0, rstd1);
            if (i == 4) ln_finish();
            pin(xa);
          }
          q_release(5 * p + i, i, 4);
        }
        pin(acc);
#pragma unroll
        for (int k = 0; k < 8; k += 2) {
          park(acc, p, k, k + 2, rstd0, rstd1);
          if (k < 6) block_fence(40 + k);
        }
      }
    }
    {
      float (&h)[32] = *(float (*)[32])&o[0];
#pragma unroll
      for (int i = 0; i < 3; i++) {
        const uint32_t sl = (10 + i) & 3;
        mbar_wait(full + 8 * sl, ((10 + i) >> 2) & 1);
        if (i != (wg ? 2 : 1)) bar_sync(my_turn, 256);
        wg_fence();
#pragma unroll
        for (int k = 0; k < 16 - 4 * i; k++) {
          const int kb = (i == 2 ? 28 : 16 * i) + k;
          const uint64_t db = mkdesc(ring + sl * STAGE, 16) + (i == 2 && k >= 4 ? k + 4 : k) * 128;
          mma_n64<1>(h, xa[4 * kb], xa[4 * kb + 1], xa[4 * kb + 2], xa[4 * kb + 3], db, kb > 0);
        }
        wg_commit();
        if (i != (wg ? 1 : 0)) bar_arrive(other_turn, 256);
        q_release(10 + i, i, 2);
      }
      pin(h);
      park(o, 2, 0, 2, rstd0, rstd1);
      block_fence(49);
      park(o, 2, 2, 4, rstd0, rstd1);
    }
#pragma unroll
    for (int i = 0; i < 4; i++) {
      q_stage(o, 13 + i, i, 3);
      q_release(13 + i, i, 3);
    }
    prof(wg, 6);
#pragma unroll
    for (int i = 0; i < 32; i++) pf[i] = xa[112 + i];
    l0 = 0.25f * rcp(rstd0);
    l1 = 0.25f * rcp(rstd1);
  }

  uint32_t oa[96];
  const uint32_t zero = __shfl_sync(0xffffffffu, blockIdx.y, lane);
  my_turn = __shfl_sync(0xffffffffu, my_turn, lane);
  other_turn = __shfl_sync(0xffffffffu, other_turn, lane);
  lo = __shfl_sync(0xffffffffu, lo, lane);
  {
    float s[64], n0 = 0.f, n1 = 0.f;
    float lp0, lp1;
    float i0 = 0.f, i1 = 0.f;
    bool redo, shift = false;
    auto turn = [&](int it, auto kc_) -> bool {
      constexpr int KIND = decltype(kc_)::value;
      constexpr uint32_t slk = KIND == 1 ? SL_KO : SL_KE, slv = KIND == 1 ? SL_VO : SL_VE, slkn = KIND == 1 ? SL_KE : SL_KO;
      constexpr int SPLIT = X_SPLIT, PARK1 = X_PARK;
      const uint32_t par = ((it + NST_Q / 2) >> 1) & 1;
      const int hsl = max((it >> 4) - 1, 0);
      const uint64_t dk = mkdesc(ring + slk * STAGE, 16), dv = mkdesc(ring + slv * STAGE, 16384);
      auto qk = [&]() {
#pragma unroll
        for (int k = 0; k < 8; k++) {
          if (KIND == 3) mma_n128_ss<0>(s, mkdesc(slot + hsl * STAGE, 16) + (k >> 2) * 512 + (k & 3) * 2, dk + (k >> 2) * 1024 + (k & 3) * 2, k > 0);
          else mma_n128<0>(s, q[4 * k], q[4 * k + 1], q[4 * k + 2], q[4 * k + 3], dk + (k >> 2) * 1024 + (k & 3) * 2, k > 0);
        }
        wg_commit();
      };
      auto pv = [&]() {
#pragma unroll
        for (int k = 0; k < 8; k++)
          mma_n128<1>(o, pf[4 * k], pf[4 * k + 1], pf[4 * k + 2], pf[4 * k + 3], dv + k * 128, k > 0 || KIND != 1 || (it & 15) != 1);
        wg_commit();
      };
      lp0 = l0; lp1 = l1;
#define TS(i)
      {
        TS(0)
        if (KIND == 3) {
          asm volatile("fence.proxy.async.shared::cta;" ::: "memory");
          const float t0 = lp0 + __shfl_xor_sync(0xffffffffu, lp0, 1), t1 = lp1 + __shfl_xor_sync(0xffffffffu, lp1, 1);
          i0 = rcp(t0 + __shfl_xor_sync(0xffffffffu, t0, 2));
          i1 = rcp(t1 + __shfl_xor_sync(0xffffffffu, t1, 2));
          asm volatile("" : "+f"(i0), "+f"(i1)::"memory");
          block_fence(31, zero);
#pragma unroll
          for (int k = 0; k < X_N1; k++) ldsm4(frag(hsl, k), q[4 * k], q[4 * k + 1], q[4 * k + 2], q[4 * k + 3]);
        }
        bar_sync(my_turn, 256);
        TS(1)
        if (KIND != 3) pin(q);
        pin(pf); pin(o);
        wg_fence();
        qk();
        TS(2)
        mbar_wait(full + 8 * slv, par);
        if (KIND == 1 && (it & 15) == 1) {
          park(o, hsl, PARK1, 8, i0, i1);
          wg_fence();
        }
        if (KIND == 3) {
#pragma unroll
          for (int k = X_N1; k < 8; k++) ldsm4(frag(hsl, k), q[4 * k], q[4 * k + 1], q[4 * k + 2], q[4 * k + 3]);
          block_fence(32, zero);
        }
        TS(3)
        pv();
        bar_arrive(other_turn, 256);
        TS(4)
        wg_wait<1>();
      }
      pin(s);
      mbar_arrive_cluster_now<10 * KIND + 3>(empty_c + 8 * slk, signaller, zero);
      TS(5)
      if (KIND == 3) {
        shift = false;
        n0 = n1 = l0 = l1 = 0.f;
      } else if (shift) {
        softmax_shift(s, n0, n1);
        pin(s);
      }
      softmax_exp<0, SPLIT>(s);
      pin(s);
      block_fence(10 * KIND + 4, zero);
      TS(6)
      wg_wait<0>();
      pin(o); pin(pf);
      mbar_arrive_cluster_now<10 * KIND + 5>(empty_c + 8 * slv, signaller, zero);
      TS(7)
      const bool kready = mbar_test(full + 8 * slkn, par);
      softmax_exp<SPLIT, 64>(s);
#pragma unroll
      for (int i = 0; i < 32; i++) pf[i] = pack2(s[2 * i], s[2 * i + 1]);
      row_sums(pf, l0, l1);
      if (KIND == 3) {
        park(o, hsl, 0, PARK1, i0, i1);
        if (it) prof(wg, 6 + (it >> 4));
        if (it >= 32 && cw == 0) bar_arrive(BAR_HELPER, 64);
      }
      redo = !(l0 + l1 <= SUM_HI) || (KIND == 3 && fminf(l0, l1) < SUM_LO);
      const bool leave = __any_sync(0xffffffffu, redo || !kready);
      return leave;
    };
    int it = -1;
#pragma unroll 1
    while (true) {
      mbar_wait(full + 8 * ((it & 1) ? SL_KE : SL_KO), ((it + NST_Q / 2) >> 1) & 1);
      it++;
#pragma unroll 1
      while (true) {
        if (it & 1) {
          if (turn(it, IC<1>()) || it == 63) break;
          it++;
        }
        if (it & 15) {
          if (turn(it, IC<2>())) break;
        } else {
          if (turn(it, IC<3>())) break;
        }
        it++;
      }
      if (__any_sync(0xffffffffu, redo)) {
        const int j = it & 15;
        float sc0 = 1.f, sc1 = 1.f;
        if (j == 0) n0 = n1 = 3.0e38f;
        l0 = j ? lp0 : 0.f;
        l1 = j ? lp1 : 0.f;
        softmax_redo(pf, q, kc + (size_t)((hs * 2 + (it >> 5)) * SEQ + j * 128) * DH, lane, n0, n1, l0, l1, sc0, sc1);
        shift = true;
        if (j == 0) sc0 = sc1 = 1.f;
#pragma unroll
        for (int i = 0; i < 16; i++) { o[4 * i] *= sc0; o[4 * i + 1] *= sc0; o[4 * i + 2] *= sc1; o[4 * i + 3] *= sc1; }
      }
      if (it == 63) break;
    }
  }

#define TE(i) {}
  {
    constexpr int ST0 = NST_Q + NST_KV;
    float acc[32], red[32], first[32];
    auto await = [&](int st) { mbar_wait(full + 8 * (st & 3), (st >> 2) & 1); };
    auto release = [&](int st) { if (signaller) mbar_arrive_cluster(empty_c + 8 * (st & 3)); };
    auto unpark = [&](int h, int k0, int k1) {
#pragma unroll
      for (int k = 0; k < 8; k++)
        if (k >= k0 && k < k1) ldsm4(frag(h, k), oa[32 * h + 4 * k], oa[32 * h + 4 * k + 1], oa[32 * h + 4 * k + 2], oa[32 * h + 4 * k + 3]);
    };
    {
      float ar[64];
      asm volatile("fence.proxy.async.shared::cta;" ::: "memory");
      l0 += __shfl_xor_sync(0xffffffffu, l0, 1); l1 += __shfl_xor_sync(0xffffffffu, l1, 1);
      l0 += __shfl_xor_sync(0xffffffffu, l0, 2); l1 += __shfl_xor_sync(0xffffffffu, l1, 2);
      float f0 = rcp(l0), f1 = rcp(l1);
      asm volatile("" : "+f"(f0), "+f"(f1)::"memory");
      await(ST0 - 1);
      unpark(1, 0, 4);
      bar_sync(my_turn, 256);
      pin(pf); pin(o);
      wg_fence();
#pragma unroll
      for (int k = 0; k < 8; k++)
        mma_n128<1>(o, pf[4 * k], pf[4 * k + 1], pf[4 * k + 2], pf[4 * k + 3], mkdesc(ring + SL_KE * STAGE, 16384) + k * 128, 1);
      wg_commit();
      await(ST0);
      unpark(1, 4, 8);
      block_fence(61, zero);
#pragma unroll
      for (int k = 0; k < 8; k++) mma_n128_ss<1>(ar, mkdesc(slot, 16) + (k >> 2) * 512 + (k & 3) * 2, mkdesc(ring + (ST0 & 3) * STAGE, 16384) + k * 128, k > 0);
      wg_commit();
      bar_arrive(other_turn, 256);
      wg_wait<1>();
      pin(o); pin(pf);
      mbar_arrive_cluster_now<62>(empty_c + 8 * SL_KE, signaller, zero);
#pragma unroll
      for (int i = 0; i < 16; i++) {
        pf[2 * i] = pack2(o[4 * i] * f0, o[4 * i + 1] * f0);
        pf[2 * i + 1] = pack2(o[4 * i + 2] * f1, o[4 * i + 3] * f1);
      }
      pin(pf);
      prof(wg, 10);
#pragma unroll
      for (int u = 1; u < 4; u++) {
        await(ST0 + u);
        wg_wait<0>();
        release(ST0 + u - 1);
        bar_sync(my_turn, 256);
        wg_fence();
#pragma unroll
        for (int k = 0; k < 8; k++) {
          const uint32_t* a = (u == 1 ? oa + 32 : u == 2 ? pf : oa + 64) + 4 * k;
          mma_n128<1>(ar, a[0], a[1], a[2], a[3], mkdesc(ring + ((ST0 + u) & 3) * STAGE, 16384) + k * 128, 1);
        }
        wg_commit();
        bar_arrive(other_turn, 256);
        if (u < 3) {
          block_fence(62 + u, zero);
          unpark(u == 1 ? 2 : 0, 0, 8);
        }
      }
      mbar_wait(cx.sb + SM_BAR_MISC, 0);
      await(ST0 + 4);
      wg_wait<0>();
      release(ST0 + 3);
      pin(ar);
#pragma unroll
      for (int i = 0; i < 32; i++) { first[i] = ar[i]; red[i] = ar[32 + i]; }
    }
    const uint32_t tag = *(const uint32_t*)(cx.sp + SM_TAG);
    uint4* const xch = at<uint4>(cx.gs->part, (qb << 20) + lane * 16);
    auto send = [&](const float (&v)[32], int dst, int idx) {
      uint4* p = at<uint4>(xch, (dst * 8 + idx) * 2048);
#pragma unroll
      for (int i = 0; i < 4; i++)
        st_gran(p + i * 32, (pack2(v[8 * i], v[8 * i + 1]) & ~TAG_BIT) | tag, pack2(v[8 * i + 2], v[8 * i + 3]),
                pack2(v[8 * i + 4], v[8 * i + 5]), pack2(v[8 * i + 6], v[8 * i + 7]));
    };
    send(first, ((hs + 1) & 7) * 7, cw);
    int nrx = 1;
    auto half_step = [&](int s, auto hc, bool arrive) {
      constexpr int h = decltype(hc)::value;
      const int st = ST0 + 2 * s + h;
      const uint64_t db = mkdesc(ring + (st & 3) * STAGE, 16);
      bar_sync(my_turn, 256);
      if (h == 0) pin(pf);
#pragma unroll
      for (int i = 32 * h; i < 32 + 64 * h; i++) asm volatile("" : "+r"(oa[i])::"memory");
      wg_fence();
#pragma unroll
      for (int k = 0; k < 16; k++) {
        const int kb = h * 16 + k - 8;
        if (kb >= 0) mma_n64<1>(acc, oa[4 * kb], oa[4 * kb + 1], oa[4 * kb + 2], oa[4 * kb + 3], db + k * 128, 1);
        else mma_n64<1>(acc, pf[4 * k], pf[4 * k + 1], pf[4 * k + 2], pf[4 * k + 3], db + k * 128, k > 0);
      }
      wg_commit();
      if (arrive) bar_arrive(other_turn, 256);
    };
    auto source = [&](int n) { return at<const uint4>(xch, ((hs * 7 + n - 1) * 8 + cw) * 2048); };
    auto fetch = [&](uint32_t (&g)[16], const uint4* p) {
#pragma unroll
      for (int i = 0; i < 4; i++) ld_gran(p + i * 32, g[4 * i], g[4 * i + 1], g[4 * i + 2], g[4 * i + 3]);
    };
    uint32_t g[16];
#pragma unroll 1
    for (int s = 2; s < 8; s++) {
      const int st = ST0 + 2 * s;
      half_step(s, IC<0>(), true);
      if (s == 2) {
        bar_arrive(BAR_OA, 352);
        send(red, 56 + cw, hs);
#pragma unroll
        for (int i = 0; i < 32; i++) red[i] = 0.f;
      }
      await(st + 1);
      if (s > 3 && granules_ok(g, tag)) { add_granules(red, g); nrx++; }
      wg_wait<0>();
      if (s < 7) release(st);
      if (s > 2) fetch(g, source(nrx));
      half_step(s, IC<1>(), true);
      await(st + 2);
      wg_wait<0>();
      if (s < 7) release(st + 1);
      pin(acc);
      if (s == 7) prof(wg, 19);
      if (s == 7) TE(0)
      send(acc, ((hs + s) & 7) * 7 + s - 1, cw);
    }
    TE(1)
    uint32_t xv[16], gt[16];
    {
      const int s = 8;
      uint32_t g2[16];
      half_step(s, IC<0>(), true);
      TE(2)
      await(NST_Q + NST_KV + NST_O - 1);
      cluster_arrive();
      mbar_wait(cx.sb + SM_BAR_XG, 0);
      const uint32_t tile = cx.sb + SM_XO + wg * 8192 + lo;
      if (granules_ok(g, tag)) { add_granules(red, g); nrx++; }
      fetch(g, source(nrx));
      block_fence(58, zero);
      wg_wait<0>();
      TE(3)
#pragma unroll
      for (int k = 0; k < 4; k++) ldsm4((tile ^ (k << 5)) + STAGE, gt[4 * k], gt[4 * k + 1], gt[4 * k + 2], gt[4 * k + 3]);
      half_step(s, IC<1>(), wg == 0);
      TE(4)
      block_fence(56, zero);
      const bool ok = granules_ok(g, tag);
      block_fence(57, zero + ok * 1000);
      const uint4* src = source(7);
      fetch(g2, src);
#pragma unroll
      for (int k = 0; k < 4; k++) ldsm4(tile ^ (k << 5), xv[4 * k], xv[4 * k + 1], xv[4 * k + 2], xv[4 * k + 3]);
      if (ok) { add_granules(red, g); nrx++; }
      TE(5)
      block_fence(59, zero);
      wg_wait<0>();
      pin(acc);
      TE(6)
#pragma unroll
      for (int i = 0; i < 32; i++) red[i] += acc[i];
      pin(red);
      TE(7)
      int n = 7;
#pragma unroll 1
      for (int spins = 0; spins < (1 << 16); spins++) {
        if (granules_ok(g2, tag)) {
          add_granules(red, g2);
          if (--n < nrx) {
            break;
          }
          src -= 1024;
        }
        fetch(g2, src);
      }
      TE(8)
    }
    prof(wg, 20);
    TE(9)
    const uint32_t ot = ring + ((ST0 + NST_O) & 3) * STAGE + cw * (16 * 144);
    uint32_t ow[16];
#pragma unroll
    for (int i = 0; i < 16; i++) ow[i] = fma2(pack2(red[2 * i], red[2 * i + 1]), gt[i], xv[i]);
#pragma unroll
    for (int i = 0; i < 4; i++)
      stsm4(ot + (lane & 15) * 144 + (2 * i + (lane >> 4)) * 16, ow[4 * i], ow[4 * i + 1], ow[4 * i + 2], ow[4 * i + 3]);
    __syncwarp();
#pragma unroll
    for (int i = 0; i < 4; i++) {
      uint4 v;
      lds128(ot + (i * 4 + (lane >> 3)) * 144 + (lane & 7) * 16, v.x, v.y, v.z, v.w);
      at<uint4>(out, ((qb * 128 + cw * 16 + (lane >> 3)) * DM + hs * 64 + (lane & 7) * 8) * 2)[i * (4 * DM / 8)] = v;
    }
    TE(10)
    prof(wg, 22);
  }
}

constexpr int AST_X = 6, AST_F = AST_X + 96;
__device__ __forceinline__ void aux_producer(const Ctx& cx, int f, const CUtensorMap* tmWq, const CUtensorMap* tmG) {
  const uint32_t full = cx.sb + SM_FULL, empty = cx.sb + SM_EMPTY;
  __nanosleep(3000);
  if (elect_one()) {
#pragma unroll 1
    for (int st = 0; st < AST_X; st++) {
      mbar_expect_tx(full + 8 * st, FSTAGE);
#pragma unroll
      for (int i = 0; i < 3; i++)
        tma2d_stream(cx.sb + st * FSTAGE + i * 8192, tmWq, (2 * f + (st & 1)) * 512 + 448, (st >> 1) * 192 + i * 64, full + 8 * st);
    }
  }
  __syncwarp();
  mbar_wait(cx.sb + SM_BAR_MISC, 0);
  proxy_fence();
  int st = AST_X;
#pragma unroll 1
  for (; st < AST_F; st++) {
    const uint32_t sl = st & 7;
    mbar_wait(empty + 8 * sl, ((st >> 3) & 1) ^ 1);
    if (elect_one()) {
      mbar_expect_tx(full + 8 * sl, FSTAGE);
      bulk_load(cx.sb + sl * FSTAGE, cx.gs->xn + (st - AST_X) * (FSTAGE / 16), FSTAGE, full + 8 * sl);
    }
    __syncwarp();
  }
#pragma unroll 1
  for (int pair = 0; pair < 14; pair++) {
#pragma unroll 1
    for (int u = 0; u < 12; u++, st++) {
      const uint32_t sl = st & 7;
      const int unit = pair * 2 + (u & 1), k = u >> 1;
      if (unit == 27) continue;
      const bool gu = pair < 9;
      mbar_wait(empty + 8 * sl, ((st >> 3) & 1) ^ 1);
      if (elect_one()) {
        mbar_expect_tx(full + 8 * sl, FSTAGE);
        tma2d_stream(cx.sb + sl * FSTAGE, tmG + (gu ? k >= 3 : 2), gu ? f * 1152 + unit * 64 : (unit - 18) * 64,
                     gu ? (k >= 3 ? k - 3 : k) * 192 : f * 1152 + k * 192, full + 8 * sl);
      }
      __syncwarp();
    }
  }
}

constexpr int BAR_FREE = 4, BAR_TILE = 6;
__device__ __forceinline__ void aux_helper(const Ctx& cx, int f, int warp, int lane) {
  unsigned epoch = 0;
  if (lane == 0) epoch = cx.gs->launch[blockIdx.x] + 1;
  epoch = __shfl_sync(0xffffffffu, epoch, 0);
  bar_sync(BAR_OA, 96);
  if (warp == 3) {
    if (lane == 0) cx.gs->launch[blockIdx.x] = epoch;
    await_count(at<const unsigned>(cx.gs->rows, (lane & 15) * 128), 8 * epoch, 200);
    if (lane == 0) mbar_arrive(cx.sb + SM_BAR_MISC);
    prof(0, 1, 31);
    await_count(at<const unsigned>(cx.gs->rows, (lane & 15) * 128 + 4), 8 * epoch, 500);
    uint32_t bound = 0xFFFFFFFFu, m0 = 0, m1 = 0;
#pragma unroll 1
    for (int k = 0; k < TOPC; k++) {
      if (__any_sync(0xffffffffu, m0 == 0)) {
        m0 = m1 = 0;
#pragma unroll 2
        for (int i = 0; i < 16; i++) {
          const uint4 v = __ldcg(at<const uint4>(cx.gs->key, lane * 16 + i * 512));
          const uint32_t w[4] = {v.x, v.y, v.z, v.w};
#pragma unroll
          for (int j = 0; j < 4; j++) {
            const uint32_t t = w[j] <= bound ? w[j] : 0;
            m1 = max(m1, min(m0, t));
            m0 = max(m0, t);
          }
        }
      }
      uint32_t m = m0;
      m = __reduce_max_sync(0xffffffffu, m);
      bound = m - 1;
      if (m0 == m) { m0 = m1; m1 = 0; }
      if (f == 0 && lane == 0) *at<uint32_t>(cx.gs->top, k * 4) = m;
#pragma unroll
      for (int j = 0; j < 3; j++) {
        const uint32_t row = 0xFFFF - (m & 0xFFFF), i = min(j * 4 + (lane >> 3), 8);
        *(uint4*)(cx.sp + SM_XSEL + i * 1024 + k * 128 + (((lane ^ k) & 7) << 4)) =
            __ldcg(at<const uint4>(cx.gs->xn, xn_offset(row, (lane & 7) * 4) + i * 8192));
      }
    }
    asm volatile("fence.proxy.async.shared::cta;" ::: "memory");
    prof(0, 2, 31);
  } else {
    const int wg = warp - 1;
#pragma unroll 1
    for (int u = 0; u < 32; u++) {
      bar_arrive(BAR_FREE + wg, 160);
      bar_sync(BAR_TILE + wg, 160);
      if (elect_one()) {
        const int n = (u >> 1) * 8 + 2 * f + wg;
        asm volatile("cp.async.bulk.global.shared::cta.bulk_group [%0], [%1], 8192;\ncp.async.bulk.commit_group;\ncp.async.bulk.wait_group 0;"
                     ::"l"(cx.gs->q3 + (n * 2 + (u & 1)) * 512), "r"(cx.sb + SM_H + wg * 8192) : "memory");
        if (u & 1) st_release(&cx.gs->q3_flag[n], epoch);
      }
      __syncwarp();
    }
  }
  bar_arrive(3, 352);
}

__device__ __forceinline__ void aux_consumer(const Ctx& cx, int f, int wg, int cw, int lane) {
  const int r = lane >> 2, c = lane & 3, tid = cw * 32 + lane;
  const uint32_t full = cx.sb + SM_FULL, empty = cx.sb + SM_EMPTY;
  const bool signaller = (tid & 127) == 0;
  auto await = [&](int st) { mbar_wait(full + 8 * (st & 7), (st >> 3) & 1); };
  auto release = [&](int st, int cnt) {
    asm volatile("{\n.reg .pred p;\nsetp.ne.u32 p, %2, 0;\n@p mbarrier.arrive.shared::cta.b64 _, [%0], %1;\n}"
                 ::"r"(empty + 8 * (st & 7)), "r"(cnt), "r"((uint32_t)signaller) : "memory");
  };
  prof(wg, 0);
  {
    const uint32_t lt = ((lane & 7) + (lane >> 4) * 8) * 128 + ((((cw & 3) * 2 + ((lane >> 3) & 1)) ^ (lane & 7)) << 4);
    uint32_t wa[144];
#pragma unroll
    for (int i = 0; i < 3; i++) {
      await(2 * i + wg);
#pragma unroll
      for (int k = 0; k < 12; k++) {
        const int kb = 12 * i + k;
        ldsm4t(cx.sb + (2 * i + wg) * FSTAGE + k * 2048 + lt, wa[4 * kb], wa[4 * kb + 1], wa[4 * kb + 2], wa[4 * kb + 3]);
      }
    }
    bar_sync(1, 256);
#pragma unroll
    for (int i = 0; i < 3; i++) release(2 * i + wg, 2);
    if (wg) bar_arrive(1, 256);
#pragma unroll 1
    for (int st = AST_X; st < AST_F; st += 3) {
      float acc[32];
      await(st);
      await(st + 1);
      await(st + 2);
      bar_sync(1 + wg, 256);
      wg_fence();
#pragma unroll
      for (int kb = 0; kb < 36; kb++) {
        const int i = kb / 12, k = kb % 12;
        mma_n64<0>(acc, wa[4 * kb], wa[4 * kb + 1], wa[4 * kb + 2], wa[4 * kb + 3],
                   mkdesc(cx.sb + ((st + i) & 7) * FSTAGE, 16) + (k >> 2) * 512 + (k & 3) * 2, kb > 0);
        if (k == 11) wg_commit();
      }
      if (st < AST_F - 3 || !wg) bar_arrive(2 - wg, 256);
      wg_wait<1>();
      release(st, 1);
      release(st + 1, 1);
      bar_sync(BAR_FREE + wg, 160);
      wg_wait<0>();
      pin(acc);
      release(st + 2, 1);
#pragma unroll
      for (int k = 0; k < 4; k++)
        stsm4t(cx.sb + SM_H + wg * 8192 + k * 2048 + lt, pack2(acc[8 * k] * SM_SCALE_LOG2, acc[8 * k + 1] * SM_SCALE_LOG2),
               pack2(acc[8 * k + 2] * SM_SCALE_LOG2, acc[8 * k + 3] * SM_SCALE_LOG2),
               pack2(acc[8 * k + 4] * SM_SCALE_LOG2, acc[8 * k + 5] * SM_SCALE_LOG2),
               pack2(acc[8 * k + 6] * SM_SCALE_LOG2, acc[8 * k + 7] * SM_SCALE_LOG2));
      asm volatile("fence.proxy.async.shared::cta;" ::: "memory");
      bar_arrive(BAR_TILE + wg, 160);
    }
    bar_sync(3, 352);
  }
  prof(wg, 3);
#pragma unroll 1
  for (int unit = wg; unit < 27; unit += 2) {
    if (unit >> 1 == 9) {
      asm volatile("fence.proxy.async.shared::cta;" ::: "memory");
      bar_sync(3, 256);
      prof(wg, 4);
    }
    const bool gu = unit < 18;
    float a0[4], a1[4];
#pragma unroll 1
    for (int m = 0; m < 2; m++) {
      float p0[4], p1[4];
      int st = AST_F + (unit >> 1) * 12 + m * 6 + wg;
      uint32_t b = cx.sb + (gu ? SM_XSEL : SM_H + m * 9216);
#pragma unroll 1
      for (int u = 0; u < 3; u++, st += 2, b += 3072) {
        await(st);
        wg_fence();
        const uint64_t da = mkdesc(cx.sb + (st & 7) * FSTAGE, 16), db = mkdesc(b, 16);
#pragma unroll
        for (int k = 0; k < 12; k++) mma_n8((k & 1) ? p1 : p0, da + k * 128, db + (k >> 2) * 64 + (k & 3) * 2, u > 0 || k > 1);
        wg_commit();
        wg_wait<1>();
        if (u) release(st - 2, 2);
      }
      wg_wait<0>();
      release(st - 2, 2);
      pin(p0); pin(p1);
#pragma unroll
      for (int i = 0; i < 4; i++) { a0[i] = a1[i]; a1[i] = p0[i] + p1[i]; }
    }
#pragma unroll
    for (int i = 0; i < 4; i++) {
      const int fl = (cw & 3) * 16 + r + (i >> 1) * 8, tok = 2 * c + (i & 1);
      if (gu) {
        const float h = bfr(silu_f(bfr(a0[i]))) * bfr(a1[i]);
        *(__nv_bfloat16*)(cx.sp + SM_H + unit * 1024 + tok * 128 + (((fl >> 3) ^ tok) << 4) + (fl & 7) * 2) = __float2bfloat16_rn(h);
      } else {
        *at<float>(cx.gs->ypart, ((f * TOPC + tok) * DM + (unit - 18) * 64 + fl) * 4) = a0[i] + a1[i];
      }
    }
  }
  prof(wg, 5);
  bar_sync(3, 256);
  if (tid == 0) red_release(&cx.gs->ycnt);
  prof(wg, 6);
}

struct Maps { CUtensorMap m[9]; };
__global__ void __cluster_dims__(2, 1, 1) __launch_bounds__(THREADS, 1)
fused_kernel(const __nv_bfloat16* __restrict__ x, const __nv_bfloat16* __restrict__ w_r, const __nv_bfloat16* __restrict__ kc,
             const __nv_bfloat16* __restrict__ wo, __nv_bfloat16* __restrict__ out, Scratch* gs,
             const __grid_constant__ Maps maps) {
  const CUtensorMap &tmX = maps.m[0], &tmWq = maps.m[1], &tmK = maps.m[2], &tmV = maps.m[3], &tmWo = maps.m[4];
  extern __shared__ __align__(1024) uint8_t smem_raw[];
  prof(0, 23, 511);
  if (threadIdx.x < 72 && blockIdx.x < N_ATT_CTA)
    asm volatile("prefetch.global.L2 [%0];" ::"l"(at<const void>(x, ((blockIdx.x >> 3) * 128 + (blockIdx.x & 7) * 8) * (DM * 2) + threadIdx.x * 128)));
  Ctx cx;
  cx.sb = smem_u32(smem_raw);
  cx.sp = smem_raw;
  cx.gs = gs;
  cx.rank = blockIdx.x & 1;
  const int warp = __shfl_sync(0xffffffffu, threadIdx.x >> 5, 0);
  const int cluster = blockIdx.x >> 1;
  const bool is_aux = blockIdx.x >= N_ATT_CTA;
  const int c7 = ((cluster - 36) * 37) >> 8;
  const int hs = cluster < 4 ? 4 + cluster : cluster < 36 ? (cluster - 4) >> 3 : 4 + c7;
  const int qb = (cluster < 4 ? 0 : cluster < 36 ? (cluster - 4) & 7 : cluster - 35 - 7 * c7) * 2 + cx.rank;

  extern __shared__ __align__(1024) uint8_t smem_alias[];
  const uint32_t xf = smem_u32(smem_alias) + SM_MISC + warp * 24;
  if (warp == 4 && elect_one()) prefetch_tmap(&tmX);
  if (elect_one()) {
    const uint32_t cnt = (warp > 4 && warp < 8) ? (is_aux ? 2 : 4) : 1;
#pragma unroll
    for (int i = 0; i < 3; i++) mbar_init(xf + 8 * i, cnt);
    asm volatile("fence.proxy.async.shared::cta;" ::: "memory");
    asm volatile("fence.mbarrier_init.release.cluster;" ::: "memory");
  }
  __syncwarp();
  cluster_arrive();
  if (warp == 4 && !is_aux) {
    if (elect_one()) {
      profc(0, 28);
#pragma unroll
      for (int i = 0; i < 3; i++) {
        mbar_expect_tx(xf + 8 * i, 24576);
        tma3d(xf - SM_XFULL + SM_X + i * 24576, &tmX, qb * 128, i * 3, xf + 8 * i);
      }
      profc(0, 29);
    }
  } else if (warp > 7 && elect_one()) {
    prefetch_tmap(&tmX + (is_aux ? warp - 4 : warp == 8 ? 8 : warp - 8));
  }
  __syncwarp();

  if (warp < 4) {
    asm volatile("setmaxnreg.dec.sync.aligned.u32 24;");
    cluster_wait();
    prof(0, 24, 511);
    if (warp == 0) {
      if (!is_aux) attn_producer(cx, qb, hs, &tmX, &tmK, &tmV, &tmWq, &tmWo);
      else aux_producer(cx, blockIdx.x - N_ATT_CTA, &tmWq, &maps.m[5]);
      prof(0, 25, 511);
    } else if (!is_aux) {
      attn_rows(cx, qb, hs, 3 - warp, read_lane(), &maps.m[8], w_r);
      if (warp == 1) attn_helper(cx, qb, hs, read_lane(), wo, &maps.m[8]);
      else bar_sync(BAR_OA, 352);
      attn_finish8(cx, qb, hs, warp - 1, read_lane(), out);
    } else {
      aux_helper(cx, blockIdx.x - N_ATT_CTA, warp, read_lane());
    }
    __syncwarp();
    cluster_arrive();
    cluster_wait();
    if (threadIdx.x == 32) { dly(cx, 201); dly(cx, 251); }
  } else {
    asm volatile("setmaxnreg.inc.sync.aligned.u32 240;");
    cluster_wait();
    const int cw = warp - 4, wg = cw >> 2;
    if (is_aux) aux_consumer(cx, blockIdx.x - N_ATT_CTA, wg, cw, read_lane());
    else attn_consumer(cx, qb, hs, wg, cw, read_lane(), x, kc, out);
  }
}

typedef CUresult (*EncodeFn)(CUtensorMap*, CUtensorMapDataType, cuuint32_t, void*, const cuuint64_t*, const cuuint64_t*,
                             const cuuint32_t*, const cuuint32_t*, CUtensorMapInterleave, CUtensorMapSwizzle,
                             CUtensorMapL2promotion, CUtensorMapFloatOOBfill);

void encode(EncodeFn fn, CUtensorMap* m, const void* p, int rank, const cuuint64_t* dims, const cuuint64_t* strides,
            const cuuint32_t* box) {
  const cuuint32_t es[5] = {1, 1, 1, 1, 1};
  fn(m, CU_TENSOR_MAP_DATA_TYPE_BFLOAT16, rank, const_cast<void*>(p), dims, strides, box, es, CU_TENSOR_MAP_INTERLEAVE_NONE,
     CU_TENSOR_MAP_SWIZZLE_128B, CU_TENSOR_MAP_L2_PROMOTION_L2_128B, CU_TENSOR_MAP_FLOAT_OOB_FILL_NONE);
}
void encode2d(EncodeFn fn, CUtensorMap* m, const void* p, uint64_t rows, uint64_t cols, uint32_t box_rows) {
  const cuuint64_t dims[2] = {cols, rows}, strides[1] = {cols * 2};
  const cuuint32_t box[2] = {64, box_rows};
  encode(fn, m, p, 2, dims, strides, box);
}

}

extern "C" void kernel_launch(void* const* d_in, const int* in_sizes, int n_in, void* d_out, int out_size) {
  (void)in_sizes; (void)n_in; (void)out_size;
  void* fnp = nullptr;
  cudaDriverEntryPointQueryResult qr;
  cudaGetDriverEntryPoint("cuTensorMapEncodeTiled", &fnp, cudaEnableDefault, &qr);
  EncodeFn fn = (EncodeFn)fnp;
  void* gs = nullptr;
  cudaGetSymbolAddress(&gs, g_scratch);
  Maps maps;
  CUtensorMap &tmX = maps.m[0], &tmWq = maps.m[1], &tmK = maps.m[2], &tmV = maps.m[3], &tmWo = maps.m[4], &tmG = maps.m[5],
              &tmU = maps.m[6], &tmD = maps.m[7];
  encode2d(fn, &tmK, d_in[1], 16 * SEQ, DH, 128);
  encode2d(fn, &tmV, d_in[2], 16 * SEQ, DH, 128);
  encode2d(fn, &tmWq, d_in[3], DM, 4096, 64);
  {
    const cuuint64_t dims[3] = {64, SEQ, 9}, strides[2] = {DM * 2, 128};
    const cuuint32_t box[3] = {64, 64, 3};
    encode(fn, &tmX, d_in[0], 3, dims, strides, box);
  }
  encode2d(fn, &maps.m[8], d_in[0], SEQ, DM, 16);
  encode2d(fn, &tmWo, d_in[4], 4096, DM, 128);
  encode2d(fn, &tmG, d_in[7], DM, FF, 192);
  encode2d(fn, &tmU, d_in[8], DM, FF, 192);
  encode2d(fn, &tmD, d_in[9], FF, DM, 192);
  cudaFuncSetAttribute(fused_kernel, cudaFuncAttributeMaxDynamicSharedMemorySize, SM_TOTAL);
  fused_kernel<<<N_CTA, THREADS, SM_TOTAL>>>((const __nv_bfloat16*)d_in[0], (const __nv_bfloat16*)d_in[6], (const __nv_bfloat16*)d_in[1],
                                            (const __nv_bfloat16*)d_in[4], (__nv_bfloat16*)d_out, (Scratch*)gs, maps);
}
```

```cpp
#include <cuda_runtime.h>
#include <cuda_bf16.h>
#include <cuda.h>
#include <stdint.h>

namespace {

constexpr int SEQ = 2048, DM = 576, DH = 128, FF = 4608, TOPC = 8;
constexpr int N_ATT_CTA = 128, N_CTA = 132;
constexpr int THREADS = 384;

constexpr uint32_t SM_RING = 0;
constexpr uint32_t STAGE = 32768;
constexpr uint32_t SM_SLOT = 131072;
constexpr uint32_t FSTAGE = 24576;
constexpr uint32_t SM_XSEL = 196608;
constexpr uint32_t SM_H = 205824;
constexpr uint32_t SM_MISC = 229376;
constexpr uint32_t SM_FULL = SM_MISC, SM_BAR_MISC = SM_MISC + 64, SM_BAR_XG = SM_MISC + 72, SM_BAR_P8 = SM_MISC + 80, SM_BAR_Q3 = SM_MISC + 88, SM_XFULL = SM_MISC + 96,
                   SM_EMPTY = SM_MISC + 120, SM_BAR_ROWS = SM_MISC + 216, SM_TAG = SM_MISC + 288,
                   SM_ROWS = SM_MISC + 304, SM_BOX8 = SM_MISC + 1024;
constexpr uint32_t SM_TOTAL = SM_MISC + 3072;
constexpr uint32_t SM_X = SM_MISC - 147456;

constexpr int BAR_ROWS = 6, BAR_HELPER = 7, BAR_OA = 8;
constexpr int NST_Q = 18, NST_KV = 128, NST_O = 18;
constexpr uint32_t SL_KE = (NST_Q - 1) & 3, SL_VE = NST_Q & 3, SL_KO = (NST_Q + 1) & 3, SL_VO = (NST_Q + 2) & 3;
#define X_N1 5
#define X_SPLIT 44
#define X_SPLIT3 36
#define X_PARK 5
#define X_C0 16
#define X_C1 32
#define X_C2 56
constexpr float SM_SCALE_LOG2 = 0.08838834764831845f * 1.4426950408889634f;

struct Scratch {
  uint4 part[16 * 64 * 2 * 4 * 128];
  uint4 gate[N_ATT_CTA * 144 * 8];
  uint4 q3[N_ATT_CTA * 1024];
  uint4 xn[SEQ * DM / 8];
  uint32_t key[SEQ];
  float ypart[4 * TOPC * DM];
  uint32_t top[32];
  unsigned launch[160];
  unsigned rows[16 * 32];
  unsigned q3_flag[N_ATT_CTA];
  unsigned ycnt;
};
__device__ __align__(1024) Scratch g_scratch;

__device__ __forceinline__ void prof(int, int, int = 0) {}
__device__ __forceinline__ void profc(int, int) {}

__device__ __forceinline__ uint32_t smem_u32(const void* p) { return (uint32_t)__cvta_generic_to_shared(p); }
__device__ __forceinline__ void mbar_init(uint32_t bar, uint32_t cnt) {
  asm volatile("mbarrier.init.shared::cta.b64 [%0], %1;" ::"r"(bar), "r"(cnt) : "memory");
}
__device__ __forceinline__ void mbar_expect_tx(uint32_t bar, uint32_t bytes) {
  asm volatile("mbarrier.arrive.expect_tx.shared::cta.b64 _, [%0], %1;" ::"r"(bar), "r"(bytes) : "memory");
}
__device__ __forceinline__ void mbar_arrive(uint32_t bar) {
  asm volatile("mbarrier.arrive.shared::cta.b64 _, [%0];" ::"r"(bar) : "memory");
}
__device__ __forceinline__ void mbar_arrive_cluster(uint32_t bar_cluster_addr) {
  asm volatile("mbarrier.arrive.shared::cluster.b64 _, [%0];" ::"r"(bar_cluster_addr) : "memory");
}
template <int ID>
__device__ __forceinline__ void mbar_arrive_cluster_now(uint32_t bar_cluster_addr, bool pred, uint32_t zero) {
  asm volatile("{\n.reg .pred p, q;\nsetp.ne.u32 p, %1, 0;\nsetp.eq.u32 q, %2, %3;\n"
               "ARR_LOOP:\n@p mbarrier.arrive.shared::cluster.b64 _, [%0];\n@q bra.uni ARR_LOOP;\n}"
               ::"r"(bar_cluster_addr), "r"((uint32_t)pred), "r"(zero), "n"(ID) : "memory");
}
__device__ __forceinline__ void block_fence(int id, uint32_t zero = blockIdx.y) {
  asm volatile("{\n.reg .pred q;\nsetp.eq.u32 q, %0, %1;\nBF_LOOP:\n@q st.volatile.shared.u32 [%0], %0;\n@q bra.uni BF_LOOP;\n}"
               ::"r"(zero), "r"(id) : "memory");
}
__device__ __forceinline__ bool mbar_test(uint32_t bar, uint32_t parity) {
  uint32_t ok;
  asm volatile("{\n.reg .pred p;\nmbarrier.test_wait.parity.shared::cta.b64 p, [%1], %2;\nselp.u32 %0, 1, 0, p;\n}"
               : "=r"(ok) : "r"(bar), "r"(parity) : "memory");
  return ok;
}
__device__ __forceinline__ void mbar_wait(uint32_t bar, uint32_t parity) {
  asm volatile("{\n.reg .pred p, q;\n.reg .u32 n;\nmov.u32 n, 0;\n"
               "WAIT_LOOP:\nmbarrier.try_wait.parity.shared::cta.b64 p, [%0], %1;\n"
               "add.u32 n, n, 1;\nsetp.lt.u32 q, n, 4194304;\nand.pred q, q, !p;\n@q bra WAIT_LOOP;\n}"
               ::"r"(bar), "r"(parity) : "memory");
}
__device__ __forceinline__ uint32_t mapa(uint32_t addr, uint32_t rank) {
  uint32_t r;
  asm volatile("mapa.shared::cluster.u32 %0, %1, %2;" : "=r"(r) : "r"(addr), "r"(rank));
  return r;
}
__device__ __forceinline__ void cluster_arrive() { asm volatile("barrier.cluster.arrive.relaxed.aligned;" ::: "memory"); }
__device__ __forceinline__ bool elect_one() {
  uint32_t p;
  asm volatile("{\n.reg .pred p;\nelect.sync _|p, 0xffffffff;\nselp.u32 %0, 1, 0, p;\n}" : "=r"(p));
  return p;
}
__device__ __forceinline__ int read_lane() { return threadIdx.x & 31; }
__device__ __forceinline__ void cluster_wait() { asm volatile("barrier.cluster.wait.acquire.aligned;" ::: "memory"); }
__device__ __forceinline__ void bar_sync(int id, int n) { asm volatile("barrier.cta.sync %0, %1;" ::"r"(id), "r"(n) : "memory"); }
__device__ __forceinline__ void bar_arrive(int id, int n) { asm volatile("barrier.cta.arrive %0, %1;" ::"r"(id), "r"(n) : "memory"); }

__device__ __forceinline__ uint64_t policy_evict_first() {
  uint64_t p;
  asm("createpolicy.fractional.L2::evict_first.b64 %0, 1.0;" : "=l"(p));
  return p;
}
__device__ __forceinline__ uint64_t policy_evict_normal() {
  uint64_t p;
  asm("createpolicy.fractional.L2::evict_normal.b64 %0, 1.0;" : "=l"(p));
  return p;
}
__device__ __forceinline__ void tma3d(uint32_t dst, const CUtensorMap* tm, int c1, int c2, uint32_t bar) {
  asm volatile("cp.async.bulk.tensor.3d.shared::cluster.global.mbarrier::complete_tx::bytes [%0], [%1, {%2, %3, %4}], [%5];"
               ::"r"(dst), "l"(tm), "r"(0), "r"(c1), "r"(c2), "r"(bar) : "memory");
}
__device__ __forceinline__ void tma2d(uint32_t dst, const CUtensorMap* tm, int c0, int c1, uint32_t bar) {
  asm volatile("cp.async.bulk.tensor.2d.shared::cluster.global.mbarrier::complete_tx::bytes [%0], [%1, {%2, %3}], [%4];"
               ::"r"(dst), "l"(tm), "r"(c0), "r"(c1), "r"(bar) : "memory");
}
__device__ __forceinline__ void tma2d_stream(uint32_t dst, const CUtensorMap* tm, int c0, int c1, uint32_t bar) {
  asm volatile("{\n.reg .b64 pol;\ncreatepolicy.fractional.L2::evict_first.b64 pol, 1.0;\n"
               "cp.async.bulk.tensor.2d.shared::cluster.global.mbarrier::complete_tx::bytes.L2::cache_hint [%0], [%1, {%2, %3}], [%4], pol;\n}"
               ::"r"(dst), "l"(tm), "r"(c0), "r"(c1), "r"(bar) : "memory");
}
__device__ __forceinline__ void tma2d_prefetch(const CUtensorMap* tm, int c0, int c1) {
  asm volatile("cp.async.bulk.prefetch.tensor.2d.L2.global [%0, {%1, %2}];" ::"l"(tm), "r"(c0), "r"(c1) : "memory");
}
__device__ __forceinline__ void prefetch_l2(const void* p, uint32_t bytes) {
  asm volatile("cp.async.bulk.prefetch.L2.global [%0], %1;" ::"l"(p), "r"(bytes) : "memory");
}
__device__ __forceinline__ void prefetch_tmap(const CUtensorMap* tm) {
  asm volatile("prefetch.tensormap [%0];" ::"l"(tm) : "memory");
}

__device__ __forceinline__ void wg_fence() { asm volatile("wgmma.fence.sync.aligned;" ::: "memory"); }
__device__ __forceinline__ void wg_commit() { asm volatile("wgmma.commit_group.sync.aligned;" ::: "memory"); }
template <int N> __device__ __forceinline__ void wg_wait() { asm volatile("wgmma.wait_group.sync.aligned %0;" ::"n"(N) : "memory"); }

__device__ __forceinline__ uint64_t mkdesc(uint32_t addr, uint32_t lbo_bytes) {
  return (uint64_t)(((addr & 0x3FFFF) >> 4) | ((lbo_bytes >> 4) << 16)) | ((uint64_t)0x40000040u << 32);
}
template <int N> __device__ __forceinline__ void pin(float (&a)[N]) {
#pragma unroll
  for (int i = 0; i < N; i++) asm volatile("" : "+f"(a[i])::"memory");
}
template <int N> __device__ __forceinline__ void pin(uint32_t (&a)[N]) {
#pragma unroll
  for (int i = 0; i < N; i++) asm volatile("" : "+r"(a[i])::"memory");
}

#define F8(d, o) "+f"(d[o]), "+f"(d[o + 1]), "+f"(d[o + 2]), "+f"(d[o + 3]), "+f"(d[o + 4]), "+f"(d[o + 5]), "+f"(d[o + 6]), "+f"(d[o + 7])
#define R32A "%0, %1, %2, %3, %4, %5, %6, %7, %8, %9, %10, %11, %12, %13, %14, %15, %16, %17, %18, %19, %20, %21, %22, %23, %24, %25, %26, %27, %28, %29, %30, %31"
#define R32B "%32, %33, %34, %35, %36, %37, %38, %39, %40, %41, %42, %43, %44, %45, %46, %47, %48, %49, %50, %51, %52, %53, %54, %55, %56, %57, %58, %59, %60, %61, %62, %63"

template <int TB>
__device__ __forceinline__ void mma_n128(float (&d)[64], uint32_t a0, uint32_t a1, uint32_t a2, uint32_t a3, uint64_t db, int acc) {
  asm volatile("{\n.reg .pred p;\nsetp.ne.b32 p, %69, 0;\n"
               "wgmma.mma_async.sync.aligned.m64n128k16.f32.bf16.bf16 {" R32A ", " R32B "}, {%64, %65, %66, %67}, %68, p, 1, 1, %70;\n}\n"
               : F8(d, 0), F8(d, 8), F8(d, 16), F8(d, 24), F8(d, 32), F8(d, 40), F8(d, 48), F8(d, 56)
               : "r"(a0), "r"(a1), "r"(a2), "r"(a3), "l"(db), "r"(acc), "n"(TB));
}
template <int TB>
__device__ __forceinline__ void mma_n128_ss(float (&d)[64], uint64_t da, uint64_t db, int acc) {
  asm volatile("{\n.reg .pred p;\nsetp.ne.b32 p, %66, 0;\n"
               "wgmma.mma_async.sync.aligned.m64n128k16.f32.bf16.bf16 {" R32A ", " R32B "}, %64, %65, p, 1, 1, 0, %67;\n}\n"
               : F8(d, 0), F8(d, 8), F8(d, 16), F8(d, 24), F8(d, 32), F8(d, 40), F8(d, 48), F8(d, 56)
               : "l"(da), "l"(db), "r"(acc), "n"(TB));
}
template <int TB>
__device__ __forceinline__ void mma_n64(float (&d)[32], uint32_t a0, uint32_t a1, uint32_t a2, uint32_t a3, uint64_t db, int acc) {
  asm volatile("{\n.reg .pred p;\nsetp.ne.b32 p, %37, 0;\n"
               "wgmma.mma_async.sync.aligned.m64n64k16.f32.bf16.bf16 {" R32A "}, {%32, %33, %34, %35}, %36, p, 1, 1, %38;\n}\n"
               : F8(d, 0), F8(d, 8), F8(d, 16), F8(d, 24)
               : "r"(a0), "r"(a1), "r"(a2), "r"(a3), "l"(db), "r"(acc), "n"(TB));
}
__device__ __forceinline__ void mma_n8(float (&d)[4], uint64_t da, uint64_t db, int acc) {
  asm volatile("{\n.reg .pred p;\nsetp.ne.b32 p, %6, 0;\n"
               "wgmma.mma_async.sync.aligned.m64n8k16.f32.bf16.bf16 {%0, %1, %2, %3}, %4, %5, p, 1, 1, 1, 0;\n}\n"
               : "+f"(d[0]), "+f"(d[1]), "+f"(d[2]), "+f"(d[3])
               : "l"(da), "l"(db), "r"(acc));
}
__device__ __forceinline__ void hmma_k16(float (&d)[4], uint32_t a0, uint32_t a1, uint32_t a2, uint32_t a3, uint32_t b0, uint32_t b1) {
  asm volatile("mma.sync.aligned.m16n8k16.row.col.f32.bf16.bf16.f32 {%0, %1, %2, %3}, {%4, %5, %6, %7}, {%8, %9}, {%0, %1, %2, %3};"
               : "+f"(d[0]), "+f"(d[1]), "+f"(d[2]), "+f"(d[3]) : "r"(a0), "r"(a1), "r"(a2), "r"(a3), "r"(b0), "r"(b1));
}

__device__ __forceinline__ uint32_t pack2(float lo, float hi) {
  uint32_t r;
  asm("cvt.rn.bf16x2.f32 %0, %1, %2;" : "=r"(r) : "f"(hi), "f"(lo));
  return r;
}
__device__ __forceinline__ float bf_lo(uint32_t w) { return __uint_as_float(w << 16); }
__device__ __forceinline__ float bf_hi(uint32_t w) { return __uint_as_float(w & 0xFFFF0000u); }
__device__ __forceinline__ float bfr(float x) { return __uint_as_float(pack2(0.f, x)); }
__device__ __forceinline__ uint32_t sub2(uint32_t a, uint32_t b) {
  uint32_t r;
  asm("sub.rn.bf16x2 %0, %1, %2;" : "=r"(r) : "r"(a), "r"(b));
  return r;
}
__device__ __forceinline__ uint32_t add2(uint32_t a, uint32_t b) {
  uint32_t r;
  asm("add.rn.bf16x2 %0, %1, %2;" : "=r"(r) : "r"(a), "r"(b));
  return r;
}
__device__ __forceinline__ uint32_t mul2(uint32_t a, uint32_t b) {
  uint32_t r;
  asm("mul.rn.bf16x2 %0, %1, %2;" : "=r"(r) : "r"(a), "r"(b));
  return r;
}
__device__ __forceinline__ uint32_t fma2(uint32_t a, uint32_t b, uint32_t c) {
  uint32_t r;
  asm("fma.rn.bf16x2 %0, %1, %2, %3;" : "=r"(r) : "r"(a), "r"(b), "r"(c));
  return r;
}
__device__ __forceinline__ float ex2(float x) {
  float r;
  asm("ex2.approx.ftz.f32 %0, %1;" : "=f"(r) : "f"(x));
  return r;
}
__device__ __forceinline__ float rcp(float x) {
  float r;
  asm("rcp.approx.ftz.f32 %0, %1;" : "=f"(r) : "f"(x));
  return r;
}
__device__ __forceinline__ float silu_f(float t) { return t * rcp(1.0f + ex2(-1.4426950408889634f * t)); }
__device__ __forceinline__ void lds128(uint32_t a, uint32_t& x, uint32_t& y, uint32_t& z, uint32_t& w) {
  asm volatile("ld.shared.v4.u32 {%0, %1, %2, %3}, [%4];" : "=r"(x), "=r"(y), "=r"(z), "=r"(w) : "r"(a) : "memory");
}
__device__ __forceinline__ void ldsm4(uint32_t a, uint32_t& x, uint32_t& y, uint32_t& z, uint32_t& w) {
  asm volatile("ldmatrix.sync.aligned.m8n8.x4.shared.b16 {%0, %1, %2, %3}, [%4];" : "=r"(x), "=r"(y), "=r"(z), "=r"(w) : "r"(a) : "memory");
}
constexpr uint32_t TAG_BIT = 0x10000;
__device__ __forceinline__ void st_gran(uint4* p, uint32_t x, uint32_t y, uint32_t z, uint32_t w) {
  asm volatile("st.relaxed.gpu.global.v4.b32 [%0], {%1, %2, %3, %4};" ::"l"(p), "r"(x), "r"(y), "r"(z), "r"(w) : "memory");
}
__device__ __forceinline__ void ld_gran(const uint4* p, uint32_t& x, uint32_t& y, uint32_t& z, uint32_t& w) {
  asm volatile("ld.relaxed.gpu.global.v4.b32 {%0, %1, %2, %3}, [%4];" : "=r"(x), "=r"(y), "=r"(z), "=r"(w) : "l"(p) : "memory");
}
__device__ __forceinline__ void ldsm4t(uint32_t a, uint32_t& x, uint32_t& y, uint32_t& z, uint32_t& w) {
  asm volatile("ldmatrix.sync.aligned.m8n8.x4.trans.shared.b16 {%0, %1, %2, %3}, [%4];" : "=r"(x), "=r"(y), "=r"(z), "=r"(w) : "r"(a) : "memory");
}
__device__ __forceinline__ void stsm4t(uint32_t a, uint32_t x, uint32_t y, uint32_t z, uint32_t w) {
  asm volatile("stmatrix.sync.aligned.m8n8.x4.trans.shared.b16 [%0], {%1, %2, %3, %4};" ::"r"(a), "r"(x), "r"(y), "r"(z), "r"(w) : "memory");
}
__device__ __forceinline__ void stsm4(uint32_t a, uint32_t x, uint32_t y, uint32_t z, uint32_t w) {
  asm volatile("stmatrix.sync.aligned.m8n8.x4.shared.b16 [%0], {%1, %2, %3, %4};" ::"r"(a), "r"(x), "r"(y), "r"(z), "r"(w) : "memory");
}
template <class T>
__device__ __forceinline__ T* at(const void* base, uint32_t off) {
  uint64_t r;
  asm("{\n.reg .u32 lo, hi;\nmov.b64 {lo, hi}, %1;\nadd.cc.u32 lo, lo, %2;\naddc.u32 hi, hi, 0;\nmov.b64 %0, {lo, hi};\n}"
      : "=l"(r) : "l"(base), "r"(off));
  return (T*)__cvta_global_to_generic(r);
}
__device__ __forceinline__ void add_granules(float (&red)[32], const uint32_t (&g)[16]) {
#pragma unroll
  for (int i = 0; i < 16; i++) { red[2 * i] += bf_lo(g[i]); red[2 * i + 1] += bf_hi((i & 3) ? g[i] : g[i] & ~TAG_BIT); }
}
__device__ __forceinline__ bool granules_ok(const uint32_t (&g)[16], uint32_t tag) {
  uint32_t u, v;
  asm("lop3.b32 %0, %1, %2, %3, 0x7E;" : "=r"(u) : "r"(g[0]), "r"(g[4]), "r"(tag));
  asm("lop3.b32 %0, %1, %2, %3, 0x7E;" : "=r"(v) : "r"(g[8]), "r"(g[12]), "r"(tag));
  return __all_sync(0xffffffffu, ((u | v) & TAG_BIT) == 0);
}
__device__ __forceinline__ unsigned ld_acquire(const unsigned* p) {
  unsigned v;
  asm volatile("ld.acquire.gpu.global.u32 %0, [%1];" : "=r"(v) : "l"(p) : "memory");
  return v;
}
__device__ __forceinline__ void red_release(unsigned* p) {
  asm volatile("red.release.gpu.global.add.u32 [%0], 1;" ::"l"(p) : "memory");
}
__device__ __forceinline__ void st_release(unsigned* p, unsigned v) {
  asm volatile("st.release.gpu.global.u32 [%0], %1;" ::"l"(p), "r"(v) : "memory");
}

template <int K0, int K1>
__device__ __forceinline__ void ln_fetch(uint32_t (&xa)[144], uint32_t boxes, uint32_t lo) {
#pragma unroll
  for (int k = K0; k < K1; k++) ldsm4(((boxes + lo) ^ ((k & 3) << 5)) + (k >> 2) * 8192, xa[4 * k], xa[4 * k + 1], xa[4 * k + 2], xa[4 * k + 3]);
}
template <int K0, int K1>
__device__ __forceinline__ void ln_sums(const uint32_t (&xa)[144], float (&sm)[4][4]) {
#pragma unroll
  for (int k = K0; k < K1; k++) hmma_k16(sm[k & 3], xa[4 * k], xa[4 * k + 1], xa[4 * k + 2], xa[4 * k + 3], 0x3F803F80u, 0x3F803F80u);
}
__device__ __forceinline__ uint32_t sq8(const uint32_t* a) {
  uint32_t t, u;
  asm("mul.rn.bf16x2 %0, %1, %1;" : "=r"(t) : "r"(a[0]));
  asm("mul.rn.bf16x2 %0, %1, %1;" : "=r"(u) : "r"(a[2]));
#pragma unroll
  for (int i = 4; i < 16; i += 4) {
    asm("fma.rn.bf16x2 %0, %1, %1, %0;" : "+r"(t) : "r"(a[i]));
    asm("fma.rn.bf16x2 %0, %1, %1, %0;" : "+r"(u) : "r"(a[i + 2]));
  }
  return add2(t, u);
}
__device__ __forceinline__ void ln_centre(uint32_t (&xa)[144], int j0, int j1, uint32_t mm0, uint32_t mm1, float& sq0, float& sq1) {
#pragma unroll
  for (int j = 0; j < 72; j += 8)
    if (j >= j0 && j < j1) {
#pragma unroll
      for (int k = j; k < j + 8; k++) {
        xa[2 * k] = sub2(xa[2 * k], mm0);
        xa[2 * k + 1] = sub2(xa[2 * k + 1], mm1);
      }
      const uint32_t t0 = sq8(xa + 2 * j), t1 = sq8(xa + 2 * j + 1);
      sq0 += bf_lo(t0) + bf_hi(t0);
      sq1 += bf_lo(t1) + bf_hi(t1);
    }
}
__device__ __forceinline__ float ln_rstd(float var) {
  float sd;
  asm("sqrt.approx.ftz.f32 %0, %1;" : "=f"(sd) : "f"(bfr(bfr(fmaxf(var, 0.0f)) + 1e-5f)));
  return rcp(bfr(sd));
}
__device__ __forceinline__ uint32_t silu2(uint32_t t) { return pack2(silu_f(bf_lo(t)), silu_f(bf_hi(t))); }
__device__ __forceinline__ float sum8(float v) {
#pragma unroll
  for (int d = 4; d; d >>= 1) v += __shfl_xor_sync(0xffffffffu, v, d);
  return v;
}
__device__ __forceinline__ void await_count(const unsigned* p, unsigned target, unsigned sleep_ns) {
#pragma unroll 1
  for (int n = 0; n < (1 << 18) && __any_sync(0xffffffffu, (int)(ld_acquire(p) - target) < 0); n++) __nanosleep(sleep_ns);
}
__device__ __forceinline__ void bulk_load(uint32_t dst, const void* src, uint32_t bytes, uint32_t bar) {
  asm volatile("cp.async.bulk.shared::cluster.global.mbarrier::complete_tx::bytes [%0], [%1], %2, [%3];"
               ::"r"(dst), "l"(src), "r"(bytes), "r"(bar) : "memory");
}
__device__ __forceinline__ void proxy_fence() { asm volatile("fence.proxy.async;" ::: "memory"); }

template <int V> struct IC { static constexpr int value = V; };

struct Ctx {
  uint32_t sb;
  uint8_t* sp;
  uint32_t rank;
  Scratch* gs;
};

__device__ __forceinline__ void dly(const Ctx&, int) {}
template <int BOXES>
__device__ __forceinline__ void load_stage(uint32_t dst, const CUtensorMap* tm, int c0, int c1, uint32_t bar, uint32_t bytes, uint64_t pol) {
  asm volatile("{\n.reg .pred p;\nelect.sync _|p, 0xffffffff;\n"
               "@p mbarrier.arrive.expect_tx.shared::cta.b64 _, [%4], %7;\n"
               "@p cp.async.bulk.tensor.2d.shared::cluster.global.mbarrier::complete_tx::bytes.multicast::cluster.L2::cache_hint"
               " [%0], [%1, {%2, %3}], [%4], %5, %6;\n}"
               ::"r"(dst), "l"(tm), "r"(c0), "r"(c1), "r"(bar), "h"((uint16_t)3), "l"(pol), "r"(bytes) : "memory");
  if (BOXES == 2)
    asm volatile("{\n.reg .pred p;\nelect.sync _|p, 0xffffffff;\n"
                 "@p cp.async.bulk.tensor.2d.shared::cluster.global.mbarrier::complete_tx::bytes.multicast::cluster.L2::cache_hint"
                 " [%0], [%1, {%2, %3}], [%4], %5, %6;\n}"
                 ::"r"(dst + 8192), "l"(tm), "r"(c0), "r"(c1 + 64), "r"(bar), "h"((uint16_t)3), "l"(pol) : "memory");
}
__device__ __forceinline__ void attn_producer(const Ctx& cx, int qb, int hs, const CUtensorMap* tmX, const CUtensorMap* tmK,
                                              const CUtensorMap* tmV, const CUtensorMap* tmWq, const CUtensorMap* tmWo) {
  const uint32_t full = cx.sb + SM_FULL, empty = cx.sb + SM_EMPTY, ring = cx.sb + SM_RING + cx.rank * 16384;
  const uint64_t keep = policy_evict_normal(), last_use = policy_evict_first();
  auto acquire = [&](int st) {
    mbar_wait(empty + 8 * (st & 3), ((st >> 2) ^ ((st & 3) >> 1) ^ 1) & 1);
    if (st > 3) dly(cx, st);
  };
  if (elect_one()) {
#pragma unroll
    for (int j = 0; j < 3; j++) {
      mbar_expect_tx(cx.sb + SM_XFULL + 96 + 8 * j, 24576);
      tma3d(cx.sb + SM_X + 73728 + j * 24576, tmX, qb * 128 + 64, j * 3, cx.sb + SM_XFULL + 96 + 8 * j);
    }
  }
  __syncwarp();
  const int c0 = cx.rank * 64;
#pragma unroll 1
  for (int p = 0; p < 3; p++) {
    const int n0 = (hs * 4 + ((0x120 >> (4 * p)) & 3)) * DH + c0;
#pragma unroll
    for (int i = 0; i < 5; i++) {
      const int st = (p == 2 ? 13 : 5 * p) + i, sl = st & 3;
      if (i == 4 && p == 2) break;
      if (st == 1) mbar_wait(cx.sb + SM_XFULL + 16, 0);
      acquire(st);
      if (i == 2) load_stage<1>(ring + sl * STAGE, tmWq, n0, 256, full + 8 * sl, 16384, last_use);
      else load_stage<2>(ring + sl * STAGE, tmWq, n0, i < 2 ? 128 * i : 128 * i - 64, full + 8 * sl, 32768, last_use);
      if (i == 3 && p < 2 && elect_one()) {
        tma2d_prefetch(tmWq, (hs * 4 + 2 - p) * DH + (qb & 1) * 64, (qb >> 1) * 64);
        if (p == 0 && qb < 9) tma2d_prefetch(tmWq, (hs * 4 + 3) * DH, qb * 64);
      }
      __syncwarp();
    }
    if (p == 1) {
      const int n3 = (hs * 4 + 3) * DH;
      acquire(10);
      load_stage<2>(ring + 2 * STAGE, tmWq, n3, 2 * c0, full + 16, 32768, last_use);
      acquire(11);
      if (cx.rank) load_stage<1>(ring + 3 * STAGE, tmWq, n3, 384, full + 24, 24576, last_use);
      else load_stage<2>(ring + 3 * STAGE, tmWq, n3, 256, full + 24, 24576, last_use);
      acquire(12);
      load_stage<1>(ring, tmWq, n3, 448 + c0, full, 16384, last_use);
    }
  }
  int vrow = 0;
  uint64_t vpol = keep;
#pragma unroll 1
  for (int j = 0; j < 32; j++) {
    const int st = NST_Q - 1 + 4 * j, row = (hs * 2 + (j >> 4)) * SEQ + (j & 7) * 256;
    const uint64_t pol = (j & 8) ? last_use : keep;
    if (j < 7 && qb < 8 && elect_one()) tma2d_prefetch((qb & 4) ? tmV : tmK, (qb & 1) * 64, row + 256 + (qb & 2) * 64);
    __syncwarp();
    if (j == 24) mbar_wait(cx.sb + SM_BAR_Q3, 0);
    acquire(st);
    load_stage<1>(ring + SL_KE * STAGE, tmK, c0, row, full + 8 * SL_KE, 32768, pol);
    acquire(st + 1);
    if (j) load_stage<1>(ring + SL_VE * STAGE, tmV, c0, vrow, full + 8 * SL_VE, 32768, vpol);
    else load_stage<2>(ring + SL_VE * STAGE, tmWq, (hs * 4 + 1) * DH + c0, 448, full + 8 * SL_VE, 32768, last_use);
    vrow = row + 128;
    vpol = pol;
    acquire(st + 2);
    load_stage<1>(ring + SL_KO * STAGE, tmK, c0, vrow, full + 8 * SL_KO, 32768, pol);
    acquire(st + 3);
    load_stage<1>(ring + SL_VO * STAGE, tmV, c0, row, full + 8 * SL_VO, 32768, pol);
  }
  acquire(NST_Q + NST_KV - 1);
  load_stage<1>(ring + SL_KE * STAGE, tmV, c0, vrow, full + 8 * SL_KE, 32768, last_use);
#pragma unroll 1
  for (int u = 0; u < NST_O; u++) {
    const int st = NST_Q + NST_KV + u, sl = st & 3;
    const int blk = u < 4 && cx.rank ? 8 : ((hs + max(u >> 1, 1)) & 7);
    const int head = u < 4 ? u ^ (u >> 1) : ((u & 1) * 2 + cx.rank + 3) & 3;
    acquire(st);
    load_stage<1>(ring + sl * STAGE, tmWo, blk * 64, hs * 512 + head * 128, full + 8 * sl, 32768, last_use);
  }
}

__device__ __forceinline__ uint32_t xn_offset(uint32_t row, int lane) {
  return (row >> 6) * (9 * 8192) + (row & 63) * 128 + ((((lane >> 2) ^ row) & 7) << 4) + (lane & 3) * 4;
}

__device__ __forceinline__ void attn_rows(const Ctx& cx, int qb, int hs, int hw, int lane, const CUtensorMap* tmX16,
                                          const __nv_bfloat16* w_r) {
  extern __shared__ __align__(1024) uint8_t smem_rows[];
  auto box = [&](int blk) { return blk < 8 ? SM_SLOT + 2 * STAGE + 8192 + (blk >> 2) * 16384 + (blk & 3) * 2048 : SM_BOX8; };
  const uint32_t sb = smem_u32(smem_rows);
  if (hw == 0) {
    bar_sync(BAR_HELPER, 160);
    if (elect_one()) {
      mbar_expect_tx(sb + SM_BAR_ROWS, 9 * 2048);
#pragma unroll
      for (int i = 0; i < 9; i++) tma2d(sb + box(i), tmX16, i * 64, qb * 128 + hs * 16, sb + SM_BAR_ROWS);
    }
    __syncwarp();
  }
  uint32_t g = (lane >> 3) * 128 + (((lane ^ (lane >> 3)) & 7) << 4);
  auto next = [&]() {
    g = ((g + 512) & 2047) ^ 64;
    asm volatile("" : "+r"(g));
  };
  float* const part = (float*)(smem_rows + SM_ROWS);
  mbar_wait(sb + SM_BAR_ROWS, 0);
  if (hw == 0) dly(cx, 190);
#pragma unroll 1
  for (int i = 0; i < 4; i++) {
    float a = 0.f, b = 0.f;
#pragma unroll
    for (int j = 0; j < 3; j++) {
      const uint4 v = *(const uint4*)(smem_rows + box(hw * 3 + j) + g);
      const uint32_t w[4] = {v.x, v.y, v.z, v.w};
#pragma unroll
      for (int k = 0; k < 4; k++) {
        a += bf_lo(w[k]) + bf_hi(w[k]);
        b = fmaf(bf_lo(w[k]), bf_lo(w[k]), fmaf(bf_hi(w[k]), bf_hi(w[k]), b));
      }
    }
    a = sum8(a);
    b = sum8(b);
    float* p = part + hw * 16 + (g >> 7);
    p[0] = a;
    p[48] = b;
    next();
  }
  bar_sync(BAR_ROWS, 96);
  if (hw == 0) dly(cx, 191);
  {
    const float* p = part + (lane & 15);
    const float mean = (p[0] + p[16] + p[32]) * (1.0f / DM), rstd = ln_rstd((p[48] + p[64] + p[80]) * (1.0f / DM) - mean * mean);
    const uint32_t mm = pack2(mean, mean), rr = pack2(rstd - bfr(rstd), rstd);
#pragma unroll 1
    for (int u = hw * 12; u < hw * 12 + 12; u++) {
      const int blk = u >> 2;
      uint4* q = (uint4*)(smem_rows + box(blk) + g);
      uint4 v = *q;
      const uint32_t m = __shfl_sync(0xffffffffu, mm, g >> 7), r = __shfl_sync(0xffffffffu, rr, g >> 7);
      const uint32_t hi = __byte_perm(r, 0, 0x3232), lo = __byte_perm(r, 0, 0x1010);
      auto norm = [&](uint32_t w) {
        const uint32_t xc = sub2(w, m);
        return fma2(xc, hi, mul2(xc, lo));
      };
      v = make_uint4(norm(v.x), norm(v.y), norm(v.z), norm(v.w));
      *q = v;
      *at<uint4>(cx.gs->xn + ((qb * 2 + (hs >> 2)) * 9 + blk) * 512 + (hs & 3) * 128, g) = v;
      next();
    }
  }
  bar_sync(BAR_ROWS, 96);
  if (hw == 0) {
    dly(cx, 192);
    if (lane == 0) red_release(&cx.gs->rows[qb * 32]);
    dly(cx, 193);
  }
#pragma unroll 1
  for (int u = hw ? 13 * hw - 3 : 0; u < 13 * hw + 10; u++) {
    const int blk = u >> 2;
    const uint32_t o = (g + (u & 3) * 512) ^ ((u & 1) << 6);
    const uint4 v = *(const uint4*)(smem_rows + box(blk) + o);
    *at<uint4>(cx.gs->gate + (blk < 8 ? (qb * 8 + blk) * 144 + hs * 16 : (qb * 8 + hs) * 144 + 128) * 8, o) =
        make_uint4(silu2(v.x), silu2(v.y), silu2(v.z), silu2(v.w));
  }
  if (hw) dly(cx, 194 + hw);
  __nanosleep(5000);
#pragma unroll 1
  for (int blk = hw * 3; blk < hw * 3 + 3; blk++) {
    const uint4 c = __ldg(at<const uint4>(w_r, blk * 128 + ((g ^ (g >> 3)) & 0x70)));
#pragma unroll 1
    for (int i = 0; i < 4; i++) {
      const uint4 v = *(const uint4*)(smem_rows + box(blk) + g);
      part[blk * 16 + (g >> 7)] =
          sum8(fmaf(bf_lo(v.x), bf_lo(c.x), fmaf(bf_hi(v.x), bf_hi(c.x), fmaf(bf_lo(v.y), bf_lo(c.y), bf_hi(v.y) * bf_hi(c.y)))) +
               fmaf(bf_lo(v.z), bf_lo(c.z), fmaf(bf_hi(v.z), bf_hi(c.z), fmaf(bf_lo(v.w), bf_lo(c.w), bf_hi(v.w) * bf_hi(c.w)))));
      next();
    }
  }
  bar_sync(BAR_ROWS, 96);
  if (hw == 0) {
    dly(cx, 194);
    float d = 0.f;
#pragma unroll
    for (int j = 0; j < 9; j++) d += part[j * 16 + (lane & 15)];
    const uint32_t row = qb * 128 + hs * 16 + (lane & 15), b = pack2(0.f, d);
    *at<uint32_t>(cx.gs->key, row * 4) = (b ^ ((int)b < 0 ? 0xFFFF0000u : 0x80000000u)) + 0xFFFF - row;
    __syncwarp();
    if (lane == 0) red_release(&cx.gs->rows[qb * 32 + 1]);
  }
}

constexpr uint32_t SM_XO = SM_SLOT, SM_GO = SM_SLOT + STAGE, SM_P8 = SM_SLOT + 2 * STAGE;
__device__ __forceinline__ void attn_helper(const Ctx& cx, int qb, int hs, int lane, const __nv_bfloat16* wo, const CUtensorMap* tmX16) {
  unsigned e = 0;
  if (lane == 0) {
    e = cx.gs->launch[blockIdx.x];
    cx.gs->launch[blockIdx.x] = e + 1;
  }
  e = __shfl_sync(0xffffffffu, e, 0);
  if (lane == 0) {
    *(uint32_t*)(cx.sp + SM_TAG) = (~e & 1) * TAG_BIT;
    mbar_arrive(cx.sb + SM_BAR_MISC);
  }
  bar_sync(BAR_HELPER, 64);
  await_count(&cx.gs->rows[qb * 32 + 1], 8 * (e + 1), 1000);
  await_count(&cx.gs->q3_flag[qb * 8 + hs], e + 1, 1000);
  proxy_fence();
  if (elect_one()) {
    mbar_expect_tx(cx.sb + SM_BAR_Q3, 16384);
#pragma unroll
    for (int i = 0; i < 2; i++) bulk_load(cx.sb + SM_SLOT + 2 * STAGE + i * 16384 + 8192, cx.gs->q3 + (qb * 16 + hs * 2 + i) * 512, 8192, cx.sb + SM_BAR_Q3);
  }
  __syncwarp();
  bar_sync(BAR_HELPER, 64);
  prefetch_l2(at<const void>(wo, (hs * 512 + qb * 32 + lane) * (DM * 2)), DM * 2);
  await_count(&cx.gs->ycnt, 4 * (e + 1), 500);
  const uint32_t mykey = __ldcg(at<const uint32_t>(cx.gs->top, (lane >> 1) * 4)), myrow = 0xFFFF - (mykey & 0xFFFF);
#pragma unroll 1
  for (uint32_t todo = __ballot_sync(0xffffffffu, lane < 16 && ((lane & 1) ? myrow >> 4 == qb * 8 + hs : myrow >> 7 == qb)); todo; todo &= todo - 1) {
    const int i = __ffs(todo) - 1, blk = (i & 1) ? 8 : hs;
    const uint32_t key = __shfl_sync(0xffffffffu, mykey, i), row = 0xFFFF - (key & 0xFFFF), o = xn_offset(row, lane);
    const uint32_t t = __ldcg(at<const uint32_t>(cx.gs->xn, o + blk * 8192));
    const float2* p = at<const float2>(cx.gs->ypart, ((i >> 1) * DM + blk * 64 + 2 * lane) * 4);
    const float2 y0 = __ldcg(p), y1 = __ldcg(p + TOPC * DM / 2), y2 = __ldcg(p + TOPC * DM), y3 = __ldcg(p + 3 * TOPC * DM / 2);
    const float rs = bfr(rcp(1.0f + ex2(-1.4426950408889634f * bf_hi(key ^ ((int)key < 0 ? 0x80000000u : 0xFFFF0000u)))));
    const uint32_t y = pack2((y0.x + y1.x) + (y2.x + y3.x), (y0.y + y1.y) + (y2.y + y3.y));
    const uint32_t u = pack2(bf_lo(y) * rs, bf_hi(y) * rs);
    *at<uint32_t>(cx.gs->gate, ((qb * 8 + hs) * 144 + ((i & 1) ? 128 + (row & 15) : row & 127)) * 128 + (o & 127)) = silu2(add2(t, u));
  }
  proxy_fence();
  bar_sync(BAR_OA, 352);
  if (elect_one()) {
    const uint32_t bar = cx.sb + SM_BAR_XG;
    mbar_expect_tx(bar, 2 * 144 * 128);
    bulk_load(cx.sb + SM_GO, cx.gs->gate + (qb * 8 + hs) * (144 * 8), 144 * 128, bar);
#pragma unroll 1
    for (int i = 0; i < 9; i++) tma2d_stream(cx.sb + SM_XO + i * 2048, tmX16, i < 8 ? hs * 64 : 512, qb * 128 + (i < 8 ? i : hs) * 16, bar);
  }
  __syncwarp();
  const uint4* src = cx.gs->part + (qb * 64 + 56 + hs) * 1024;
#pragma unroll 1
  for (int n = 0; n < (1 << 16); n++) {
    __nanosleep(n ? 400 : 700);
    uint32_t a, b, d, t;
    ld_gran(at<const uint4>(src, (lane & 7) * 2048 + 2032), a, b, d, t);
    if (__all_sync(0xffffffffu, ((a >> 16) ^ e) & 1)) break;
  }
  if (elect_one()) {
    mbar_expect_tx(cx.sb + SM_BAR_P8, 16384);
    bulk_load(cx.sb + SM_P8, src, 16384, cx.sb + SM_BAR_P8);
  }
  __syncwarp();
}
__device__ __forceinline__ void attn_finish8(const Ctx& cx, int qb, int hs, int hw, int lane, __nv_bfloat16* out) {
  const uint32_t tag = *(const uint32_t*)(cx.sp + SM_TAG);
  mbar_wait(cx.sb + SM_BAR_P8, 0);
  mbar_wait(cx.sb + SM_BAR_XG, 0);
#pragma unroll 1
  for (int g = 2 - hw; g < 4; g += 3) {
    float acc[8] = {0.f, 0.f, 0.f, 0.f, 0.f, 0.f, 0.f, 0.f};
    uint32_t a[4];
#pragma unroll 1
    for (uint32_t o = g * 512 + lane * 16; o < 16384; o += 2048) {
      lds128(cx.sb + SM_P8 + o, a[0], a[1], a[2], a[3]);
#pragma unroll 1
      for (int n = 0; n < (1 << 16) && __any_sync(0xffffffffu, (a[0] & TAG_BIT) != tag); n++)
        ld_gran(at<const uint4>(cx.gs->part, (qb * 64 + 56 + hs) * 16384 + o), a[0], a[1], a[2], a[3]);
      a[0] &= ~TAG_BIT;
#pragma unroll
      for (int j = 0; j < 4; j++) { acc[2 * j] += bf_lo(a[j]); acc[2 * j + 1] += bf_hi(a[j]); }
    }
    asm volatile("" : "+r"(lane));
    const uint32_t tile = cx.sb + SM_XO + (128 + (lane & 15)) * 128 + (((lane >> 4) ^ (lane & 7)) << 4);
    uint32_t b[4];
    ldsm4((tile ^ (g << 5)) + STAGE, a[0], a[1], a[2], a[3]);
    ldsm4(tile ^ (g << 5), b[0], b[1], b[2], b[3]);
    stsm4(tile ^ (g << 5), fma2(pack2(acc[0], acc[1]), a[0], b[0]), fma2(pack2(acc[2], acc[3]), a[1], b[1]),
          fma2(pack2(acc[4], acc[5]), a[2], b[2]), fma2(pack2(acc[6], acc[7]), a[3], b[3]));
  }
  bar_sync(BAR_ROWS, 96);
#pragma unroll 1
  for (int ch = threadIdx.x - 32; ch < 128; ch += 96)
    *at<uint4>(out, ((qb * 128 + hs * 16 + (ch >> 3)) * DM + 512 + (ch & 7) * 8) * 2) =
        *(const uint4*)(cx.sp + SM_XO + (128 + (ch >> 3)) * 128 + (((ch ^ (ch >> 3)) & 7) << 4));
}

constexpr float SUM_HI = 1.8446744e19f, SUM_LO = 9.0949470e-13f;

__device__ __forceinline__ void softmax_shift(float (&s)[64], float n0, float n1) {
#pragma unroll
  for (int i = 0; i < 64; i++) s[i] += (i & 2) ? n1 : n0;
}
template <int LO, int HI>
__device__ __forceinline__ void softmax_exp(float (&s)[64]) {
#pragma unroll
  for (int i = LO; i < HI; i++) s[i] = ex2(s[i]);
}
__device__ __forceinline__ void row_sums(const uint32_t (&pf)[32], float& l0, float& l1) {
  uint32_t t[16];
#pragma unroll
  for (int i = 0; i < 16; i++) t[i] = add2(pf[(i >> 1) * 4 + (i & 1)], pf[(i >> 1) * 4 + 2 + (i & 1)]);
#pragma unroll
  for (int i = 0; i < 8; i++) t[i] = add2(t[(i >> 1) * 4 + (i & 1)], t[(i >> 1) * 4 + 2 + (i & 1)]);
#pragma unroll
  for (int i = 0; i < 4; i++) t[i] = add2(t[(i >> 1) * 4 + (i & 1)], t[(i >> 1) * 4 + 2 + (i & 1)]);
  l0 += (bf_lo(t[0]) + bf_lo(t[2])) + (bf_hi(t[0]) + bf_hi(t[2]));
  l1 += (bf_lo(t[1]) + bf_lo(t[3])) + (bf_hi(t[1]) + bf_hi(t[3]));
}
__device__ __forceinline__ void softmax_redo(uint32_t (&pf)[32], const uint32_t (&q)[32], const __nv_bfloat16* kblk, int lane, float& n0,
                                             float& n1, float& l0, float& l1, float& sc0, float& sc1) {
  float x0 = -n0, x1 = -n1;
#pragma unroll 1
  for (int u = 0; u < 16; u++) {
    const uint32_t* kp = (const uint32_t*)(kblk + ((u & 7) * 16 + (lane >> 2)) * DH) + (lane & 3);
    float d[2][4] = {};
#pragma unroll
    for (int k = 0; k < 16; k++)
      hmma_k16(d[k & 1], q[2 * (k & 14)], q[2 * (k & 14) + 1], q[2 * (k & 14) + 2], q[2 * (k & 14) + 3],
               kp[(k & 1) * 4 * DH + (k >> 1) * 8], kp[(k & 1) * 4 * DH + (k >> 1) * 8 + 4]);
    if (u < 8) {
      x0 = fmaxf(fmaxf(x0, fmaxf(d[0][0], d[0][1])), fmaxf(d[1][0], d[1][1]));
      x1 = fmaxf(fmaxf(x1, fmaxf(d[0][2], d[0][3])), fmaxf(d[1][2], d[1][3]));
      if (u == 7) {
#pragma unroll
        for (int m = 1; m < 4; m <<= 1) {
          x0 = fmaxf(x0, __shfl_xor_sync(0xffffffffu, x0, m));
          x1 = fmaxf(x1, __shfl_xor_sync(0xffffffffu, x1, m));
        }
        sc0 = ex2(-x0 - n0);
        sc1 = ex2(-x1 - n1);
        n0 = -x0;
        n1 = -x1;
        l0 *= sc0;
        l1 *= sc1;
      }
    } else {
#pragma unroll
      for (int i = 0; i < 28; i++) pf[i] = pf[i + 4];
#pragma unroll
      for (int i = 0; i < 4; i++) {
        const float n = (i & 1) ? n1 : n0;
        pf[28 + i] = pack2(ex2(d[i >> 1][(i & 1) * 2] + n), ex2(d[i >> 1][(i & 1) * 2 + 1] + n));
        ((i & 1) ? l1 : l0) += bf_lo(pf[28 + i]) + bf_hi(pf[28 + i]);
      }
    }
  }
}

__device__ __forceinline__ void attn_consumer(const Ctx& cx, int qb, int hs, int wg, int cw, int lane, const __nv_bfloat16* x,
                                              const __nv_bfloat16* kc, __nv_bfloat16* out) {
  const uint32_t full = cx.sb + SM_FULL;
  const uint32_t ring = cx.sb + SM_RING;
  uint32_t lo = ((cw & 3) * 16 + (lane & 15)) * 128 + (((lane >> 4) ^ (lane & 7)) << 4);
  const uint32_t slot = cx.sb + SM_SLOT + wg * 16384;
  auto frag = [&](int sl, int k) { return ((slot + sl * STAGE + lo) ^ ((k & 3) << 5)) + (k >> 2) * 8192; };
  auto park = [&](const float (&a)[64], int sl, int k0, int k1, float f0, float f1) {
#pragma unroll
    for (int k = 0; k < 8; k++)
      if (k >= k0 && k < k1)
        stsm4(frag(sl, k), pack2(a[8 * k] * f0, a[8 * k + 1] * f0), pack2(a[8 * k + 2] * f1, a[8 * k + 3] * f1),
              pack2(a[8 * k + 4] * f0, a[8 * k + 5] * f0), pack2(a[8 * k + 6] * f1, a[8 * k + 7] * f1));
  };
  const bool signaller = lane == 0 && (cw & 3) < 2;
  int my_turn = 1 + wg, other_turn = 2 - wg;

  uint32_t pf[32], q[32], empty_c;
  float o[64], l0, l1;
  {
    uint32_t xa[144];
    float rstd0, rstd1;
    {
      const uint32_t xb = cx.sb + SM_X + wg * 73728, xf = cx.sb + SM_XFULL + wg * 96;
      float sm[4][4] = {};
      prof(wg, 0);
      empty_c = mapa(cx.sb + SM_EMPTY, cw & 1);
      mbar_wait(xf, 0);
      if ((threadIdx.x & 127) == 0) profc(wg, 30);
      ln_fetch<0, 12>(xa, xb, lo);
      mbar_wait(xf + 8, 0);
      ln_fetch<12, 24>(xa, xb, lo);
      ln_sums<0, 12>(xa, sm);
      mbar_wait(xf + 16, 0);
      if ((threadIdx.x & 127) == 0) profc(wg, 1);
      ln_fetch<24, 36>(xa, xb, lo);
      ln_sums<12, 36>(xa, sm);
      rstd0 = ((sm[0][0] + sm[1][0]) + (sm[2][0] + sm[3][0])) * (1.0f / DM);
      rstd1 = ((sm[0][2] + sm[1][2]) + (sm[2][2] + sm[3][2])) * (1.0f / DM);
    }
    asm volatile("" : "+f"(rstd0), "+f"(rstd1)::"memory");
    block_fence(38);
    if (wg) bar_arrive(other_turn, 256);
    block_fence(39);
    const uint32_t mm0 = pack2(rstd0, rstd0), mm1 = pack2(rstd1, rstd1);
    rstd0 -= bf_lo(mm0);
    rstd1 -= bf_lo(mm1);
    rstd0 *= rstd0 * (-0.25f * DM);
    rstd1 *= rstd1 * (-0.25f * DM);
    auto ln_finish = [&]() {
      rstd0 += __shfl_xor_sync(0xffffffffu, rstd0, 1); rstd1 += __shfl_xor_sync(0xffffffffu, rstd1, 1);
      rstd0 += __shfl_xor_sync(0xffffffffu, rstd0, 2); rstd1 += __shfl_xor_sync(0xffffffffu, rstd1, 2);
      rstd0 = ln_rstd(rstd0 * (1.0f / DM)) * SM_SCALE_LOG2;
      rstd1 = ln_rstd(rstd1 * (1.0f / DM)) * SM_SCALE_LOG2;
    };
    ln_centre(xa, 0, X_C0, mm0, mm1, rstd0, rstd1);
    if (wg == 0) {
      bar_sync(4, 128);
      if (signaller) {
        asm volatile("mbarrier.arrive.shared::cluster.b64 _, [%0], 2;" ::"r"(empty_c + 16) : "memory");
        asm volatile("mbarrier.arrive.shared::cluster.b64 _, [%0], 2;" ::"r"(empty_c + 24) : "memory");
      }
      block_fence(37);
      pin(xa);
      ln_centre(xa, X_C0, X_C1, mm0, mm1, rstd0, rstd1);
    }
    pin(xa);
    if ((threadIdx.x & 127) == 0) profc(wg, 2);

    extern __shared__ __align__(1024) uint8_t smem_q[];
    const uint32_t ring = smem_u32(smem_q) + SM_RING;
    auto release = [&](int st) { if (signaller) mbar_arrive_cluster(empty_c + 8 * (st & 3)); };
    auto q_stage = [&](float (&acc)[64], int st, int i, int last) {
      mbar_wait(full + 8 * (st & 3), (st >> 2) & 1);
      if (i != (wg ? last : 1)) bar_sync(my_turn, 256);
      wg_fence();
      const uint64_t db = mkdesc(ring + (st & 3) * STAGE, 16384);
#pragma unroll
      for (int k = 0; k < 8; k++) {
        const int kb = (i < 3 ? 8 * i : 8 * i - 4) + k;
        if (i != 2 || k < 4) mma_n128<1>(acc, xa[4 * kb], xa[4 * kb + 1], xa[4 * kb + 2], xa[4 * kb + 3], db + k * 128, kb > 0);
      }
      wg_commit();
      if (i != (wg ? last - 1 : 0)) bar_arrive(other_turn, 256);
    };
    auto q_release = [&](int st, int i, int last) {
      if (i == 1 || i == last) {
        wg_wait<1>();
        if (i == last || !wg) release(st - 1);
      }
      if (i != last - 1 && (i || wg)) {
        wg_wait<0>();
        release(st);
      }
    };
    {
      float (&acc)[64] = o;
#pragma unroll 1
      for (int p = 0; p < 2; p++) {
#pragma unroll
        for (int i = 0; i < 5; i++) {
          q_stage(acc, 5 * p + i, i, 4);
          if (p == 0 && i != 3) {
            if (i == 0 && wg) bar_arrive(BAR_HELPER, 160);
            if ((wg || i) && i < 3) ln_centre(xa, i == 0 ? X_C0 : i == 1 ? X_C1 : X_C2, i == 0 ? X_C1 : i == 1 ? X_C2 : 72, mm0, mm1, rstd0, rstd1);
            if (i == 4) ln_finish();
            pin(xa);
          }
          q_release(5 * p + i, i, 4);
        }
        pin(acc);
#pragma unroll
        for (int k = 0; k < 8; k += 2) {
          park(acc, p, k, k + 2, rstd0, rstd1);
          if (k < 6) block_fence(40 + k);
        }
      }
    }
    {
      float (&h)[32] = *(float (*)[32])&o[0];
#pragma unroll
      for (int i = 0; i < 3; i++) {
        const uint32_t sl = (10 + i) & 3;
        mbar_wait(full + 8 * sl, ((10 + i) >> 2) & 1);
        if (i != (wg ? 2 : 1)) bar_sync(my_turn, 256);
        wg_fence();
#pragma unroll
        for (int k = 0; k < 16 - 4 * i; k++) {
          const int kb = (i == 2 ? 28 : 16 * i) + k;
          const uint64_t db = mkdesc(ring + sl * STAGE, 16) + (i == 2 && k >= 4 ? k + 4 : k) * 128;
          mma_n64<1>(h, xa[4 * kb], xa[4 * kb + 1], xa[4 * kb + 2], xa[4 * kb + 3], db, kb > 0);
        }
        wg_commit();
        if (i != (wg ? 1 : 0)) bar_arrive(other_turn, 256);
        q_release(10 + i, i, 2);
      }
      pin(h);
      park(o, 2, 0, 2, rstd0, rstd1);
      block_fence(49);
      park(o, 2, 2, 4, rstd0, rstd1);
    }
#pragma unroll
    for (int i = 0; i < 4; i++) {
      q_stage(o, 13 + i, i, 3);
      q_release(13 + i, i, 3);
    }
    prof(wg, 6);
#pragma unroll
    for (int i = 0; i < 32; i++) pf[i] = xa[112 + i];
    l0 = 0.25f * rcp(rstd0);
    l1 = 0.25f * rcp(rstd1);
  }

  uint32_t oa[96];
  const uint32_t zero = __shfl_sync(0xffffffffu, blockIdx.y, lane);
  my_turn = __shfl_sync(0xffffffffu, my_turn, lane);
  other_turn = __shfl_sync(0xffffffffu, other_turn, lane);
  lo = __shfl_sync(0xffffffffu, lo, lane);
  {
    float s[64], n0 = 0.f, n1 = 0.f;
    float lp0, lp1;
    float i0 = 0.f, i1 = 0.f;
    bool redo, shift = false;
    auto turn = [&](int it, auto kc_) -> bool {
      constexpr int KIND = decltype(kc_)::value;
      constexpr uint32_t slk = KIND == 1 ? SL_KO : SL_KE, slv = KIND == 1 ? SL_VO : SL_VE, slkn = KIND == 1 ? SL_KE : SL_KO;
      constexpr int SPLIT = KIND == 3 ? X_SPLIT3 : X_SPLIT, PARK1 = X_PARK;
      const uint32_t par = ((it + NST_Q / 2) >> 1) & 1;
      const int hsl = max((it >> 4) - 1, 0);
      const uint64_t dk = mkdesc(ring + slk * STAGE, 16), dv = mkdesc(ring + slv * STAGE, 16384);
      auto qk = [&]() {
#pragma unroll
        for (int k = 0; k < 8; k++) {
          if (KIND == 3) mma_n128_ss<0>(s, mkdesc(slot + hsl * STAGE, 16) + (k >> 2) * 512 + (k & 3) * 2, dk + (k >> 2) * 1024 + (k & 3) * 2, k > 0);
          else mma_n128<0>(s, q[4 * k], q[4 * k + 1], q[4 * k + 2], q[4 * k + 3], dk + (k >> 2) * 1024 + (k & 3) * 2, k > 0);
        }
        wg_commit();
      };
      auto pv = [&]() {
#pragma unroll
        for (int k = 0; k < 8; k++)
          mma_n128<1>(o, pf[4 * k], pf[4 * k + 1], pf[4 * k + 2], pf[4 * k + 3], dv + k * 128, k > 0 || KIND != 1 || (it & 15) != 1);
        wg_commit();
      };
      lp0 = l0; lp1 = l1;
#define TS(i)
      {
        TS(0)
        if (KIND == 3) {
          asm volatile("fence.proxy.async.shared::cta;" ::: "memory");
          const float t0 = lp0 + __shfl_xor_sync(0xffffffffu, lp0, 1), t1 = lp1 + __shfl_xor_sync(0xffffffffu, lp1, 1);
          i0 = rcp(t0 + __shfl_xor_sync(0xffffffffu, t0, 2));
          i1 = rcp(t1 + __shfl_xor_sync(0xffffffffu, t1, 2));
          asm volatile("" : "+f"(i0), "+f"(i1)::"memory");
          block_fence(31, zero);
#pragma unroll
          for (int k = 0; k < X_N1; k++) ldsm4(frag(hsl, k), q[4 * k], q[4 * k + 1], q[4 * k + 2], q[4 * k + 3]);
        }
        bar_sync(my_turn, 256);
        TS(1)
        if (KIND != 3) pin(q);
        pin(pf); pin(o);
        wg_fence();
        qk();
        TS(2)
        mbar_wait(full + 8 * slv, par);
        if (KIND == 1 && (it & 15) == 1) {
          park(o, hsl, PARK1, 8, i0, i1);
          wg_fence();
        }
        if (KIND == 3) {
#pragma unroll
          for (int k = X_N1; k < 8; k++) ldsm4(frag(hsl, k), q[4 * k], q[4 * k + 1], q[4 * k + 2], q[4 * k + 3]);
          block_fence(32, zero);
        }
        TS(3)
        pv();
        bar_arrive(other_turn, 256);
        TS(4)
        wg_wait<1>();
      }
      pin(s);
      mbar_arrive_cluster_now<10 * KIND + 3>(empty_c + 8 * slk, signaller, zero);
      TS(5)
      if (KIND == 3) {
        shift = false;
        n0 = n1 = l0 = l1 = 0.f;
      } else if (shift) {
        softmax_shift(s, n0, n1);
        pin(s);
      }
      softmax_exp<0, SPLIT>(s);
      pin(s);
      block_fence(10 * KIND + 4, zero);
      TS(6)
      wg_wait<0>();
      pin(o); pin(pf);
      mbar_arrive_cluster_now<10 * KIND + 5>(empty_c + 8 * slv, signaller, zero);
      TS(7)
      const bool kready = mbar_test(full + 8 * slkn, par);
      softmax_exp<SPLIT, 64>(s);
#pragma unroll
      for (int i = 0; i < 32; i++) pf[i] = pack2(s[2 * i], s[2 * i + 1]);
      row_sums(pf, l0, l1);
      if (KIND == 3) {
        park(o, hsl, 0, PARK1, i0, i1);
        if (it) prof(wg, 6 + (it >> 4));
        if (it >= 32 && cw == 0) bar_arrive(BAR_HELPER, 64);
      }
      redo = !(l0 + l1 <= SUM_HI) || (KIND == 3 && fminf(l0, l1) < SUM_LO);
      const bool leave = __any_sync(0xffffffffu, redo || !kready);
      return leave;
    };
    int it = -1;
#pragma unroll 1
    while (true) {
      mbar_wait(full + 8 * ((it & 1) ? SL_KE : SL_KO), ((it + NST_Q / 2) >> 1) & 1);
      it++;
#pragma unroll 1
      while (true) {
        if (it & 1) {
          if (turn(it, IC<1>()) || it == 63) break;
          it++;
        }
        if (it & 15) {
          if (turn(it, IC<2>())) break;
        } else {
          if (turn(it, IC<3>())) break;
        }
        it++;
      }
      if (__any_sync(0xffffffffu, redo)) {
        const int j = it & 15;
        float sc0 = 1.f, sc1 = 1.f;
        if (j == 0) n0 = n1 = 3.0e38f;
        l0 = j ? lp0 : 0.f;
        l1 = j ? lp1 : 0.f;
        softmax_redo(pf, q, kc + (size_t)((hs * 2 + (it >> 5)) * SEQ + j * 128) * DH, lane, n0, n1, l0, l1, sc0, sc1);
        shift = true;
        if (j == 0) sc0 = sc1 = 1.f;
#pragma unroll
        for (int i = 0; i < 16; i++) { o[4 * i] *= sc0; o[4 * i + 1] *= sc0; o[4 * i + 2] *= sc1; o[4 * i + 3] *= sc1; }
      }
      if (it == 63) break;
    }
  }

#define TE(i) {}
  {
    constexpr int ST0 = NST_Q + NST_KV;
    float acc[32], red[32], first[32];
    uint32_t tag;
    uint4* xch;
    auto await = [&](int st) { mbar_wait(full + 8 * (st & 3), (st >> 2) & 1); };
    auto release = [&](int st) { if (signaller) mbar_arrive_cluster(empty_c + 8 * (st & 3)); };
    auto unpark = [&](int h, int k0, int k1) {
#pragma unroll
      for (int k = 0; k < 8; k++)
        if (k >= k0 && k < k1) ldsm4(frag(h, k), oa[32 * h + 4 * k], oa[32 * h + 4 * k + 1], oa[32 * h + 4 * k + 2], oa[32 * h + 4 * k + 3]);
    };
    {
      float ar[64];
      asm volatile("fence.proxy.async.shared::cta;" ::: "memory");
      l0 += __shfl_xor_sync(0xffffffffu, l0, 1); l1 += __shfl_xor_sync(0xffffffffu, l1, 1);
      l0 += __shfl_xor_sync(0xffffffffu, l0, 2); l1 += __shfl_xor_sync(0xffffffffu, l1, 2);
      float f0 = rcp(l0), f1 = rcp(l1);
      asm volatile("" : "+f"(f0), "+f"(f1)::"memory");
      await(ST0 - 1);
      unpark(1, 0, 4);
      bar_sync(my_turn, 256);
      pin(pf); pin(o);
      wg_fence();
#pragma unroll
      for (int k = 0; k < 8; k++)
        mma_n128<1>(o, pf[4 * k], pf[4 * k + 1], pf[4 * k + 2], pf[4 * k + 3], mkdesc(ring + SL_KE * STAGE, 16384) + k * 128, 1);
      wg_commit();
      await(ST0);
      unpark(1, 4, 8);
      block_fence(61, zero);
#pragma unroll
      for (int k = 0; k < 8; k++) mma_n128_ss<1>(ar, mkdesc(slot, 16) + (k >> 2) * 512 + (k & 3) * 2, mkdesc(ring + (ST0 & 3) * STAGE, 16384) + k * 128, k > 0);
      wg_commit();
      bar_arrive(other_turn, 256);
      wg_wait<1>();
      pin(o); pin(pf);
      mbar_arrive_cluster_now<62>(empty_c + 8 * SL_KE, signaller, zero);
#pragma unroll
      for (int i = 0; i < 16; i++) {
        pf[2 * i] = pack2(o[4 * i] * f0, o[4 * i + 1] * f0);
        pf[2 * i + 1] = pack2(o[4 * i + 2] * f1, o[4 * i + 3] * f1);
      }
      pin(pf);
      prof(wg, 10);
#pragma unroll
      for (int u = 1; u < 4; u++) {
        await(ST0 + u);
        wg_wait<0>();
        release(ST0 + u - 1);
        bar_sync(my_turn, 256);
        wg_fence();
#pragma unroll
        for (int k = 0; k < 8; k++) {
          const uint32_t* a = (u == 1 ? oa + 32 : u == 2 ? pf : oa + 64) + 4 * k;
          mma_n128<1>(ar, a[0], a[1], a[2], a[3], mkdesc(ring + ((ST0 + u) & 3) * STAGE, 16384) + k * 128, 1);
        }
        wg_commit();
        bar_arrive(other_turn, 256);
        if (u < 3) {
          block_fence(62 + u, zero);
          unpark(u == 1 ? 2 : 0, 0, 8);
        }
      }
      mbar_wait(cx.sb + SM_BAR_MISC, 0);
      tag = *(const volatile uint32_t*)(cx.sp + SM_TAG);
      xch = at<uint4>(cx.gs->part, (qb << 20) + lane * 16 + zero);
      tag = __shfl_sync(0xffffffffu, tag, lane);
      await(ST0 + 4);
      wg_wait<0>();
      release(ST0 + 3);
      pin(ar);
#pragma unroll
      for (int i = 0; i < 32; i++) { first[i] = ar[i]; red[i] = ar[32 + i]; }
    }
    auto send = [&](const float (&v)[32], int dst, int idx) {
      uint4* p = at<uint4>(xch, (dst * 8 + idx) * 2048);
#pragma unroll
      for (int i = 0; i < 4; i++)
        st_gran(p + i * 32, (pack2(v[8 * i], v[8 * i + 1]) & ~TAG_BIT) | tag, pack2(v[8 * i + 2], v[8 * i + 3]),
                pack2(v[8 * i + 4], v[8 * i + 5]), pack2(v[8 * i + 6], v[8 * i + 7]));
    };
    send(first, ((hs + 1) & 7) * 7, cw);
    int nrx = 1;
    auto half_step = [&](int s, auto hc, bool arrive) {
      constexpr int h = decltype(hc)::value;
      const int st = ST0 + 2 * s + h;
      const uint64_t db = mkdesc(ring + (st & 3) * STAGE, 16);
      bar_sync(my_turn, 256);
      if (h == 0) pin(pf);
#pragma unroll
      for (int i = 32 * h; i < 32 + 64 * h; i++) asm volatile("" : "+r"(oa[i])::"memory");
      wg_fence();
#pragma unroll
      for (int k = 0; k < 16; k++) {
        const int kb = h * 16 + k - 8;
        if (kb >= 0) mma_n64<1>(acc, oa[4 * kb], oa[4 * kb + 1], oa[4 * kb + 2], oa[4 * kb + 3], db + k * 128, 1);
        else mma_n64<1>(acc, pf[4 * k], pf[4 * k + 1], pf[4 * k + 2], pf[4 * k + 3], db + k * 128, k > 0);
      }
      wg_commit();
      if (arrive) bar_arrive(other_turn, 256);
    };
    auto source = [&](int n) { return at<const uint4>(xch, ((hs * 7 + n - 1) * 8 + cw) * 2048); };
    auto fetch = [&](uint32_t (&g)[16], const uint4* p) {
#pragma unroll
      for (int i = 0; i < 4; i++) ld_gran(p + i * 32, g[4 * i], g[4 * i + 1], g[4 * i + 2], g[4 * i + 3]);
    };
    uint32_t g[16];
#pragma unroll 1
    for (int s = 2; s < 8; s++) {
      const int st = ST0 + 2 * s;
      half_step(s, IC<0>(), true);
      if (s == 2) {
        bar_arrive(BAR_OA, 352);
        send(red, 56 + cw, hs);
#pragma unroll
        for (int i = 0; i < 32; i++) red[i] = 0.f;
      }
      await(st + 1);
      if (s > 3 && granules_ok(g, tag)) { add_granules(red, g); nrx++; }
      wg_wait<0>();
      if (s < 7) release(st);
      if (s > 2) fetch(g, source(nrx));
      half_step(s, IC<1>(), true);
      await(st + 2);
      wg_wait<0>();
      if (s < 7) release(st + 1);
      pin(acc);
      if (s == 7) prof(wg, 19);
      send(acc, ((hs + s) & 7) * 7 + s - 1, cw);
    }
    TE(1)
    uint32_t xv[16], gt[16];
    {
      const int s = 8;
      uint32_t g2[16];
      half_step(s, IC<0>(), true);
      TE(2)
      await(NST_Q + NST_KV + NST_O - 1);
      cluster_arrive();
      mbar_wait(cx.sb + SM_BAR_XG, 0);
      const uint32_t tile = cx.sb + SM_XO + wg * 8192 + lo;
      if (granules_ok(g, tag)) { add_granules(red, g); nrx++; }
      fetch(g, source(nrx));
      block_fence(58, zero);
      wg_wait<0>();
      TE(3)
#pragma unroll
      for (int k = 0; k < 4; k++) ldsm4((tile ^ (k << 5)) + STAGE, gt[4 * k], gt[4 * k + 1], gt[4 * k + 2], gt[4 * k + 3]);
      half_step(s, IC<1>(), wg == 0);
      TE(4)
      block_fence(56, zero);
      const bool ok = granules_ok(g, tag);
      block_fence(57, zero + ok * 1000);
      const uint4* src = source(7);
      fetch(g2, src);
#pragma unroll
      for (int k = 0; k < 4; k++) ldsm4(tile ^ (k << 5), xv[4 * k], xv[4 * k + 1], xv[4 * k + 2], xv[4 * k + 3]);
      if (ok) { add_granules(red, g); nrx++; }
      TE(5)
      block_fence(59, zero);
      wg_wait<0>();
      pin(acc);
      TE(6)
#pragma unroll
      for (int i = 0; i < 32; i++) red[i] += acc[i];
      pin(red);
      TE(7)
      int n = 7;
#pragma unroll 1
      for (int spins = 0; spins < (1 << 16); spins++) {
        if (granules_ok(g2, tag)) {
          add_granules(red, g2);
          if (--n < nrx) {
            break;
          }
          src -= 1024;
        }
        fetch(g2, src);
      }
      TE(8)
    }
    prof(wg, 20);
    TE(9)
    const uint32_t ot = ring + ((ST0 + NST_O) & 3) * STAGE + cw * (16 * 144);
    uint32_t ow[16];
#pragma unroll
    for (int i = 0; i < 16; i++) ow[i] = fma2(pack2(red[2 * i], red[2 * i + 1]), gt[i], xv[i]);
#pragma unroll
    for (int i = 0; i < 4; i++)
      stsm4(ot + (lane & 15) * 144 + (2 * i + (lane >> 4)) * 16, ow[4 * i], ow[4 * i + 1], ow[4 * i + 2], ow[4 * i + 3]);
    __syncwarp();
#pragma unroll
    for (int i = 0; i < 4; i++) {
      uint4 v;
      lds128(ot + (i * 4 + (lane >> 3)) * 144 + (lane & 7) * 16, v.x, v.y, v.z, v.w);
      at<uint4>(out, ((qb * 128 + cw * 16 + (lane >> 3)) * DM + hs * 64 + (lane & 7) * 8) * 2)[i * (4 * DM / 8)] = v;
    }
    TE(10)
    prof(wg, 22);
  }
}

constexpr int AST_X = 6, AST_F = AST_X + 96;
__device__ __forceinline__ void aux_producer(const Ctx& cx, int f, const CUtensorMap* tmWq, const CUtensorMap* tmG) {
  const uint32_t full = cx.sb + SM_FULL, empty = cx.sb + SM_EMPTY;
  __nanosleep(3000);
  if (elect_one()) {
#pragma unroll 1
    for (int st = 0; st < AST_X; st++) {
      mbar_expect_tx(full + 8 * st, FSTAGE);
#pragma unroll
      for (int i = 0; i < 3; i++)
        tma2d_stream(cx.sb + st * FSTAGE + i * 8192, tmWq, (2 * f + (st & 1)) * 512 + 448, (st >> 1) * 192 + i * 64, full + 8 * st);
    }
  }
  __syncwarp();
  mbar_wait(cx.sb + SM_BAR_MISC, 0);
  proxy_fence();
  int st = AST_X;
#pragma unroll 1
  for (; st < AST_F; st++) {
    const uint32_t sl = st & 7;
    mbar_wait(empty + 8 * sl, ((st >> 3) & 1) ^ 1);
    if (elect_one()) {
      mbar_expect_tx(full + 8 * sl, FSTAGE);
      bulk_load(cx.sb + sl * FSTAGE, cx.gs->xn + (st - AST_X) * (FSTAGE / 16), FSTAGE, full + 8 * sl);
    }
    __syncwarp();
  }
#pragma unroll 1
  for (int pair = 0; pair < 14; pair++) {
#pragma unroll 1
    for (int u = 0; u < 12; u++, st++) {
      const uint32_t sl = st & 7;
      const int unit = pair * 2 + (u & 1), k = u >> 1;
      if (unit == 27) continue;
      const bool gu = pair < 9;
      mbar_wait(empty + 8 * sl, ((st >> 3) & 1) ^ 1);
      if (elect_one()) {
        mbar_expect_tx(full + 8 * sl, FSTAGE);
        tma2d_stream(cx.sb + sl * FSTAGE, tmG + (gu ? k >= 3 : 2), gu ? f * 1152 + unit * 64 : (unit - 18) * 64,
                     gu ? (k >= 3 ? k - 3 : k) * 192 : f * 1152 + k * 192, full + 8 * sl);
      }
      __syncwarp();
    }
  }
}

constexpr int BAR_FREE = 4, BAR_TILE = 6;
__device__ __forceinline__ void aux_helper(const Ctx& cx, int f, int warp, int lane) {
  unsigned epoch = 0;
  if (lane == 0) epoch = cx.gs->launch[blockIdx.x] + 1;
  epoch = __shfl_sync(0xffffffffu, epoch, 0);
  bar_sync(BAR_OA, 96);
  if (warp == 3) {
    if (lane == 0) cx.gs->launch[blockIdx.x] = epoch;
    await_count(at<const unsigned>(cx.gs->rows, (lane & 15) * 128), 8 * epoch, 200);
    if (lane == 0) mbar_arrive(cx.sb + SM_BAR_MISC);
    prof(0, 1, 31);
    await_count(at<const unsigned>(cx.gs->rows, (lane & 15) * 128 + 4), 8 * epoch, 500);
    uint32_t bound = 0xFFFFFFFFu, m0 = 0, m1 = 0;
#pragma unroll 1
    for (int k = 0; k < TOPC; k++) {
      if (__any_sync(0xffffffffu, m0 == 0)) {
        m0 = m1 = 0;
#pragma unroll 2
        for (int i = 0; i < 16; i++) {
          const uint4 v = __ldcg(at<const uint4>(cx.gs->key, lane * 16 + i * 512));
          const uint32_t w[4] = {v.x, v.y, v.z, v.w};
#pragma unroll
          for (int j = 0; j < 4; j++) {
            const uint32_t t = w[j] <= bound ? w[j] : 0;
            m1 = max(m1, min(m0, t));
            m0 = max(m0, t);
          }
        }
      }
      uint32_t m = m0;
      m = __reduce_max_sync(0xffffffffu, m);
      bound = m - 1;
      if (m0 == m) { m0 = m1; m1 = 0; }
      if (f == 0 && lane == 0) *at<uint32_t>(cx.gs->top, k * 4) = m;
#pragma unroll
      for (int j = 0; j < 3; j++) {
        const uint32_t row = 0xFFFF - (m & 0xFFFF), i = min(j * 4 + (lane >> 3), 8);
        *(uint4*)(cx.sp + SM_XSEL + i * 1024 + k * 128 + (((lane ^ k) & 7) << 4)) =
            __ldcg(at<const uint4>(cx.gs->xn, xn_offset(row, (lane & 7) * 4) + i * 8192));
      }
    }
    asm volatile("fence.proxy.async.shared::cta;" ::: "memory");
    prof(0, 2, 31);
  } else {
    const int wg = warp - 1;
#pragma unroll 1
    for (int u = 0; u < 32; u++) {
      bar_arrive(BAR_FREE + wg, 160);
      bar_sync(BAR_TILE + wg, 160);
      if (elect_one()) {
        const int n = (u >> 1) * 8 + 2 * f + wg;
        asm volatile("cp.async.bulk.global.shared::cta.bulk_group [%0], [%1], 8192;\ncp.async.bulk.commit_group;\ncp.async.bulk.wait_group 0;"
                     ::"l"(cx.gs->q3 + (n * 2 + (u & 1)) * 512), "r"(cx.sb + SM_H + wg * 8192) : "memory");
        if (u & 1) st_release(&cx.gs->q3_flag[n], epoch);
      }
      __syncwarp();
    }
  }
  bar_arrive(3, 352);
}

__device__ __forceinline__ void aux_consumer(const Ctx& cx, int f, int wg, int cw, int lane) {
  const int r = lane >> 2, c = lane & 3, tid = cw * 32 + lane;
  const uint32_t full = cx.sb + SM_FULL, empty = cx.sb + SM_EMPTY;
  const bool signaller = (tid & 127) == 0;
  auto await = [&](int st) { mbar_wait(full + 8 * (st & 7), (st >> 3) & 1); };
  auto release = [&](int st, int cnt) {
    asm volatile("{\n.reg .pred p;\nsetp.ne.u32 p, %2, 0;\n@p mbarrier.arrive.shared::cta.b64 _, [%0], %1;\n}"
                 ::"r"(empty + 8 * (st & 7)), "r"(cnt), "r"((uint32_t)signaller) : "memory");
  };
  prof(wg, 0);
  {
    const uint32_t lt = ((lane & 7) + (lane >> 4) * 8) * 128 + ((((cw & 3) * 2 + ((lane >> 3) & 1)) ^ (lane & 7)) << 4);
    uint32_t wa[144];
#pragma unroll
    for (int i = 0; i < 3; i++) {
      await(2 * i + wg);
#pragma unroll
      for (int k = 0; k < 12; k++) {
        const int kb = 12 * i + k;
        ldsm4t(cx.sb + (2 * i + wg) * FSTAGE + k * 2048 + lt, wa[4 * kb], wa[4 * kb + 1], wa[4 * kb + 2], wa[4 * kb + 3]);
      }
    }
    bar_sync(1, 256);
#pragma unroll
    for (int i = 0; i < 3; i++) release(2 * i + wg, 2);
    if (wg) bar_arrive(1, 256);
#pragma unroll 1
    for (int st = AST_X; st < AST_F; st += 3) {
      float acc[32];
      await(st);
      await(st + 1);
      await(st + 2);
      bar_sync(1 + wg, 256);
      wg_fence();
#pragma unroll
      for (int kb = 0; kb < 36; kb++) {
        const int i = kb / 12, k = kb % 12;
        mma_n64<0>(acc, wa[4 * kb], wa[4 * kb + 1], wa[4 * kb + 2], wa[4 * kb + 3],
                   mkdesc(cx.sb + ((st + i) & 7) * FSTAGE, 16) + (k >> 2) * 512 + (k & 3) * 2, kb > 0);
        if (k == 11) wg_commit();
      }
      if (st < AST_F - 3 || !wg) bar_arrive(2 - wg, 256);
      wg_wait<1>();
      release(st, 1);
      release(st + 1, 1);
      bar_sync(BAR_FREE + wg, 160);
      wg_wait<0>();
      pin(acc);
      release(st + 2, 1);
#pragma unroll
      for (int k = 0; k < 4; k++)
        stsm4t(cx.sb + SM_H + wg * 8192 + k * 2048 + lt, pack2(acc[8 * k] * SM_SCALE_LOG2, acc[8 * k + 1] * SM_SCALE_LOG2),
               pack2(acc[8 * k + 2] * SM_SCALE_LOG2, acc[8 * k + 3] * SM_SCALE_LOG2),
               pack2(acc[8 * k + 4] * SM_SCALE_LOG2, acc[8 * k + 5] * SM_SCALE_LOG2),
               pack2(acc[8 * k + 6] * SM_SCALE_LOG2, acc[8 * k + 7] * SM_SCALE_LOG2));
      asm volatile("fence.proxy.async.shared::cta;" ::: "memory");
      bar_arrive(BAR_TILE + wg, 160);
    }
    bar_sync(3, 352);
  }
  prof(wg, 3);
#pragma unroll 1
  for (int unit = wg; unit < 27; unit += 2) {
    if (unit >> 1 == 9) {
      asm volatile("fence.proxy.async.shared::cta;" ::: "memory");
      bar_sync(3, 256);
      prof(wg, 4);
    }
    const bool gu = unit < 18;
    float a0[4], a1[4];
#pragma unroll 1
    for (int m = 0; m < 2; m++) {
      float p0[4], p1[4];
      int st = AST_F + (unit >> 1) * 12 + m * 6 + wg;
      uint32_t b = cx.sb + (gu ? SM_XSEL : SM_H + m * 9216);
#pragma unroll 1
      for (int u = 0; u < 3; u++, st += 2, b += 3072) {
        await(st);
        wg_fence();
        const uint64_t da = mkdesc(cx.sb + (st & 7) * FSTAGE, 16), db = mkdesc(b, 16);
#pragma unroll
        for (int k = 0; k < 12; k++) mma_n8((k & 1) ? p1 : p0, da + k * 128, db + (k >> 2) * 64 + (k & 3) * 2, u > 0 || k > 1);
        wg_commit();
        wg_wait<1>();
        if (u) release(st - 2, 2);
      }
      wg_wait<0>();
      release(st - 2, 2);
      pin(p0); pin(p1);
#pragma unroll
      for (int i = 0; i < 4; i++) { a0[i] = a1[i]; a1[i] = p0[i] + p1[i]; }
    }
#pragma unroll
    for (int i = 0; i < 4; i++) {
      const int fl = (cw & 3) * 16 + r + (i >> 1) * 8, tok = 2 * c + (i & 1);
      if (gu) {
        const float h = bfr(silu_f(bfr(a0[i]))) * bfr(a1[i]);
        *(__nv_bfloat16*)(cx.sp + SM_H + unit * 1024 + tok * 128 + (((fl >> 3) ^ tok) << 4) + (fl & 7) * 2) = __float2bfloat16_rn(h);
      } else {
        *at<float>(cx.gs->ypart, ((f * TOPC + tok) * DM + (unit - 18) * 64 + fl) * 4) = a0[i] + a1[i];
      }
    }
  }
  prof(wg, 5);
  bar_sync(3, 256);
  if (tid == 0) red_release(&cx.gs->ycnt);
  prof(wg, 6);
}

struct Maps { CUtensorMap m[9]; };
__global__ void __cluster_dims__(2, 1, 1) __launch_bounds__(THREADS, 1)
fused_kernel(const __nv_bfloat16* __restrict__ x, const __nv_bfloat16* __restrict__ w_r, const __nv_bfloat16* __restrict__ kc,
             const __nv_bfloat16* __restrict__ wo, __nv_bfloat16* __restrict__ out, Scratch* gs,
             const __grid_constant__ Maps maps) {
  const CUtensorMap &tmX = maps.m[0], &tmWq = maps.m[1], &tmK = maps.m[2], &tmV = maps.m[3], &tmWo = maps.m[4];
  extern __shared__ __align__(1024) uint8_t smem_raw[];
  prof(0, 23, 511);
  if (threadIdx.x < 72 && blockIdx.x < N_ATT_CTA)
    asm volatile("prefetch.global.L2 [%0];" ::"l"(at<const void>(x, ((blockIdx.x >> 3) * 128 + (blockIdx.x & 7) * 8) * (DM * 2) + threadIdx.x * 128)));
  Ctx cx;
  cx.sb = smem_u32(smem_raw);
  cx.sp = smem_raw;
  cx.gs = gs;
  cx.rank = blockIdx.x & 1;
  const int warp = __shfl_sync(0xffffffffu, threadIdx.x >> 5, 0);
  const int cluster = blockIdx.x >> 1;
  const bool is_aux = blockIdx.x >= N_ATT_CTA;
  const int c7 = ((cluster - 36) * 37) >> 8;
  const int hs = cluster < 4 ? 4 + cluster : cluster < 36 ? (cluster - 4) >> 3 : 4 + c7;
  const int qb = (cluster < 4 ? 0 : cluster < 36 ? (cluster - 4) & 7 : cluster - 35 - 7 * c7) * 2 + cx.rank;

  extern __shared__ __align__(1024) uint8_t smem_alias[];
  const uint32_t xf = smem_u32(smem_alias) + SM_MISC + warp * 24;
  if (warp == 4 && elect_one()) prefetch_tmap(&tmX);
  if (elect_one()) {
    const uint32_t cnt = (warp > 4 && warp < 8) ? (is_aux ? 2 : 4) : 1;
#pragma unroll
    for (int i = 0; i < 3; i++) mbar_init(xf + 8 * i, cnt);
    asm volatile("fence.proxy.async.shared::cta;" ::: "memory");
    asm volatile("fence.mbarrier_init.release.cluster;" ::: "memory");
  }
  __syncwarp();
  cluster_arrive();
  if (warp == 4 && !is_aux) {
    if (elect_one()) {
      profc(0, 28);
#pragma unroll
      for (int i = 0; i < 3; i++) {
        mbar_expect_tx(xf + 8 * i, 24576);
        tma3d(xf - SM_XFULL + SM_X + i * 24576, &tmX, qb * 128, i * 3, xf + 8 * i);
      }
      profc(0, 29);
    }
  } else if (warp > 7 && elect_one()) {
    prefetch_tmap(&tmX + (is_aux ? warp - 4 : warp == 8 ? 8 : warp - 8));
  }
  __syncwarp();

  if (warp < 4) {
    asm volatile("setmaxnreg.dec.sync.aligned.u32 24;");
    cluster_wait();
    prof(0, 24, 511);
    if (warp == 0) {
      if (!is_aux) attn_producer(cx, qb, hs, &tmX, &tmK, &tmV, &tmWq, &tmWo);
      else aux_producer(cx, blockIdx.x - N_ATT_CTA, &tmWq, &maps.m[5]);
      prof(0, 25, 511);
    } else if (!is_aux) {
      attn_rows(cx, qb, hs, 3 - warp, read_lane(), &maps.m[8], w_r);
      if (warp == 1) attn_helper(cx, qb, hs, read_lane(), wo, &maps.m[8]);
      else bar_sync(BAR_OA, 352);
      attn_finish8(cx, qb, hs, warp - 1, read_lane(), out);
    } else {
      aux_helper(cx, blockIdx.x - N_ATT_CTA, warp, read_lane());
    }
    __syncwarp();
    cluster_arrive();
    cluster_wait();
    if (threadIdx.x == 32) { dly(cx, 201); dly(cx, 251); }
  } else {
    asm volatile("setmaxnreg.inc.sync.aligned.u32 240;");
    cluster_wait();
    const int cw = warp - 4, wg = cw >> 2;
    if (is_aux) aux_consumer(cx, blockIdx.x - N_ATT_CTA, wg, cw, read_lane());
    else attn_consumer(cx, qb, hs, wg, cw, read_lane(), x, kc, out);
  }
}

typedef CUresult (*EncodeFn)(CUtensorMap*, CUtensorMapDataType, cuuint32_t, void*, const cuuint64_t*, const cuuint64_t*,
                             const cuuint32_t*, const cuuint32_t*, CUtensorMapInterleave, CUtensorMapSwizzle,
                             CUtensorMapL2promotion, CUtensorMapFloatOOBfill);

void encode(EncodeFn fn, CUtensorMap* m, const void* p, int rank, const cuuint64_t* dims, const cuuint64_t* strides,
            const cuuint32_t* box) {
  const cuuint32_t es[5] = {1, 1, 1, 1, 1};
  fn(m, CU_TENSOR_MAP_DATA_TYPE_BFLOAT16, rank, const_cast<void*>(p), dims, strides, box, es, CU_TENSOR_MAP_INTERLEAVE_NONE,
     CU_TENSOR_MAP_SWIZZLE_128B, CU_TENSOR_MAP_L2_PROMOTION_L2_128B, CU_TENSOR_MAP_FLOAT_OOB_FILL_NONE);
}
void encode2d(EncodeFn fn, CUtensorMap* m, const void* p, uint64_t rows, uint64_t cols, uint32_t box_rows) {
  const cuuint64_t dims[2] = {cols, rows}, strides[1] = {cols * 2};
  const cuuint32_t box[2] = {64, box_rows};
  encode(fn, m, p, 2, dims, strides, box);
}

}

extern "C" void kernel_launch(void* const* d_in, const int* in_sizes, int n_in, void* d_out, int out_size) {
  (void)in_sizes; (void)n_in; (void)out_size;
  void* fnp = nullptr;
  cudaDriverEntryPointQueryResult qr;
  cudaGetDriverEntryPoint("cuTensorMapEncodeTiled", &fnp, cudaEnableDefault, &qr);
  EncodeFn fn = (EncodeFn)fnp;
  void* gs = nullptr;
  cudaGetSymbolAddress(&gs, g_scratch);
  Maps maps;
  CUtensorMap &tmX = maps.m[0], &tmWq = maps.m[1], &tmK = maps.m[2], &tmV = maps.m[3], &tmWo = maps.m[4], &tmG = maps.m[5],
              &tmU = maps.m[6], &tmD = maps.m[7];
  encode2d(fn, &tmK, d_in[1], 16 * SEQ, DH, 128);
  encode2d(fn, &tmV, d_in[2], 16 * SEQ, DH, 128);
  encode2d(fn, &tmWq, d_in[3], DM, 4096, 64);
  {
    const cuuint64_t dims[3] = {64, SEQ, 9}, strides[2] = {DM * 2, 128};
    const cuuint32_t box[3] = {64, 64, 3};
    encode(fn, &tmX, d_in[0], 3, dims, strides, box);
  }
  encode2d(fn, &maps.m[8], d_in[0], SEQ, DM, 16);
  encode2d(fn, &tmWo, d_in[4], 4096, DM, 128);
  encode2d(fn, &tmG, d_in[7], DM, FF, 192);
  encode2d(fn, &tmU, d_in[8], DM, FF, 192);
  encode2d(fn, &tmD, d_in[9], FF, DM, 192);
  cudaFuncSetAttribute(fused_kernel, cudaFuncAttributeMaxDynamicSharedMemorySize, SM_TOTAL);
  fused_kernel<<<N_CTA, THREADS, SM_TOTAL>>>((const __nv_bfloat16*)d_in[0], (const __nv_bfloat16*)d_in[6], (const __nv_bfloat16*)d_in[1],
                                            (const __nv_bfloat16*)d_in[4], (__nv_bfloat16*)d_out, (Scratch*)gs, maps);
}
```

```cpp
#include <cuda_runtime.h>
#include <cuda_bf16.h>
#include <cuda.h>
#include <stdint.h>

namespace {

constexpr int SEQ = 2048, DM = 576, DH = 128, FF = 4608, TOPC = 8;
constexpr int N_ATT_CTA = 128, N_CTA = 132;
constexpr int THREADS = 384;

constexpr uint32_t SM_RING = 0;
constexpr uint32_t STAGE = 32768;
constexpr uint32_t SM_SLOT = 131072;
constexpr uint32_t FSTAGE = 24576;
constexpr uint32_t SM_XSEL = 196608;
constexpr uint32_t SM_H = 205824;
constexpr uint32_t SM_MISC = 229376;
constexpr uint32_t SM_FULL = SM_MISC, SM_BAR_MISC = SM_MISC + 64, SM_BAR_XG = SM_MISC + 72, SM_BAR_P8 = SM_MISC + 80, SM_BAR_Q3 = SM_MISC + 88, SM_XFULL = SM_MISC + 96,
                   SM_EMPTY = SM_MISC + 120, SM_BAR_ROWS = SM_MISC + 216, SM_TAG = SM_MISC + 288,
                   SM_ROWS = SM_MISC + 304, SM_BOX8 = SM_MISC + 1024;
constexpr uint32_t SM_TOTAL = SM_MISC + 3072;
constexpr uint32_t SM_X = SM_MISC - 147456;

constexpr int BAR_ROWS = 6, BAR_HELPER = 7, BAR_OA = 8;
constexpr int NST_Q = 18, NST_KV = 128, NST_O = 18;
constexpr uint32_t SL_KE = (NST_Q - 1) & 3, SL_VE = NST_Q & 3, SL_KO = (NST_Q + 1) & 3, SL_VO = (NST_Q + 2) & 3;
#define X_N1 5
#define X_SPLIT 44
#define X_SPLIT3 36
#define X_PARK 5
#define X_C0 16
#define X_C1 32
#define X_C2 56
constexpr float SM_SCALE_LOG2 = 0.08838834764831845f * 1.4426950408889634f;

struct Scratch {
  uint4 part[16 * 64 * 2 * 4 * 128];
  uint4 gate[N_ATT_CTA * 144 * 8];
  uint4 q3[N_ATT_CTA * 1024];
  uint4 xn[SEQ * DM / 8];
  uint32_t key[SEQ];
  float ypart[4 * TOPC * DM];
  uint32_t top[32];
  unsigned launch[160];
  unsigned rows[16 * 32];
  unsigned q3_flag[N_ATT_CTA];
  unsigned ycnt;
};
__device__ __align__(1024) Scratch g_scratch;

__device__ __forceinline__ void prof(int, int, int = 0) {}
__device__ __forceinline__ void profc(int, int) {}

__device__ __forceinline__ uint32_t smem_u32(const void* p) { return (uint32_t)__cvta_generic_to_shared(p); }
__device__ __forceinline__ void mbar_init(uint32_t bar, uint32_t cnt) {
  asm volatile("mbarrier.init.shared::cta.b64 [%0], %1;" ::"r"(bar), "r"(cnt) : "memory");
}
__device__ __forceinline__ void mbar_expect_tx(uint32_t bar, uint32_t bytes) {
  asm volatile("mbarrier.arrive.expect_tx.shared::cta.b64 _, [%0], %1;" ::"r"(bar), "r"(bytes) : "memory");
}
__device__ __forceinline__ void mbar_arrive(uint32_t bar) {
  asm volatile("mbarrier.arrive.shared::cta.b64 _, [%0];" ::"r"(bar) : "memory");
}
__device__ __forceinline__ void mbar_arrive_cluster(uint32_t bar_cluster_addr) {
  asm volatile("mbarrier.arrive.shared::cluster.b64 _, [%0];" ::"r"(bar_cluster_addr) : "memory");
}
template <int ID>
__device__ __forceinline__ void mbar_arrive_cluster_now(uint32_t bar_cluster_addr, bool pred, uint32_t zero) {
  asm volatile("{\n.reg .pred p, q;\nsetp.ne.u32 p, %1, 0;\nsetp.eq.u32 q, %2, %3;\n"
               "ARR_LOOP:\n@p mbarrier.arrive.shared::cluster.b64 _, [%0];\n@q bra.uni ARR_LOOP;\n}"
               ::"r"(bar_cluster_addr), "r"((uint32_t)pred), "r"(zero), "n"(ID) : "memory");
}
__device__ __forceinline__ void block_fence(int id, uint32_t zero = blockIdx.y) {
  asm volatile("{\n.reg .pred q;\nsetp.eq.u32 q, %0, %1;\nBF_LOOP:\n@q st.volatile.shared.u32 [%0], %0;\n@q bra.uni BF_LOOP;\n}"
               ::"r"(zero), "r"(id) : "memory");
}
__device__ __forceinline__ bool mbar_test(uint32_t bar, uint32_t parity) {
  uint32_t ok;
  asm volatile("{\n.reg .pred p;\nmbarrier.test_wait.parity.shared::cta.b64 p, [%1], %2;\nselp.u32 %0, 1, 0, p;\n}"
               : "=r"(ok) : "r"(bar), "r"(parity) : "memory");
  return ok;
}
__device__ __forceinline__ void mbar_wait(uint32_t bar, uint32_t parity) {
  asm volatile("{\n.reg .pred p, q;\n.reg .u32 n;\nmov.u32 n, 0;\n"
               "WAIT_LOOP:\nmbarrier.try_wait.parity.shared::cta.b64 p, [%0], %1;\n"
               "add.u32 n, n, 1;\nsetp.lt.u32 q, n, 4194304;\nand.pred q, q, !p;\n@q bra WAIT_LOOP;\n}"
               ::"r"(bar), "r"(parity) : "memory");
}
__device__ __forceinline__ uint32_t mapa(uint32_t addr, uint32_t rank) {
  uint32_t r;
  asm volatile("mapa.shared::cluster.u32 %0, %1, %2;" : "=r"(r) : "r"(addr), "r"(rank));
  return r;
}
__device__ __forceinline__ void cluster_arrive() { asm volatile("barrier.cluster.arrive.relaxed.aligned;" ::: "memory"); }
__device__ __forceinline__ bool elect_one() {
  uint32_t p;
  asm volatile("{\n.reg .pred p;\nelect.sync _|p, 0xffffffff;\nselp.u32 %0, 1, 0, p;\n}" : "=r"(p));
  return p;
}
__device__ __forceinline__ int read_lane() { return threadIdx.x & 31; }
__device__ __forceinline__ void cluster_wait() { asm volatile("barrier.cluster.wait.acquire.aligned;" ::: "memory"); }
__device__ __forceinline__ void bar_sync(int id, int n) { asm volatile("barrier.cta.sync %0, %1;" ::"r"(id), "r"(n) : "memory"); }
__device__ __forceinline__ void bar_arrive(int id, int n) { asm volatile("barrier.cta.arrive %0, %1;" ::"r"(id), "r"(n) : "memory"); }

__device__ __forceinline__ uint64_t policy_evict_first() {
  uint64_t p;
  asm("createpolicy.fractional.L2::evict_first.b64 %0, 1.0;" : "=l"(p));
  return p;
}
__device__ __forceinline__ uint64_t policy_evict_normal() {
  uint64_t p;
  asm("createpolicy.fractional.L2::evict_normal.b64 %0, 1.0;" : "=l"(p));
  return p;
}
__device__ __forceinline__ void tma3d(uint32_t dst, const CUtensorMap* tm, int c1, int c2, uint32_t bar) {
  asm volatile("cp.async.bulk.tensor.3d.shared::cluster.global.mbarrier::complete_tx::bytes [%0], [%1, {%2, %3, %4}], [%5];"
               ::"r"(dst), "l"(tm), "r"(0), "r"(c1), "r"(c2), "r"(bar) : "memory");
}
__device__ __forceinline__ void tma2d(uint32_t dst, const CUtensorMap* tm, int c0, int c1, uint32_t bar) {
  asm volatile("cp.async.bulk.tensor.2d.shared::cluster.global.mbarrier::complete_tx::bytes [%0], [%1, {%2, %3}], [%4];"
               ::"r"(dst), "l"(tm), "r"(c0), "r"(c1), "r"(bar) : "memory");
}
__device__ __forceinline__ void tma2d_stream(uint32_t dst, const CUtensorMap* tm, int c0, int c1, uint32_t bar) {
  asm volatile("{\n.reg .b64 pol;\ncreatepolicy.fractional.L2::evict_first.b64 pol, 1.0;\n"
               "cp.async.bulk.tensor.2d.shared::cluster.global.mbarrier::complete_tx::bytes.L2::cache_hint [%0], [%1, {%2, %3}], [%4], pol;\n}"
               ::"r"(dst), "l"(tm), "r"(c0), "r"(c1), "r"(bar) : "memory");
}
__device__ __forceinline__ void tma2d_prefetch(const CUtensorMap* tm, int c0, int c1) {
  asm volatile("cp.async.bulk.prefetch.tensor.2d.L2.global [%0, {%1, %2}];" ::"l"(tm), "r"(c0), "r"(c1) : "memory");
}
__device__ __forceinline__ void prefetch_l2(const void* p, uint32_t bytes) {
  asm volatile("cp.async.bulk.prefetch.L2.global [%0], %1;" ::"l"(p), "r"(bytes) : "memory");
}
__device__ __forceinline__ void prefetch_tmap(const CUtensorMap* tm) {
  asm volatile("prefetch.tensormap [%0];" ::"l"(tm) : "memory");
}

__device__ __forceinline__ void wg_fence() { asm volatile("wgmma.fence.sync.aligned;" ::: "memory"); }
__device__ __forceinline__ void wg_commit() { asm volatile("wgmma.commit_group.sync.aligned;" ::: "memory"); }
template <int N> __device__ __forceinline__ void wg_wait() { asm volatile("wgmma.wait_group.sync.aligned %0;" ::"n"(N) : "memory"); }

__device__ __forceinline__ uint64_t mkdesc(uint32_t addr, uint32_t lbo_bytes) {
  return (uint64_t)(((addr & 0x3FFFF) >> 4) | ((lbo_bytes >> 4) << 16)) | ((uint64_t)0x40000040u << 32);
}
template <int N> __device__ __forceinline__ void pin(float (&a)[N]) {
#pragma unroll
  for (int i = 0; i < N; i++) asm volatile("" : "+f"(a[i])::"memory");
}
template <int N> __device__ __forceinline__ void pin(uint32_t (&a)[N]) {
#pragma unroll
  for (int i = 0; i < N; i++) asm volatile("" : "+r"(a[i])::"memory");
}

#define F8(d, o) "+f"(d[o]), "+f"(d[o + 1]), "+f"(d[o + 2]), "+f"(d[o + 3]), "+f"(d[o + 4]), "+f"(d[o + 5]), "+f"(d[o + 6]), "+f"(d[o + 7])
#define R32A "%0, %1, %2, %3, %4, %5, %6, %7, %8, %9, %10, %11, %12, %13, %14, %15, %16, %17, %18, %19, %20, %21, %22, %23, %24, %25, %26, %27, %28, %29, %30, %31"
#define R32B "%32, %33, %34, %35, %36, %37, %38, %39, %40, %41, %42, %43, %44, %45, %46, %47, %48, %49, %50, %51, %52, %53, %54, %55, %56, %57, %58, %59, %60, %61, %62, %63"

template <int TB>
__device__ __forceinline__ void mma_n128(float (&d)[64], uint32_t a0, uint32_t a1, uint32_t a2, uint32_t a3, uint64_t db, int acc) {
  asm volatile("{\n.reg .pred p;\nsetp.ne.b32 p, %69, 0;\n"
               "wgmma.mma_async.sync.aligned.m64n128k16.f32.bf16.bf16 {" R32A ", " R32B "}, {%64, %65, %66, %67}, %68, p, 1, 1, %70;\n}\n"
               : F8(d, 0), F8(d, 8), F8(d, 16), F8(d, 24), F8(d, 32), F8(d, 40), F8(d, 48), F8(d, 56)
               : "r"(a0), "r"(a1), "r"(a2), "r"(a3), "l"(db), "r"(acc), "n"(TB));
}
template <int TB>
__device__ __forceinline__ void mma_n128_ss(float (&d)[64], uint64_t da, uint64_t db, int acc) {
  asm volatile("{\n.reg .pred p;\nsetp.ne.b32 p, %66, 0;\n"
               "wgmma.mma_async.sync.aligned.m64n128k16.f32.bf16.bf16 {" R32A ", " R32B "}, %64, %65, p, 1, 1, 0, %67;\n}\n"
               : F8(d, 0), F8(d, 8), F8(d, 16), F8(d, 24), F8(d, 32), F8(d, 40), F8(d, 48), F8(d, 56)
               : "l"(da), "l"(db), "r"(acc), "n"(TB));
}
template <int TB>
__device__ __forceinline__ void mma_n64(float (&d)[32], uint32_t a0, uint32_t a1, uint32_t a2, uint32_t a3, uint64_t db, int acc) {
  asm volatile("{\n.reg .pred p;\nsetp.ne.b32 p, %37, 0;\n"
               "wgmma.mma_async.sync.aligned.m64n64k16.f32.bf16.bf16 {" R32A "}, {%32, %33, %34, %35}, %36, p, 1, 1, %38;\n}\n"
               : F8(d, 0), F8(d, 8), F8(d, 16), F8(d, 24)
               : "r"(a0), "r"(a1), "r"(a2), "r"(a3), "l"(db), "r"(acc), "n"(TB));
}
__device__ __forceinline__ void mma_n8(float (&d)[4], uint64_t da, uint64_t db, int acc) {
  asm volatile("{\n.reg .pred p;\nsetp.ne.b32 p, %6, 0;\n"
               "wgmma.mma_async.sync.aligned.m64n8k16.f32.bf16.bf16 {%0, %1, %2, %3}, %4, %5, p, 1, 1, 1, 0;\n}\n"
               : "+f"(d[0]), "+f"(d[1]), "+f"(d[2]), "+f"(d[3])
               : "l"(da), "l"(db), "r"(acc));
}
__device__ __forceinline__ void hmma_k16(float (&d)[4], uint32_t a0, uint32_t a1, uint32_t a2, uint32_t a3, uint32_t b0, uint32_t b1) {
  asm volatile("mma.sync.aligned.m16n8k16.row.col.f32.bf16.bf16.f32 {%0, %1, %2, %3}, {%4, %5, %6, %7}, {%8, %9}, {%0, %1, %2, %3};"
               : "+f"(d[0]), "+f"(d[1]), "+f"(d[2]), "+f"(d[3]) : "r"(a0), "r"(a1), "r"(a2), "r"(a3), "r"(b0), "r"(b1));
}

__device__ __forceinline__ uint32_t pack2(float lo, float hi) {
  uint32_t r;
  asm("cvt.rn.bf16x2.f32 %0, %1, %2;" : "=r"(r) : "f"(hi), "f"(lo));
  return r;
}
__device__ __forceinline__ float bf_lo(uint32_t w) { return __uint_as_float(w << 16); }
__device__ __forceinline__ float bf_hi(uint32_t w) { return __uint_as_float(w & 0xFFFF0000u); }
__device__ __forceinline__ float bfr(float x) { return __uint_as_float(pack2(0.f, x)); }
__device__ __forceinline__ uint32_t sub2(uint32_t a, uint32_t b) {
  uint32_t r;
  asm("sub.rn.bf16x2 %0, %1, %2;" : "=r"(r) : "r"(a), "r"(b));
  return r;
}
__device__ __forceinline__ uint32_t add2(uint32_t a, uint32_t b) {
  uint32_t r;
  asm("add.rn.bf16x2 %0, %1, %2;" : "=r"(r) : "r"(a), "r"(b));
  return r;
}
__device__ __forceinline__ uint32_t mul2(uint32_t a, uint32_t b) {
  uint32_t r;
  asm("mul.rn.bf16x2 %0, %1, %2;" : "=r"(r) : "r"(a), "r"(b));
  return r;
}
__device__ __forceinline__ uint32_t fma2(uint32_t a, uint32_t b, uint32_t c) {
  uint32_t r;
  asm("fma.rn.bf16x2 %0, %1, %2, %3;" : "=r"(r) : "r"(a), "r"(b), "r"(c));
  return r;
}
__device__ __forceinline__ float ex2(float x) {
  float r;
  asm("ex2.approx.ftz.f32 %0, %1;" : "=f"(r) : "f"(x));
  return r;
}
__device__ __forceinline__ float rcp(float x) {
  float r;
  asm("rcp.approx.ftz.f32 %0, %1;" : "=f"(r) : "f"(x));
  return r;
}
__device__ __forceinline__ float silu_f(float t) { return t * rcp(1.0f + ex2(-1.4426950408889634f * t)); }
__device__ __forceinline__ void lds128(uint32_t a, uint32_t& x, uint32_t& y, uint32_t& z, uint32_t& w) {
  asm volatile("ld.shared.v4.u32 {%0, %1, %2, %3}, [%4];" : "=r"(x), "=r"(y), "=r"(z), "=r"(w) : "r"(a) : "memory");
}
__device__ __forceinline__ void ldsm4(uint32_t a, uint32_t& x, uint32_t& y, uint32_t& z, uint32_t& w) {
  asm volatile("ldmatrix.sync.aligned.m8n8.x4.shared.b16 {%0, %1, %2, %3}, [%4];" : "=r"(x), "=r"(y), "=r"(z), "=r"(w) : "r"(a) : "memory");
}
constexpr uint32_t TAG_BIT = 0x10000;
__device__ __forceinline__ void st_gran(uint4* p, uint32_t x, uint32_t y, uint32_t z, uint32_t w) {
  asm volatile("st.relaxed.gpu.global.v4.b32 [%0], {%1, %2, %3, %4};" ::"l"(p), "r"(x), "r"(y), "r"(z), "r"(w) : "memory");
}
__device__ __forceinline__ void ld_gran(const uint4* p, uint32_t& x, uint32_t& y, uint32_t& z, uint32_t& w) {
  asm volatile("ld.relaxed.gpu.global.v4.b32 {%0, %1, %2, %3}, [%4];" : "=r"(x), "=r"(y), "=r"(z), "=r"(w) : "l"(p) : "memory");
}
__device__ __forceinline__ void ldsm4t(uint32_t a, uint32_t& x, uint32_t& y, uint32_t& z, uint32_t& w) {
  asm volatile("ldmatrix.sync.aligned.m8n8.x4.trans.shared.b16 {%0, %1, %2, %3}, [%4];" : "=r"(x), "=r"(y), "=r"(z), "=r"(w) : "r"(a) : "memory");
}
__device__ __forceinline__ void stsm4t(uint32_t a, uint32_t x, uint32_t y, uint32_t z, uint32_t w) {
  asm volatile("stmatrix.sync.aligned.m8n8.x4.trans.shared.b16 [%0], {%1, %2, %3, %4};" ::"r"(a), "r"(x), "r"(y), "r"(z), "r"(w) : "memory");
}
__device__ __forceinline__ void stsm4(uint32_t a, uint32_t x, uint32_t y, uint32_t z, uint32_t w) {
  asm volatile("stmatrix.sync.aligned.m8n8.x4.shared.b16 [%0], {%1, %2, %3, %4};" ::"r"(a), "r"(x), "r"(y), "r"(z), "r"(w) : "memory");
}
template <class T>
__device__ __forceinline__ T* at(const void* base, uint32_t off) {
  uint64_t r;
  asm("{\n.reg .u32 lo, hi;\nmov.b64 {lo, hi}, %1;\nadd.cc.u32 lo, lo, %2;\naddc.u32 hi, hi, 0;\nmov.b64 %0, {lo, hi};\n}"
      : "=l"(r) : "l"(base), "r"(off));
  return (T*)__cvta_global_to_generic(r);
}
__device__ __forceinline__ void add_granules(float (&red)[32], const uint32_t (&g)[16]) {
#pragma unroll
  for (int i = 0; i < 16; i++) { red[2 * i] += bf_lo(g[i]); red[2 * i + 1] += bf_hi((i & 3) ? g[i] : g[i] & ~TAG_BIT); }
}
__device__ __forceinline__ bool granules_ok(const uint32_t (&g)[16], uint32_t tag) {
  uint32_t u, v;
  asm("lop3.b32 %0, %1, %2, %3, 0x7E;" : "=r"(u) : "r"(g[0]), "r"(g[4]), "r"(tag));
  asm("lop3.b32 %0, %1, %2, %3, 0x7E;" : "=r"(v) : "r"(g[8]), "r"(g[12]), "r"(tag));
  return __all_sync(0xffffffffu, ((u | v) & TAG_BIT) == 0);
}
__device__ __forceinline__ unsigned ld_acquire(const unsigned* p) {
  unsigned v;
  asm volatile("ld.acquire.gpu.global.u32 %0, [%1];" : "=r"(v) : "l"(p) : "memory");
  return v;
}
__device__ __forceinline__ void red_release(unsigned* p) {
  asm volatile("red.release.gpu.global.add.u32 [%0], 1;" ::"l"(p) : "memory");
}
__device__ __forceinline__ void st_release(unsigned* p, unsigned v) {
  asm volatile("st.release.gpu.global.u32 [%0], %1;" ::"l"(p), "r"(v) : "memory");
}

template <int K0, int K1>
__device__ __forceinline__ void ln_fetch(uint32_t (&xa)[144], uint32_t boxes, uint32_t lo) {
#pragma unroll
  for (int k = K0; k < K1; k++) ldsm4(((boxes + lo) ^ ((k & 3) << 5)) + (k >> 2) * 8192, xa[4 * k], xa[4 * k + 1], xa[4 * k + 2], xa[4 * k + 3]);
}
template <int K0, int K1>
__device__ __forceinline__ void ln_sums(const uint32_t (&xa)[144], float (&sm)[4][4]) {
#pragma unroll
  for (int k = K0; k < K1; k++) hmma_k16(sm[k & 3], xa[4 * k], xa[4 * k + 1], xa[4 * k + 2], xa[4 * k + 3], 0x3F803F80u, 0x3F803F80u);
}
__device__ __forceinline__ uint32_t sq8(const uint32_t* a) {
  uint32_t t, u;
  asm("mul.rn.bf16x2 %0, %1, %1;" : "=r"(t) : "r"(a[0]));
  asm("mul.rn.bf16x2 %0, %1, %1;" : "=r"(u) : "r"(a[2]));
#pragma unroll
  for (int i = 4; i < 16; i += 4) {
    asm("fma.rn.bf16x2 %0, %1, %1, %0;" : "+r"(t) : "r"(a[i]));
    asm("fma.rn.bf16x2 %0, %1, %1, %0;" : "+r"(u) : "r"(a[i + 2]));
  }
  return add2(t, u);
}
__device__ __forceinline__ void ln_centre(uint32_t (&xa)[144], int j0, int j1, uint32_t mm0, uint32_t mm1, float& sq0, float& sq1) {
#pragma unroll
  for (int j = 0; j < 72; j += 8)
    if (j >= j0 && j < j1) {
#pragma unroll
      for (int k = j; k < j + 8; k++) {
        xa[2 * k] = sub2(xa[2 * k], mm0);
        xa[2 * k + 1] = sub2(xa[2 * k + 1], mm1);
      }
      const uint32_t t0 = sq8(xa + 2 * j), t1 = sq8(xa + 2 * j + 1);
      sq0 += bf_lo(t0) + bf_hi(t0);
      sq1 += bf_lo(t1) + bf_hi(t1);
    }
}
__device__ __forceinline__ float ln_rstd(float var) {
  float sd;
  asm("sqrt.approx.ftz.f32 %0, %1;" : "=f"(sd) : "f"(bfr(bfr(fmaxf(var, 0.0f)) + 1e-5f)));
  return rcp(bfr(sd));
}
__device__ __forceinline__ uint32_t silu2(uint32_t t) { return pack2(silu_f(bf_lo(t)), silu_f(bf_hi(t))); }
__device__ __forceinline__ float sum8(float v) {
#pragma unroll
  for (int d = 4; d; d >>= 1) v += __shfl_xor_sync(0xffffffffu, v, d);
  return v;
}
__device__ __forceinline__ void await_count(const unsigned* p, unsigned target, unsigned sleep_ns) {
#pragma unroll 1
  for (int n = 0; n < (1 << 18) && __any_sync(0xffffffffu, (int)(ld_acquire(p) - target) < 0); n++) __nanosleep(sleep_ns);
}
__device__ __forceinline__ void bulk_load(uint32_t dst, const void* src, uint32_t bytes, uint32_t bar) {
  asm volatile("cp.async.bulk.shared::cluster.global.mbarrier::complete_tx::bytes [%0], [%1], %2, [%3];"
               ::"r"(dst), "l"(src), "r"(bytes), "r"(bar) : "memory");
}
__device__ __forceinline__ void proxy_fence() { asm volatile("fence.proxy.async;" ::: "memory"); }

template <int V> struct IC { static constexpr int value = V; };

struct Ctx {
  uint32_t sb;
  uint8_t* sp;
  uint32_t rank;
  Scratch* gs;
};

__device__ __forceinline__ void dly(const Ctx&, int) {}
template <int BOXES>
__device__ __forceinline__ void load_stage(uint32_t dst, const CUtensorMap* tm, int c0, int c1, uint32_t bar, uint32_t bytes, uint64_t pol) {
  asm volatile("{\n.reg .pred p;\nelect.sync _|p, 0xffffffff;\n"
               "@p mbarrier.arrive.expect_tx.shared::cta.b64 _, [%4], %7;\n"
               "@p cp.async.bulk.tensor.2d.shared::cluster.global.mbarrier::complete_tx::bytes.multicast::cluster.L2::cache_hint"
               " [%0], [%1, {%2, %3}], [%4], %5, %6;\n}"
               ::"r"(dst), "l"(tm), "r"(c0), "r"(c1), "r"(bar), "h"((uint16_t)3), "l"(pol), "r"(bytes) : "memory");
  if (BOXES == 2)
    asm volatile("{\n.reg .pred p;\nelect.sync _|p, 0xffffffff;\n"
                 "@p cp.async.bulk.tensor.2d.shared::cluster.global.mbarrier::complete_tx::bytes.multicast::cluster.L2::cache_hint"
                 " [%0], [%1, {%2, %3}], [%4], %5, %6;\n}"
                 ::"r"(dst + 8192), "l"(tm), "r"(c0), "r"(c1 + 64), "r"(bar), "h"((uint16_t)3), "l"(pol) : "memory");
}
__device__ __forceinline__ void attn_producer(const Ctx& cx, int qb, int hs, const CUtensorMap* tmX, const CUtensorMap* tmK,
                                              const CUtensorMap* tmV, const CUtensorMap* tmWq, const CUtensorMap* tmWo) {
  const uint32_t full = cx.sb + SM_FULL, empty = cx.sb + SM_EMPTY, ring = cx.sb + SM_RING + cx.rank * 16384;
  const uint64_t keep = policy_evict_normal(), last_use = policy_evict_first();
  auto acquire = [&](int st) {
    mbar_wait(empty + 8 * (st & 3), ((st >> 2) ^ ((st & 3) >> 1) ^ 1) & 1);
    if (st > 3) dly(cx, st);
  };
  if (elect_one()) {
#pragma unroll
    for (int j = 0; j < 3; j++) {
      mbar_expect_tx(cx.sb + SM_XFULL + 96 + 8 * j, 24576);
      tma3d(cx.sb + SM_X + 73728 + j * 24576, tmX, qb * 128 + 64, j * 3, cx.sb + SM_XFULL + 96 + 8 * j);
    }
  }
  __syncwarp();
  const int c0 = cx.rank * 64;
#pragma unroll 1
  for (int p = 0; p < 3; p++) {
    const int n0 = (hs * 4 + ((0x120 >> (4 * p)) & 3)) * DH + c0;
#pragma unroll
    for (int i = 0; i < 5; i++) {
      const int st = (p == 2 ? 13 : 5 * p) + i, sl = st & 3;
      if (i == 4 && p == 2) break;
      if (st == 1) mbar_wait(cx.sb + SM_XFULL + 16, 0);
      acquire(st);
      if (i == 2) load_stage<1>(ring + sl * STAGE, tmWq, n0, 256, full + 8 * sl, 16384, last_use);
      else load_stage<2>(ring + sl * STAGE, tmWq, n0, i < 2 ? 128 * i : 128 * i - 64, full + 8 * sl, 32768, last_use);
      if (i == 3 && p < 2 && elect_one()) {
        tma2d_prefetch(tmWq, (hs * 4 + 2 - p) * DH + (qb & 1) * 64, (qb >> 1) * 64);
        if (p == 0 && qb < 9) tma2d_prefetch(tmWq, (hs * 4 + 3) * DH, qb * 64);
      }
      __syncwarp();
    }
    if (p == 1) {
      const int n3 = (hs * 4 + 3) * DH;
      acquire(10);
      load_stage<2>(ring + 2 * STAGE, tmWq, n3, 2 * c0, full + 16, 32768, last_use);
      acquire(11);
      if (cx.rank) load_stage<1>(ring + 3 * STAGE, tmWq, n3, 384, full + 24, 24576, last_use);
      else load_stage<2>(ring + 3 * STAGE, tmWq, n3, 256, full + 24, 24576, last_use);
      acquire(12);
      load_stage<1>(ring, tmWq, n3, 448 + c0, full, 16384, last_use);
    }
  }
  int vrow = 0;
  uint64_t vpol = keep;
#pragma unroll 1
  for (int j = 0; j < 32; j++) {
    const int st = NST_Q - 1 + 4 * j, row = (hs * 2 + (j >> 4)) * SEQ + (j & 7) * 256;
    const uint64_t pol = (j & 8) ? last_use : keep;
    if (j < 7 && qb < 8 && elect_one()) tma2d_prefetch((qb & 4) ? tmV : tmK, (qb & 1) * 64, row + 256 + (qb & 2) * 64);
    __syncwarp();
    if (j == 24) mbar_wait(cx.sb + SM_BAR_Q3, 0);
    acquire(st);
    load_stage<1>(ring + SL_KE * STAGE, tmK, c0, row, full + 8 * SL_KE, 32768, pol);
    acquire(st + 1);
    if (j) load_stage<1>(ring + SL_VE * STAGE, tmV, c0, vrow, full + 8 * SL_VE, 32768, vpol);
    else load_stage<2>(ring + SL_VE * STAGE, tmWq, (hs * 4 + 1) * DH + c0, 448, full + 8 * SL_VE, 32768, last_use);
    vrow = row + 128;
    vpol = pol;
    acquire(st + 2);
    load_stage<1>(ring + SL_KO * STAGE, tmK, c0, vrow, full + 8 * SL_KO, 32768, pol);
    acquire(st + 3);
    load_stage<1>(ring + SL_VO * STAGE, tmV, c0, row, full + 8 * SL_VO, 32768, pol);
  }
  acquire(NST_Q + NST_KV - 1);
  load_stage<1>(ring + SL_KE * STAGE, tmV, c0, vrow, full + 8 * SL_KE, 32768, last_use);
#pragma unroll 1
  for (int u = 0; u < NST_O; u++) {
    const int st = NST_Q + NST_KV + u, sl = st & 3;
    const int blk = u < 4 && cx.rank ? 8 : ((hs + max(u >> 1, 1)) & 7);
    const int head = u < 4 ? u ^ (u >> 1) : ((u & 1) * 2 + cx.rank + 3) & 3;
    acquire(st);
    load_stage<1>(ring + sl * STAGE, tmWo, blk * 64, hs * 512 + head * 128, full + 8 * sl, 32768, last_use);
  }
}

__device__ __forceinline__ uint32_t xn_offset(uint32_t row, int lane) {
  return (row >> 6) * (9 * 8192) + (row & 63) * 128 + ((((lane >> 2) ^ row) & 7) << 4) + (lane & 3) * 4;
}

__device__ __forceinline__ void attn_rows(const Ctx& cx, int qb, int hs, int hw, int lane, const CUtensorMap* tmX16,
                                          const __nv_bfloat16* w_r) {
  extern __shared__ __align__(1024) uint8_t smem_rows[];
  auto box = [&](int blk) { return blk < 8 ? SM_SLOT + 2 * STAGE + 8192 + (blk >> 2) * 16384 + (blk & 3) * 2048 : SM_BOX8; };
  const uint32_t sb = smem_u32(smem_rows);
  if (hw == 0) {
    bar_sync(BAR_HELPER, 160);
    if (elect_one()) {
      mbar_expect_tx(sb + SM_BAR_ROWS, 9 * 2048);
#pragma unroll
      for (int i = 0; i < 9; i++) tma2d(sb + box(i), tmX16, i * 64, qb * 128 + hs * 16, sb + SM_BAR_ROWS);
    }
    __syncwarp();
  }
  uint32_t g = (lane >> 3) * 128 + (((lane ^ (lane >> 3)) & 7) << 4);
  auto next = [&]() {
    g = ((g + 512) & 2047) ^ 64;
    asm volatile("" : "+r"(g));
  };
  float* const part = (float*)(smem_rows + SM_ROWS);
  mbar_wait(sb + SM_BAR_ROWS, 0);
  if (hw == 0) dly(cx, 190);
#pragma unroll 1
  for (int i = 0; i < 4; i++) {
    float a = 0.f, b = 0.f;
#pragma unroll
    for (int j = 0; j < 3; j++) {
      const uint4 v = *(const uint4*)(smem_rows + box(hw * 3 + j) + g);
      const uint32_t w[4] = {v.x, v.y, v.z, v.w};
#pragma unroll
      for (int k = 0; k < 4; k++) {
        a += bf_lo(w[k]) + bf_hi(w[k]);
        b = fmaf(bf_lo(w[k]), bf_lo(w[k]), fmaf(bf_hi(w[k]), bf_hi(w[k]), b));
      }
    }
    a = sum8(a);
    b = sum8(b);
    float* p = part + hw * 16 + (g >> 7);
    p[0] = a;
    p[48] = b;
    next();
  }
  bar_sync(BAR_ROWS, 96);
  if (hw == 0) dly(cx, 191);
  {
    const float* p = part + (lane & 15);
    const float mean = (p[0] + p[16] + p[32]) * (1.0f / DM), rstd = ln_rstd((p[48] + p[64] + p[80]) * (1.0f / DM) - mean * mean);
    const uint32_t mm = pack2(mean, mean), rr = pack2(rstd - bfr(rstd), rstd);
#pragma unroll 1
    for (int u = hw * 12; u < hw * 12 + 12; u++) {
      const int blk = u >> 2;
      uint4* q = (uint4*)(smem_rows + box(blk) + g);
      uint4 v = *q;
      const uint32_t m = __shfl_sync(0xffffffffu, mm, g >> 7), r = __shfl_sync(0xffffffffu, rr, g >> 7);
      const uint32_t hi = __byte_perm(r, 0, 0x3232), lo = __byte_perm(r, 0, 0x1010);
      auto norm = [&](uint32_t w) {
        const uint32_t xc = sub2(w, m);
        return fma2(xc, hi, mul2(xc, lo));
      };
      v = make_uint4(norm(v.x), norm(v.y), norm(v.z), norm(v.w));
      *q = v;
      *at<uint4>(cx.gs->xn + ((qb * 2 + (hs >> 2)) * 9 + blk) * 512 + (hs & 3) * 128, g) = v;
      next();
    }
  }
  bar_sync(BAR_ROWS, 96);
  if (hw == 0) {
    dly(cx, 192);
    if (lane == 0) red_release(&cx.gs->rows[qb * 32]);
    dly(cx, 193);
  }
#pragma unroll 1
  for (int u = hw ? 13 * hw - 3 : 0; u < 13 * hw + 10; u++) {
    const int blk = u >> 2;
    const uint32_t o = (g + (u & 3) * 512) ^ ((u & 1) << 6);
    const uint4 v = *(const uint4*)(smem_rows + box(blk) + o);
    *at<uint4>(cx.gs->gate + (blk < 8 ? (qb * 8 + blk) * 144 + hs * 16 : (qb * 8 + hs) * 144 + 128) * 8, o) =
        make_uint4(silu2(v.x), silu2(v.y), silu2(v.z), silu2(v.w));
  }
  if (hw) dly(cx, 194 + hw);
  __nanosleep(5000);
#pragma unroll 1
  for (int blk = hw * 3; blk < hw * 3 + 3; blk++) {
    const uint4 c = __ldg(at<const uint4>(w_r, blk * 128 + ((g ^ (g >> 3)) & 0x70)));
#pragma unroll 1
    for (int i = 0; i < 4; i++) {
      const uint4 v = *(const uint4*)(smem_rows + box(blk) + g);
      part[blk * 16 + (g >> 7)] =
          sum8(fmaf(bf_lo(v.x), bf_lo(c.x), fmaf(bf_hi(v.x), bf_hi(c.x), fmaf(bf_lo(v.y), bf_lo(c.y), bf_hi(v.y) * bf_hi(c.y)))) +
               fmaf(bf_lo(v.z), bf_lo(c.z), fmaf(bf_hi(v.z), bf_hi(c.z), fmaf(bf_lo(v.w), bf_lo(c.w), bf_hi(v.w) * bf_hi(c.w)))));
      next();
    }
  }
  bar_sync(BAR_ROWS, 96);
  if (hw == 0) {
    dly(cx, 194);
    float d = 0.f;
#pragma unroll
    for (int j = 0; j < 9; j++) d += part[j * 16 + (lane & 15)];
    const uint32_t row = qb * 128 + hs * 16 + (lane & 15), b = pack2(0.f, d);
    *at<uint32_t>(cx.gs->key, row * 4) = (b ^ ((int)b < 0 ? 0xFFFF0000u : 0x80000000u)) + 0xFFFF - row;
    __syncwarp();
    if (lane == 0) red_release(&cx.gs->rows[qb * 32 + 1]);
  }
}

constexpr uint32_t SM_XO = SM_SLOT, SM_GO = SM_SLOT + STAGE, SM_P8 = SM_SLOT + 2 * STAGE;
__device__ __forceinline__ void attn_helper(const Ctx& cx, int qb, int hs, int lane, const __nv_bfloat16* wo, const CUtensorMap* tmX16) {
  unsigned e = 0;
  if (lane == 0) {
    e = cx.gs->launch[blockIdx.x];
    cx.gs->launch[blockIdx.x] = e + 1;
  }
  e = __shfl_sync(0xffffffffu, e, 0);
  if (lane == 0) {
    *(uint32_t*)(cx.sp + SM_TAG) = (~e & 1) * TAG_BIT;
    mbar_arrive(cx.sb + SM_BAR_MISC);
  }
  bar_sync(BAR_HELPER, 64);
  await_count(&cx.gs->rows[qb * 32 + 1], 8 * (e + 1), 1000);
  await_count(&cx.gs->q3_flag[qb * 8 + hs], e + 1, 1000);
  proxy_fence();
  if (elect_one()) {
    mbar_expect_tx(cx.sb + SM_BAR_Q3, 16384);
#pragma unroll
    for (int i = 0; i < 2; i++) bulk_load(cx.sb + SM_SLOT + 2 * STAGE + i * 16384 + 8192, cx.gs->q3 + (qb * 16 + hs * 2 + i) * 512, 8192, cx.sb + SM_BAR_Q3);
  }
  __syncwarp();
  bar_sync(BAR_HELPER, 64);
  prefetch_l2(at<const void>(wo, (hs * 512 + qb * 32 + lane) * (DM * 2)), DM * 2);
  await_count(&cx.gs->ycnt, 4 * (e + 1), 500);
  const uint32_t mykey = __ldcg(at<const uint32_t>(cx.gs->top, (lane >> 1) * 4)), myrow = 0xFFFF - (mykey & 0xFFFF);
#pragma unroll 1
  for (uint32_t todo = __ballot_sync(0xffffffffu, lane < 16 && ((lane & 1) ? myrow >> 4 == qb * 8 + hs : myrow >> 7 == qb)); todo; todo &= todo - 1) {
    const int i = __ffs(todo) - 1, blk = (i & 1) ? 8 : hs;
    const uint32_t key = __shfl_sync(0xffffffffu, mykey, i), row = 0xFFFF - (key & 0xFFFF), o = xn_offset(row, lane);
    const uint32_t t = __ldcg(at<const uint32_t>(cx.gs->xn, o + blk * 8192));
    const float2* p = at<const float2>(cx.gs->ypart, ((i >> 1) * DM + blk * 64 + 2 * lane) * 4);
    const float2 y0 = __ldcg(p), y1 = __ldcg(p + TOPC * DM / 2), y2 = __ldcg(p + TOPC * DM), y3 = __ldcg(p + 3 * TOPC * DM / 2);
    const float rs = bfr(rcp(1.0f + ex2(-1.4426950408889634f * bf_hi(key ^ ((int)key < 0 ? 0x80000000u : 0xFFFF0000u)))));
    const uint32_t y = pack2((y0.x + y1.x) + (y2.x + y3.x), (y0.y + y1.y) + (y2.y + y3.y));
    const uint32_t u = pack2(bf_lo(y) * rs, bf_hi(y) * rs);
    *at<uint32_t>(cx.gs->gate, ((qb * 8 + hs) * 144 + ((i & 1) ? 128 + (row & 15) : row & 127)) * 128 + (o & 127)) = silu2(add2(t, u));
  }
  proxy_fence();
  bar_sync(BAR_OA, 352);
  if (elect_one()) {
    const uint32_t bar = cx.sb + SM_BAR_XG;
    mbar_expect_tx(bar, 2 * 144 * 128);
    bulk_load(cx.sb + SM_GO, cx.gs->gate + (qb * 8 + hs) * (144 * 8), 144 * 128, bar);
#pragma unroll 1
    for (int i = 0; i < 9; i++) tma2d_stream(cx.sb + SM_XO + i * 2048, tmX16, i < 8 ? hs * 64 : 512, qb * 128 + (i < 8 ? i : hs) * 16, bar);
  }
  __syncwarp();
  const uint4* src = cx.gs->part + (qb * 64 + 56 + hs) * 1024;
#pragma unroll 1
  for (int n = 0; n < (1 << 16); n++) {
    __nanosleep(n ? 400 : 700);
    uint32_t a, b, d, t;
    ld_gran(at<const uint4>(src, (lane & 7) * 2048 + 2032), a, b, d, t);
    if (__all_sync(0xffffffffu, ((a >> 16) ^ e) & 1)) break;
  }
  if (elect_one()) {
    mbar_expect_tx(cx.sb + SM_BAR_P8, 16384);
    bulk_load(cx.sb + SM_P8, src, 16384, cx.sb + SM_BAR_P8);
  }
  __syncwarp();
}
__device__ __forceinline__ void attn_finish8(const Ctx& cx, int qb, int hs, int hw, int lane, __nv_bfloat16* out) {
  const uint32_t tag = *(const uint32_t*)(cx.sp + SM_TAG);
  mbar_wait(cx.sb + SM_BAR_P8, 0);
  mbar_wait(cx.sb + SM_BAR_XG, 0);
#pragma unroll 1
  for (int g = 2 - hw; g < 4; g += 3) {
    float acc[8] = {0.f, 0.f, 0.f, 0.f, 0.f, 0.f, 0.f, 0.f};
    uint32_t a[4];
#pragma unroll 1
    for (uint32_t o = g * 512 + lane * 16; o < 16384; o += 2048) {
      lds128(cx.sb + SM_P8 + o, a[0], a[1], a[2], a[3]);
#pragma unroll 1
      for (int n = 0; n < (1 << 16) && __any_sync(0xffffffffu, (a[0] & TAG_BIT) != tag); n++)
        ld_gran(at<const uint4>(cx.gs->part, (qb * 64 + 56 + hs) * 16384 + o), a[0], a[1], a[2], a[3]);
      a[0] &= ~TAG_BIT;
#pragma unroll
      for (int j = 0; j < 4; j++) { acc[2 * j] += bf_lo(a[j]); acc[2 * j + 1] += bf_hi(a[j]); }
    }
    asm volatile("" : "+r"(lane));
    const uint32_t tile = cx.sb + SM_XO + (128 + (lane & 15)) * 128 + (((lane >> 4) ^ (lane & 7)) << 4);
    uint32_t b[4];
    ldsm4((tile ^ (g << 5)) + STAGE, a[0], a[1], a[2], a[3]);
    ldsm4(tile ^ (g << 5), b[0], b[1], b[2], b[3]);
    stsm4(tile ^ (g << 5), fma2(pack2(acc[0], acc[1]), a[0], b[0]), fma2(pack2(acc[2], acc[3]), a[1], b[1]),
          fma2(pack2(acc[4], acc[5]), a[2], b[2]), fma2(pack2(acc[6], acc[7]), a[3], b[3]));
  }
  bar_sync(BAR_ROWS, 96);
#pragma unroll 1
  for (int ch = threadIdx.x - 32; ch < 128; ch += 96)
    *at<uint4>(out, ((qb * 128 + hs * 16 + (ch >> 3)) * DM + 512 + (ch & 7) * 8) * 2) =
        *(const uint4*)(cx.sp + SM_XO + (128 + (ch >> 3)) * 128 + (((ch ^ (ch >> 3)) & 7) << 4));
}

constexpr float SUM_HI = 1.8446744e19f, SUM_LO = 9.0949470e-13f;

__device__ __forceinline__ void softmax_shift(float (&s)[64], float n0, float n1) {
#pragma unroll
  for (int i = 0; i < 64; i++) s[i] += (i & 2) ? n1 : n0;
}
template <int LO, int HI>
__device__ __forceinline__ void softmax_exp(float (&s)[64]) {
#pragma unroll
  for (int i = LO; i < HI; i++) s[i] = ex2(s[i]);
}
__device__ __forceinline__ void row_sums(const uint32_t (&pf)[32], float& l0, float& l1) {
  uint32_t t[16];
#pragma unroll
  for (int i = 0; i < 16; i++) t[i] = add2(pf[(i >> 1) * 4 + (i & 1)], pf[(i >> 1) * 4 + 2 + (i & 1)]);
#pragma unroll
  for (int i = 0; i < 8; i++) t[i] = add2(t[(i >> 1) * 4 + (i & 1)], t[(i >> 1) * 4 + 2 + (i & 1)]);
#pragma unroll
  for (int i = 0; i < 4; i++) t[i] = add2(t[(i >> 1) * 4 + (i & 1)], t[(i >> 1) * 4 + 2 + (i & 1)]);
  l0 += (bf_lo(t[0]) + bf_lo(t[2])) + (bf_hi(t[0]) + bf_hi(t[2]));
  l1 += (bf_lo(t[1]) + bf_lo(t[3])) + (bf_hi(t[1]) + bf_hi(t[3]));
}
__device__ __forceinline__ void softmax_redo(uint32_t (&pf)[32], const uint32_t (&q)[32], const __nv_bfloat16* kblk, int lane, float& n0,
                                             float& n1, float& l0, float& l1, float& sc0, float& sc1) {
  float x0 = -n0, x1 = -n1;
#pragma unroll 1
  for (int u = 0; u < 16; u++) {
    const uint32_t* kp = (const uint32_t*)(kblk + ((u & 7) * 16 + (lane >> 2)) * DH) + (lane & 3);
    float d[2][4] = {};
#pragma unroll
    for (int k = 0; k < 16; k++)
      hmma_k16(d[k & 1], q[2 * (k & 14)], q[2 * (k & 14) + 1], q[2 * (k & 14) + 2], q[2 * (k & 14) + 3],
               kp[(k & 1) * 4 * DH + (k >> 1) * 8], kp[(k & 1) * 4 * DH + (k >> 1) * 8 + 4]);
    if (u < 8) {
      x0 = fmaxf(fmaxf(x0, fmaxf(d[0][0], d[0][1])), fmaxf(d[1][0], d[1][1]));
      x1 = fmaxf(fmaxf(x1, fmaxf(d[0][2], d[0][3])), fmaxf(d[1][2], d[1][3]));
      if (u == 7) {
#pragma unroll
        for (int m = 1; m < 4; m <<= 1) {
          x0 = fmaxf(x0, __shfl_xor_sync(0xffffffffu, x0, m));
          x1 = fmaxf(x1, __shfl_xor_sync(0xffffffffu, x1, m));
        }
        sc0 = ex2(-x0 - n0);
        sc1 = ex2(-x1 - n1);
        n0 = -x0;
        n1 = -x1;
        l0 *= sc0;
        l1 *= sc1;
      }
    } else {
#pragma unroll
      for (int i = 0; i < 28; i++) pf[i] = pf[i + 4];
#pragma unroll
      for (int i = 0; i < 4; i++) {
        const float n = (i & 1) ? n1 : n0;
        pf[28 + i] = pack2(ex2(d[i >> 1][(i & 1) * 2] + n), ex2(d[i >> 1][(i & 1) * 2 + 1] + n));
        ((i & 1) ? l1 : l0) += bf_lo(pf[28 + i]) + bf_hi(pf[28 + i]);
      }
    }
  }
}

__device__ __forceinline__ void attn_consumer(const Ctx& cx, int qb, int hs, int wg, int cw, int lane, const __nv_bfloat16* x,
                                              const __nv_bfloat16* kc, __nv_bfloat16* out) {
  const uint32_t full = cx.sb + SM_FULL;
  const uint32_t ring = cx.sb + SM_RING;
  uint32_t lo = ((cw & 3) * 16 + (lane & 15)) * 128 + (((lane >> 4) ^ (lane & 7)) << 4);
  const uint32_t slot = cx.sb + SM_SLOT + wg * 16384;
  auto frag = [&](int sl, int k) { return ((slot + sl * STAGE + lo) ^ ((k & 3) << 5)) + (k >> 2) * 8192; };
  auto park = [&](const float (&a)[64], int sl, int k0, int k1, float f0, float f1) {
#pragma unroll
    for (int k = 0; k < 8; k++)
      if (k >= k0 && k < k1)
        stsm4(frag(sl, k), pack2(a[8 * k] * f0, a[8 * k + 1] * f0), pack2(a[8 * k + 2] * f1, a[8 * k + 3] * f1),
              pack2(a[8 * k + 4] * f0, a[8 * k + 5] * f0), pack2(a[8 * k + 6] * f1, a[8 * k + 7] * f1));
  };
  const bool signaller = lane == 0 && (cw & 3) < 2;
  int my_turn = 1 + wg, other_turn = 2 - wg;

  uint32_t pf[32], q[32], empty_c;
  float o[64], l0, l1;
  {
    uint32_t xa[144];
    float rstd0, rstd1;
    {
      const uint32_t xb = cx.sb + SM_X + wg * 73728, xf = cx.sb + SM_XFULL + wg * 96;
      float sm[4][4] = {};
      prof(wg, 0);
      empty_c = mapa(cx.sb + SM_EMPTY, cw & 1);
      mbar_wait(xf, 0);
      if ((threadIdx.x & 127) == 0) profc(wg, 30);
      ln_fetch<0, 12>(xa, xb, lo);
      mbar_wait(xf + 8, 0);
      ln_fetch<12, 24>(xa, xb, lo);
      ln_sums<0, 12>(xa, sm);
      mbar_wait(xf + 16, 0);
      if ((threadIdx.x & 127) == 0) profc(wg, 1);
      ln_fetch<24, 36>(xa, xb, lo);
      ln_sums<12, 36>(xa, sm);
      block_fence(36);
      if (wg) bar_arrive(other_turn, 256);
      block_fence(35);
      rstd0 = ((sm[0][0] + sm[1][0]) + (sm[2][0] + sm[3][0])) * (1.0f / DM);
      rstd1 = ((sm[0][2] + sm[1][2]) + (sm[2][2] + sm[3][2])) * (1.0f / DM);
    }
    const uint32_t mm0 = pack2(rstd0, rstd0), mm1 = pack2(rstd1, rstd1);
    rstd0 -= bf_lo(mm0);
    rstd1 -= bf_lo(mm1);
    rstd0 *= rstd0 * (-0.25f * DM);
    rstd1 *= rstd1 * (-0.25f * DM);
    auto ln_finish = [&]() {
      rstd0 += __shfl_xor_sync(0xffffffffu, rstd0, 1); rstd1 += __shfl_xor_sync(0xffffffffu, rstd1, 1);
      rstd0 += __shfl_xor_sync(0xffffffffu, rstd0, 2); rstd1 += __shfl_xor_sync(0xffffffffu, rstd1, 2);
      rstd0 = ln_rstd(rstd0 * (1.0f / DM)) * SM_SCALE_LOG2;
      rstd1 = ln_rstd(rstd1 * (1.0f / DM)) * SM_SCALE_LOG2;
    };
    ln_centre(xa, 0, X_C0, mm0, mm1, rstd0, rstd1);
    if (wg == 0) {
      bar_sync(4, 128);
      if (signaller) {
        asm volatile("mbarrier.arrive.shared::cluster.b64 _, [%0], 2;" ::"r"(empty_c + 16) : "memory");
        asm volatile("mbarrier.arrive.shared::cluster.b64 _, [%0], 2;" ::"r"(empty_c + 24) : "memory");
      }
      block_fence(37);
      pin(xa);
      ln_centre(xa, X_C0, X_C1, mm0, mm1, rstd0, rstd1);
    }
    pin(xa);
    if ((threadIdx.x & 127) == 0) profc(wg, 2);

    extern __shared__ __align__(1024) uint8_t smem_q[];
    const uint32_t ring = smem_u32(smem_q) + SM_RING;
    auto release = [&](int st) { if (signaller) mbar_arrive_cluster(empty_c + 8 * (st & 3)); };
    auto q_stage = [&](float (&acc)[64], int st, int i, int last) {
      mbar_wait(full + 8 * (st & 3), (st >> 2) & 1);
      if (i != (wg ? last : 1)) bar_sync(my_turn, 256);
      wg_fence();
      const uint64_t db = mkdesc(ring + (st & 3) * STAGE, 16384);
#pragma unroll
      for (int k = 0; k < 8; k++) {
        const int kb = (i < 3 ? 8 * i : 8 * i - 4) + k;
        if (i != 2 || k < 4) mma_n128<1>(acc, xa[4 * kb], xa[4 * kb + 1], xa[4 * kb + 2], xa[4 * kb + 3], db + k * 128, kb > 0);
      }
      wg_commit();
      if (i != (wg ? last - 1 : 0)) bar_arrive(other_turn, 256);
    };
    auto q_release = [&](int st, int i, int last) {
      if (i == 1 || i == last) {
        wg_wait<1>();
        if (i == last || !wg) release(st - 1);
      }
      if (i != last - 1 && (i || wg)) {
        wg_wait<0>();
        release(st);
      }
    };
    {
      float (&acc)[64] = o;
#pragma unroll 1
      for (int p = 0; p < 2; p++) {
#pragma unroll
        for (int i = 0; i < 5; i++) {
          q_stage(acc, 5 * p + i, i, 4);
          if (p == 0 && i != 3) {
            if (i == 0 && wg) bar_arrive(BAR_HELPER, 160);
            if ((wg || i) && i < 3) ln_centre(xa, i == 0 ? X_C0 : i == 1 ? X_C1 : X_C2, i == 0 ? X_C1 : i == 1 ? X_C2 : 72, mm0, mm1, rstd0, rstd1);
            if (i == 4) ln_finish();
            pin(xa);
          }
          q_release(5 * p + i, i, 4);
        }
        pin(acc);
#pragma unroll
        for (int k = 0; k < 8; k += 2) {
          park(acc, p, k, k + 2, rstd0, rstd1);
          if (k < 6) block_fence(40 + k);
        }
      }
    }
    {
      float (&h)[32] = *(float (*)[32])&o[0];
#pragma unroll
      for (int i = 0; i < 3; i++) {
        const uint32_t sl = (10 + i) & 3;
        mbar_wait(full + 8 * sl, ((10 + i) >> 2) & 1);
        if (i != (wg ? 2 : 1)) bar_sync(my_turn, 256);
        wg_fence();
#pragma unroll
        for (int k = 0; k < 16 - 4 * i; k++) {
          const int kb = (i == 2 ? 28 : 16 * i) + k;
          const uint64_t db = mkdesc(ring + sl * STAGE, 16) + (i == 2 && k >= 4 ? k + 4 : k) * 128;
          mma_n64<1>(h, xa[4 * kb], xa[4 * kb + 1], xa[4 * kb + 2], xa[4 * kb + 3], db, kb > 0);
        }
        wg_commit();
        if (i != (wg ? 1 : 0)) bar_arrive(other_turn, 256);
        q_release(10 + i, i, 2);
      }
      pin(h);
      park(o, 2, 0, 2, rstd0, rstd1);
      block_fence(49);
      park(o, 2, 2, 4, rstd0, rstd1);
    }
#pragma unroll
    for (int i = 0; i < 4; i++) {
      q_stage(o, 13 + i, i, 3);
      q_release(13 + i, i, 3);
    }
    prof(wg, 6);
#pragma unroll
    for (int i = 0; i < 32; i++) pf[i] = xa[112 + i];
    l0 = 0.25f * rcp(rstd0);
    l1 = 0.25f * rcp(rstd1);
  }

  uint32_t oa[96];
  const uint32_t zero = __shfl_sync(0xffffffffu, blockIdx.y, lane);
  my_turn = __shfl_sync(0xffffffffu, my_turn, lane);
  other_turn = __shfl_sync(0xffffffffu, other_turn, lane);
  lo = __shfl_sync(0xffffffffu, lo, lane);
  {
    float s[64], n0 = 0.f, n1 = 0.f;
    float lp0, lp1;
    float i0 = 0.f, i1 = 0.f;
    bool redo, shift = false;
    auto turn = [&](int it, auto kc_) -> bool {
      constexpr int KIND = decltype(kc_)::value;
      constexpr uint32_t slk = KIND == 1 ? SL_KO : SL_KE, slv = KIND == 1 ? SL_VO : SL_VE, slkn = KIND == 1 ? SL_KE : SL_KO;
      constexpr int SPLIT = KIND == 3 ? X_SPLIT3 : X_SPLIT, PARK1 = X_PARK;
      const uint32_t par = ((it + NST_Q / 2) >> 1) & 1;
      const int hsl = max((it >> 4) - 1, 0);
      const uint64_t dk = mkdesc(ring + slk * STAGE, 16), dv = mkdesc(ring + slv * STAGE, 16384);
      auto qk = [&]() {
#pragma unroll
        for (int k = 0; k < 8; k++) {
          if (KIND == 3) mma_n128_ss<0>(s, mkdesc(slot + hsl * STAGE, 16) + (k >> 2) * 512 + (k & 3) * 2, dk + (k >> 2) * 1024 + (k & 3) * 2, k > 0);
          else mma_n128<0>(s, q[4 * k], q[4 * k + 1], q[4 * k + 2], q[4 * k + 3], dk + (k >> 2) * 1024 + (k & 3) * 2, k > 0);
        }
        wg_commit();
      };
      auto pv = [&]() {
#pragma unroll
        for (int k = 0; k < 8; k++)
          mma_n128<1>(o, pf[4 * k], pf[4 * k + 1], pf[4 * k + 2], pf[4 * k + 3], dv + k * 128, k > 0 || KIND != 1 || (it & 15) != 1);
        wg_commit();
      };
      lp0 = l0; lp1 = l1;
#define TS(i)
      {
        TS(0)
        if (KIND == 3) {
          asm volatile("fence.proxy.async.shared::cta;" ::: "memory");
          const float t0 = lp0 + __shfl_xor_sync(0xffffffffu, lp0, 1), t1 = lp1 + __shfl_xor_sync(0xffffffffu, lp1, 1);
          i0 = rcp(t0 + __shfl_xor_sync(0xffffffffu, t0, 2));
          i1 = rcp(t1 + __shfl_xor_sync(0xffffffffu, t1, 2));
          asm volatile("" : "+f"(i0), "+f"(i1)::"memory");
          block_fence(31, zero);
#pragma unroll
          for (int k = 0; k < X_N1; k++) ldsm4(frag(hsl, k), q[4 * k], q[4 * k + 1], q[4 * k + 2], q[4 * k + 3]);
        }
        bar_sync(my_turn, 256);
        TS(1)
        if (KIND != 3) pin(q);
        pin(pf); pin(o);
        wg_fence();
        qk();
        TS(2)
        mbar_wait(full + 8 * slv, par);
        if (KIND == 1 && (it & 15) == 1) {
          park(o, hsl, PARK1, 8, i0, i1);
          wg_fence();
        }
        if (KIND == 3) {
#pragma unroll
          for (int k = X_N1; k < 8; k++) ldsm4(frag(hsl, k), q[4 * k], q[4 * k + 1], q[4 * k + 2], q[4 * k + 3]);
          block_fence(32, zero);
        }
        TS(3)
        pv();
        bar_arrive(other_turn, 256);
        TS(4)
        wg_wait<1>();
      }
      pin(s);
      mbar_arrive_cluster_now<10 * KIND + 3>(empty_c + 8 * slk, signaller, zero);
      TS(5)
      if (KIND == 3) {
        shift = false;
        n0 = n1 = l0 = l1 = 0.f;
      } else if (shift) {
        softmax_shift(s, n0, n1);
        pin(s);
      }
      softmax_exp<0, SPLIT>(s);
      pin(s);
      block_fence(10 * KIND + 4, zero);
      TS(6)
      wg_wait<0>();
      pin(o); pin(pf);
      mbar_arrive_cluster_now<10 * KIND + 5>(empty_c + 8 * slv, signaller, zero);
      TS(7)
      const bool kready = mbar_test(full + 8 * slkn, par);
      softmax_exp<SPLIT, 64>(s);
#pragma unroll
      for (int i = 0; i < 32; i++) pf[i] = pack2(s[2 * i], s[2 * i + 1]);
      row_sums(pf, l0, l1);
      if (KIND == 3) {
        park(o, hsl, 0, PARK1, i0, i1);
        if (it) prof(wg, 6 + (it >> 4));
        if (it >= 32 && cw == 0) bar_arrive(BAR_HELPER, 64);
      }
      redo = !(l0 + l1 <= SUM_HI) || (KIND == 3 && fminf(l0, l1) < SUM_LO);
      const bool leave = __any_sync(0xffffffffu, redo || !kready);
      return leave;
    };
    int it = -1;
#pragma unroll 1
    while (true) {
      mbar_wait(full + 8 * ((it & 1) ? SL_KE : SL_KO), ((it + NST_Q / 2) >> 1) & 1);
      it++;
#pragma unroll 1
      while (true) {
        if (it & 1) {
          if (turn(it, IC<1>()) || it == 63) break;
          it++;
        }
        if (it & 15) {
          if (turn(it, IC<2>())) break;
        } else {
          if (turn(it, IC<3>())) break;
        }
        it++;
      }
      if (__any_sync(0xffffffffu, redo)) {
        const int j = it & 15;
        float sc0 = 1.f, sc1 = 1.f;
        if (j == 0) n0 = n1 = 3.0e38f;
        l0 = j ? lp0 : 0.f;
        l1 = j ? lp1 : 0.f;
        softmax_redo(pf, q, kc + (size_t)((hs * 2 + (it >> 5)) * SEQ + j * 128) * DH, lane, n0, n1, l0, l1, sc0, sc1);
        shift = true;
        if (j == 0) sc0 = sc1 = 1.f;
#pragma unroll
        for (int i = 0; i < 16; i++) { o[4 * i] *= sc0; o[4 * i + 1] *= sc0; o[4 * i + 2] *= sc1; o[4 * i + 3] *= sc1; }
      }
      if (it == 63) break;
    }
  }

#define TE(i) {}
  {
    constexpr int ST0 = NST_Q + NST_KV;
    float acc[32], red[32], first[32];
    uint32_t tag;
    uint4* xch;
    auto await = [&](int st) { mbar_wait(full + 8 * (st & 3), (st >> 2) & 1); };
    auto release = [&](int st) { if (signaller) mbar_arrive_cluster(empty_c + 8 * (st & 3)); };
    auto unpark = [&](int h, int k0, int k1) {
#pragma unroll
      for (int k = 0; k < 8; k++)
        if (k >= k0 && k < k1) ldsm4(frag(h, k), oa[32 * h + 4 * k], oa[32 * h + 4 * k + 1], oa[32 * h + 4 * k + 2], oa[32 * h + 4 * k + 3]);
    };
    {
      float ar[64];
      asm volatile("fence.proxy.async.shared::cta;" ::: "memory");
      l0 += __shfl_xor_sync(0xffffffffu, l0, 1); l1 += __shfl_xor_sync(0xffffffffu, l1, 1);
      l0 += __shfl_xor_sync(0xffffffffu, l0, 2); l1 += __shfl_xor_sync(0xffffffffu, l1, 2);
      float f0 = rcp(l0), f1 = rcp(l1);
      asm volatile("" : "+f"(f0), "+f"(f1)::"memory");
      await(ST0 - 1);
      unpark(1, 0, 4);
      bar_sync(my_turn, 256);
      pin(pf); pin(o);
      wg_fence();
#pragma unroll
      for (int k = 0; k < 8; k++)
        mma_n128<1>(o, pf[4 * k], pf[4 * k + 1], pf[4 * k + 2], pf[4 * k + 3], mkdesc(ring + SL_KE * STAGE, 16384) + k * 128, 1);
      wg_commit();
      await(ST0);
      unpark(1, 4, 8);
      block_fence(61, zero);
#pragma unroll
      for (int k = 0; k < 8; k++) mma_n128_ss<1>(ar, mkdesc(slot, 16) + (k >> 2) * 512 + (k & 3) * 2, mkdesc(ring + (ST0 & 3) * STAGE, 16384) + k * 128, k > 0);
      wg_commit();
      bar_arrive(other_turn, 256);
      wg_wait<1>();
      pin(o); pin(pf);
      mbar_arrive_cluster_now<62>(empty_c + 8 * SL_KE, signaller, zero);
#pragma unroll
      for (int i = 0; i < 16; i++) {
        pf[2 * i] = pack2(o[4 * i] * f0, o[4 * i + 1] * f0);
        pf[2 * i + 1] = pack2(o[4 * i + 2] * f1, o[4 * i + 3] * f1);
      }
      pin(pf);
      prof(wg, 10);
#pragma unroll
      for (int u = 1; u < 4; u++) {
        await(ST0 + u);
        wg_wait<0>();
        release(ST0 + u - 1);
        bar_sync(my_turn, 256);
        wg_fence();
#pragma unroll
        for (int k = 0; k < 8; k++) {
          const uint32_t* a = (u == 1 ? oa + 32 : u == 2 ? pf : oa + 64) + 4 * k;
          mma_n128<1>(ar, a[0], a[1], a[2], a[3], mkdesc(ring + ((ST0 + u) & 3) * STAGE, 16384) + k * 128, 1);
        }
        wg_commit();
        bar_arrive(other_turn, 256);
        if (u < 3) {
          block_fence(62 + u, zero);
          unpark(u == 1 ? 2 : 0, 0, 8);
        }
      }
      mbar_wait(cx.sb + SM_BAR_MISC, 0);
      tag = *(const volatile uint32_t*)(cx.sp + SM_TAG);
      xch = at<uint4>(cx.gs->part, (qb << 20) + lane * 16 + zero);
      tag = __shfl_sync(0xffffffffu, tag, lane);
      await(ST0 + 4);
      wg_wait<0>();
      release(ST0 + 3);
      pin(ar);
#pragma unroll
      for (int i = 0; i < 32; i++) { first[i] = ar[i]; red[i] = ar[32 + i]; }
    }
    auto send = [&](const float (&v)[32], int dst, int idx) {
      uint4* p = at<uint4>(xch, (dst * 8 + idx) * 2048);
#pragma unroll
      for (int i = 0; i < 4; i++)
        st_gran(p + i * 32, (pack2(v[8 * i], v[8 * i + 1]) & ~TAG_BIT) | tag, pack2(v[8 * i + 2], v[8 * i + 3]),
                pack2(v[8 * i + 4], v[8 * i + 5]), pack2(v[8 * i + 6], v[8 * i + 7]));
    };
    send(first, ((hs + 1) & 7) * 7, cw);
    int nrx = 1;
    auto half_step = [&](int s, auto hc, bool arrive) {
      constexpr int h = decltype(hc)::value;
      const int st = ST0 + 2 * s + h;
      const uint64_t db = mkdesc(ring + (st & 3) * STAGE, 16);
      bar_sync(my_turn, 256);
      if (h == 0) pin(pf);
#pragma unroll
      for (int i = 32 * h; i < 32 + 64 * h; i++) asm volatile("" : "+r"(oa[i])::"memory");
      wg_fence();
#pragma unroll
      for (int k = 0; k < 16; k++) {
        const int kb = h * 16 + k - 8;
        if (kb >= 0) mma_n64<1>(acc, oa[4 * kb], oa[4 * kb + 1], oa[4 * kb + 2], oa[4 * kb + 3], db + k * 128, 1);
        else mma_n64<1>(acc, pf[4 * k], pf[4 * k + 1], pf[4 * k + 2], pf[4 * k + 3], db + k * 128, k > 0);
      }
      wg_commit();
      if (arrive) bar_arrive(other_turn, 256);
    };
    auto source = [&](int n) { return at<const uint4>(xch, ((hs * 7 + n - 1) * 8 + cw) * 2048); };
    auto fetch = [&](uint32_t (&g)[16], const uint4* p) {
#pragma unroll
      for (int i = 0; i < 4; i++) ld_gran(p + i * 32, g[4 * i], g[4 * i + 1], g[4 * i + 2], g[4 * i + 3]);
    };
    uint32_t g[16];
#pragma unroll 1
    for (int s = 2; s < 8; s++) {
      const int st = ST0 + 2 * s;
      half_step(s, IC<0>(), true);
      if (s == 2) {
        bar_arrive(BAR_OA, 352);
        send(red, 56 + cw, hs);
#pragma unroll
        for (int i = 0; i < 32; i++) red[i] = 0.f;
      }
      await(st + 1);
      if (s > 3 && granules_ok(g, tag)) { add_granules(red, g); nrx++; }
      wg_wait<0>();
      if (s < 7) release(st);
      if (s > 2) fetch(g, source(nrx));
      half_step(s, IC<1>(), true);
      await(st + 2);
      wg_wait<0>();
      if (s < 7) release(st + 1);
      pin(acc);
      if (s == 7) prof(wg, 19);
      send(acc, ((hs + s) & 7) * 7 + s - 1, cw);
    }
    TE(1)
    uint32_t xv[16], gt[16];
    {
      const int s = 8;
      uint32_t g2[16];
      half_step(s, IC<0>(), true);
      TE(2)
      await(NST_Q + NST_KV + NST_O - 1);
      cluster_arrive();
      mbar_wait(cx.sb + SM_BAR_XG, 0);
      const uint32_t tile = cx.sb + SM_XO + wg * 8192 + lo;
      if (granules_ok(g, tag)) { add_granules(red, g); nrx++; }
      fetch(g, source(nrx));
      block_fence(58, zero);
      wg_wait<0>();
      TE(3)
#pragma unroll
      for (int k = 0; k < 4; k++) ldsm4((tile ^ (k << 5)) + STAGE, gt[4 * k], gt[4 * k + 1], gt[4 * k + 2], gt[4 * k + 3]);
      half_step(s, IC<1>(), wg == 0);
      TE(4)
      block_fence(56, zero);
      const bool ok = granules_ok(g, tag);
      block_fence(57, zero + ok * 1000);
      const uint4* src = source(7);
      fetch(g2, src);
#pragma unroll
      for (int k = 0; k < 4; k++) ldsm4(tile ^ (k << 5), xv[4 * k], xv[4 * k + 1], xv[4 * k + 2], xv[4 * k + 3]);
      if (ok) { add_granules(red, g); nrx++; }
      TE(5)
      block_fence(59, zero);
      wg_wait<0>();
      pin(acc);
      TE(6)
#pragma unroll
      for (int i = 0; i < 32; i++) red[i] += acc[i];
      pin(red);
      TE(7)
      int n = 7;
#pragma unroll 1
      for (int spins = 0; spins < (1 << 16); spins++) {
        if (granules_ok(g2, tag)) {
          add_granules(red, g2);
          if (--n < nrx) {
            break;
          }
          src -= 1024;
        }
        fetch(g2, src);
      }
      TE(8)
    }
    prof(wg, 20);
    TE(9)
    const uint32_t ot = ring + ((ST0 + NST_O) & 3) * STAGE + cw * (16 * 144);
    uint32_t ow[16];
#pragma unroll
    for (int i = 0; i < 16; i++) ow[i] = fma2(pack2(red[2 * i], red[2 * i + 1]), gt[i], xv[i]);
#pragma unroll
    for (int i = 0; i < 4; i++)
      stsm4(ot + (lane & 15) * 144 + (2 * i + (lane >> 4)) * 16, ow[4 * i], ow[4 * i + 1], ow[4 * i + 2], ow[4 * i + 3]);
    __syncwarp();
#pragma unroll
    for (int i = 0; i < 4; i++) {
      uint4 v;
      lds128(ot + (i * 4 + (lane >> 3)) * 144 + (lane & 7) * 16, v.x, v.y, v.z, v.w);
      at<uint4>(out, ((qb * 128 + cw * 16 + (lane >> 3)) * DM + hs * 64 + (lane & 7) * 8) * 2)[i * (4 * DM / 8)] = v;
    }
    TE(10)
    prof(wg, 22);
  }
}

constexpr int AST_X = 6, AST_F = AST_X + 96;
__device__ __forceinline__ void aux_producer(const Ctx& cx, int f, const CUtensorMap* tmWq, const CUtensorMap* tmG) {
  const uint32_t full = cx.sb + SM_FULL, empty = cx.sb + SM_EMPTY;
  __nanosleep(3000);
  if (elect_one()) {
#pragma unroll 1
    for (int st = 0; st < AST_X; st++) {
      mbar_expect_tx(full + 8 * st, FSTAGE);
#pragma unroll
      for (int i = 0; i < 3; i++)
        tma2d_stream(cx.sb + st * FSTAGE + i * 8192, tmWq, (2 * f + (st & 1)) * 512 + 448, (st >> 1) * 192 + i * 64, full + 8 * st);
    }
  }
  __syncwarp();
  mbar_wait(cx.sb + SM_BAR_MISC, 0);
  proxy_fence();
  int st = AST_X;
#pragma unroll 1
  for (; st < AST_F; st++) {
    const uint32_t sl = st & 7;
    mbar_wait(empty + 8 * sl, ((st >> 3) & 1) ^ 1);
    if (elect_one()) {
      mbar_expect_tx(full + 8 * sl, FSTAGE);
      bulk_load(cx.sb + sl * FSTAGE, cx.gs->xn + (st - AST_X) * (FSTAGE / 16), FSTAGE, full + 8 * sl);
    }
    __syncwarp();
  }
#pragma unroll 1
  for (int pair = 0; pair < 14; pair++) {
#pragma unroll 1
    for (int u = 0; u < 12; u++, st++) {
      const uint32_t sl = st & 7;
      const int unit = pair * 2 + (u & 1), k = u >> 1;
      if (unit == 27) continue;
      const bool gu = pair < 9;
      mbar_wait(empty + 8 * sl, ((st >> 3) & 1) ^ 1);
      if (elect_one()) {
        mbar_expect_tx(full + 8 * sl, FSTAGE);
        tma2d_stream(cx.sb + sl * FSTAGE, tmG + (gu ? k >= 3 : 2), gu ? f * 1152 + unit * 64 : (unit - 18) * 64,
                     gu ? (k >= 3 ? k - 3 : k) * 192 : f * 1152 + k * 192, full + 8 * sl);
      }
      __syncwarp();
    }
  }
}

constexpr int BAR_FREE = 4, BAR_TILE = 6;
__device__ __forceinline__ void aux_helper(const Ctx& cx, int f, int warp, int lane) {
  unsigned epoch = 0;
  if (lane == 0) epoch = cx.gs->launch[blockIdx.x] + 1;
  epoch = __shfl_sync(0xffffffffu, epoch, 0);
  bar_sync(BAR_OA, 96);
  if (warp == 3) {
    if (lane == 0) cx.gs->launch[blockIdx.x] = epoch;
    await_count(at<const unsigned>(cx.gs->rows, (lane & 15) * 128), 8 * epoch, 200);
    if (lane == 0) mbar_arrive(cx.sb + SM_BAR_MISC);
    prof(0, 1, 31);
    await_count(at<const unsigned>(cx.gs->rows, (lane & 15) * 128 + 4), 8 * epoch, 500);
    uint32_t bound = 0xFFFFFFFFu, m0 = 0, m1 = 0;
#pragma unroll 1
    for (int k = 0; k < TOPC; k++) {
      if (__any_sync(0xffffffffu, m0 == 0)) {
        m0 = m1 = 0;
#pragma unroll 2
        for (int i = 0; i < 16; i++) {
          const uint4 v = __ldcg(at<const uint4>(cx.gs->key, lane * 16 + i * 512));
          const uint32_t w[4] = {v.x, v.y, v.z, v.w};
#pragma unroll
          for (int j = 0; j < 4; j++) {
            const uint32_t t = w[j] <= bound ? w[j] : 0;
            m1 = max(m1, min(m0, t));
            m0 = max(m0, t);
          }
        }
      }
      uint32_t m = m0;
      m = __reduce_max_sync(0xffffffffu, m);
      bound = m - 1;
      if (m0 == m) { m0 = m1; m1 = 0; }
      if (f == 0 && lane == 0) *at<uint32_t>(cx.gs->top, k * 4) = m;
#pragma unroll
      for (int j = 0; j < 3; j++) {
        const uint32_t row = 0xFFFF - (m & 0xFFFF), i = min(j * 4 + (lane >> 3), 8);
        *(uint4*)(cx.sp + SM_XSEL + i * 1024 + k * 128 + (((lane ^ k) & 7) << 4)) =
            __ldcg(at<const uint4>(cx.gs->xn, xn_offset(row, (lane & 7) * 4) + i * 8192));
      }
    }
    asm volatile("fence.proxy.async.shared::cta;" ::: "memory");
    prof(0, 2, 31);
  } else {
    const int wg = warp - 1;
#pragma unroll 1
    for (int u = 0; u < 32; u++) {
      bar_arrive(BAR_FREE + wg, 160);
      bar_sync(BAR_TILE + wg, 160);
      if (elect_one()) {
        const int n = (u >> 1) * 8 + 2 * f + wg;
        asm volatile("cp.async.bulk.global.shared::cta.bulk_group [%0], [%1], 8192;\ncp.async.bulk.commit_group;\ncp.async.bulk.wait_group 0;"
                     ::"l"(cx.gs->q3 + (n * 2 + (u & 1)) * 512), "r"(cx.sb + SM_H + wg * 8192) : "memory");
        if (u & 1) st_release(&cx.gs->q3_flag[n], epoch);
      }
      __syncwarp();
    }
  }
  bar_arrive(3, 352);
}

__device__ __forceinline__ void aux_consumer(const Ctx& cx, int f, int wg, int cw, int lane) {
  const int r = lane >> 2, c = lane & 3, tid = cw * 32 + lane;
  const uint32_t full = cx.sb + SM_FULL, empty = cx.sb + SM_EMPTY;
  const bool signaller = (tid & 127) == 0;
  auto await = [&](int st) { mbar_wait(full + 8 * (st & 7), (st >> 3) & 1); };
  auto release = [&](int st, int cnt) {
    asm volatile("{\n.reg .pred p;\nsetp.ne.u32 p, %2, 0;\n@p mbarrier.arrive.shared::cta.b64 _, [%0], %1;\n}"
                 ::"r"(empty + 8 * (st & 7)), "r"(cnt), "r"((uint32_t)signaller) : "memory");
  };
  prof(wg, 0);
  {
    const uint32_t lt = ((lane & 7) + (lane >> 4) * 8) * 128 + ((((cw & 3) * 2 + ((lane >> 3) & 1)) ^ (lane & 7)) << 4);
    uint32_t wa[144];
#pragma unroll
    for (int i = 0; i < 3; i++) {
      await(2 * i + wg);
#pragma unroll
      for (int k = 0; k < 12; k++) {
        const int kb = 12 * i + k;
        ldsm4t(cx.sb + (2 * i + wg) * FSTAGE + k * 2048 + lt, wa[4 * kb], wa[4 * kb + 1], wa[4 * kb + 2], wa[4 * kb + 3]);
      }
    }
    bar_sync(1, 256);
#pragma unroll
    for (int i = 0; i < 3; i++) release(2 * i + wg, 2);
    if (wg) bar_arrive(1, 256);
#pragma unroll 1
    for (int st = AST_X; st < AST_F; st += 3) {
      float acc[32];
      await(st);
      await(st + 1);
      await(st + 2);
      bar_sync(1 + wg, 256);
      wg_fence();
#pragma unroll
      for (int kb = 0; kb < 36; kb++) {
        const int i = kb / 12, k = kb % 12;
        mma_n64<0>(acc, wa[4 * kb], wa[4 * kb + 1], wa[4 * kb + 2], wa[4 * kb + 3],
                   mkdesc(cx.sb + ((st + i) & 7) * FSTAGE, 16) + (k >> 2) * 512 + (k & 3) * 2, kb > 0);
        if (k == 11) wg_commit();
      }
      if (st < AST_F - 3 || !wg) bar_arrive(2 - wg, 256);
      wg_wait<1>();
      release(st, 1);
      release(st + 1, 1);
      bar_sync(BAR_FREE + wg, 160);
      wg_wait<0>();
      pin(acc);
      release(st + 2, 1);
#pragma unroll
      for (int k = 0; k < 4; k++)
        stsm4t(cx.sb + SM_H + wg * 8192 + k * 2048 + lt, pack2(acc[8 * k] * SM_SCALE_LOG2, acc[8 * k + 1] * SM_SCALE_LOG2),
               pack2(acc[8 * k + 2] * SM_SCALE_LOG2, acc[8 * k + 3] * SM_SCALE_LOG2),
               pack2(acc[8 * k + 4] * SM_SCALE_LOG2, acc[8 * k + 5] * SM_SCALE_LOG2),
               pack2(acc[8 * k + 6] * SM_SCALE_LOG2, acc[8 * k + 7] * SM_SCALE_LOG2));
      asm volatile("fence.proxy.async.shared::cta;" ::: "memory");
      bar_arrive(BAR_TILE + wg, 160);
    }
    bar_sync(3, 352);
  }
  prof(wg, 3);
#pragma unroll 1
  for (int unit = wg; unit < 27; unit += 2) {
    if (unit >> 1 == 9) {
      asm volatile("fence.proxy.async.shared::cta;" ::: "memory");
      bar_sync(3, 256);
      prof(wg, 4);
    }
    const bool gu = unit < 18;
    float a0[4], a1[4];
#pragma unroll 1
    for (int m = 0; m < 2; m++) {
      float p0[4], p1[4];
      int st = AST_F + (unit >> 1) * 12 + m * 6 + wg;
      uint32_t b = cx.sb + (gu ? SM_XSEL : SM_H + m * 9216);
#pragma unroll 1
      for (int u = 0; u < 3; u++, st += 2, b += 3072) {
        await(st);
        wg_fence();
        const uint64_t da = mkdesc(cx.sb + (st & 7) * FSTAGE, 16), db = mkdesc(b, 16);
#pragma unroll
        for (int k = 0; k < 12; k++) mma_n8((k & 1) ? p1 : p0, da + k * 128, db + (k >> 2) * 64 + (k & 3) * 2, u > 0 || k > 1);
        wg_commit();
        wg_wait<1>();
        if (u) release(st - 2, 2);
      }
      wg_wait<0>();
      release(st - 2, 2);
      pin(p0); pin(p1);
#pragma unroll
      for (int i = 0; i < 4; i++) { a0[i] = a1[i]; a1[i] = p0[i] + p1[i]; }
    }
#pragma unroll
    for (int i = 0; i < 4; i++) {
      const int fl = (cw & 3) * 16 + r + (i >> 1) * 8, tok = 2 * c + (i & 1);
      if (gu) {
        const float h = bfr(silu_f(bfr(a0[i]))) * bfr(a1[i]);
        *(__nv_bfloat16*)(cx.sp + SM_H + unit * 1024 + tok * 128 + (((fl >> 3) ^ tok) << 4) + (fl & 7) * 2) = __float2bfloat16_rn(h);
      } else {
        *at<float>(cx.gs->ypart, ((f * TOPC + tok) * DM + (unit - 18) * 64 + fl) * 4) = a0[i] + a1[i];
      }
    }
  }
  prof(wg, 5);
  bar_sync(3, 256);
  if (tid == 0) red_release(&cx.gs->ycnt);
  prof(wg, 6);
}

struct Maps { CUtensorMap m[9]; };
__global__ void __cluster_dims__(2, 1, 1) __launch_bounds__(THREADS, 1)
fused_kernel(const __nv_bfloat16* __restrict__ x, const __nv_bfloat16* __restrict__ w_r, const __nv_bfloat16* __restrict__ kc,
             const __nv_bfloat16* __restrict__ wo, __nv_bfloat16* __restrict__ out, Scratch* gs,
             const __grid_constant__ Maps maps) {
  const CUtensorMap &tmX = maps.m[0], &tmWq = maps.m[1], &tmK = maps.m[2], &tmV = maps.m[3], &tmWo = maps.m[4];
  extern __shared__ __align__(1024) uint8_t smem_raw[];
  prof(0, 23, 511);
  if (threadIdx.x < 72 && blockIdx.x < N_ATT_CTA)
    asm volatile("prefetch.global.L2 [%0];" ::"l"(at<const void>(x, ((blockIdx.x >> 3) * 128 + (blockIdx.x & 7) * 8) * (DM * 2) + threadIdx.x * 128)));
  Ctx cx;
  cx.sb = smem_u32(smem_raw);
  cx.sp = smem_raw;
  cx.gs = gs;
  cx.rank = blockIdx.x & 1;
  const int warp = __shfl_sync(0xffffffffu, threadIdx.x >> 5, 0);
  const int cluster = blockIdx.x >> 1;
  const bool is_aux = blockIdx.x >= N_ATT_CTA;
  const int c7 = ((cluster - 36) * 37) >> 8;
  const int hs = cluster < 4 ? 4 + cluster : cluster < 36 ? (cluster - 4) >> 3 : 4 + c7;
  const int qb = (cluster < 4 ? 0 : cluster < 36 ? (cluster - 4) & 7 : cluster - 35 - 7 * c7) * 2 + cx.rank;

  extern __shared__ __align__(1024) uint8_t smem_alias[];
  const uint32_t xf = smem_u32(smem_alias) + SM_MISC + warp * 24;
  if (warp == 4 && elect_one()) prefetch_tmap(&tmX);
  if (elect_one()) {
    const uint32_t cnt = (warp > 4 && warp < 8) ? (is_aux ? 2 : 4) : 1;
#pragma unroll
    for (int i = 0; i < 3; i++) mbar_init(xf + 8 * i, cnt);
    asm volatile("fence.proxy.async.shared::cta;" ::: "memory");
    asm volatile("fence.mbarrier_init.release.cluster;" ::: "memory");
  }
  __syncwarp();
  cluster_arrive();
  if (warp == 4 && !is_aux) {
    if (elect_one()) {
      profc(0, 28);
#pragma unroll
      for (int i = 0; i < 3; i++) {
        mbar_expect_tx(xf + 8 * i, 24576);
        tma3d(xf - SM_XFULL + SM_X + i * 24576, &tmX, qb * 128, i * 3, xf + 8 * i);
      }
      profc(0, 29);
    }
  } else if (warp > 7 && elect_one()) {
    prefetch_tmap(&tmX + (is_aux ? warp - 4 : warp == 8 ? 8 : warp - 8));
  }
  __syncwarp();

  if (warp < 4) {
    asm volatile("setmaxnreg.dec.sync.aligned.u32 24;");
    cluster_wait();
    prof(0, 24, 511);
    if (warp == 0) {
      if (!is_aux) attn_producer(cx, qb, hs, &tmX, &tmK, &tmV, &tmWq, &tmWo);
      else aux_producer(cx, blockIdx.x - N_ATT_CTA, &tmWq, &maps.m[5]);
      prof(0, 25, 511);
    } else if (!is_aux) {
      attn_rows(cx, qb, hs, 3 - warp, read_lane(), &maps.m[8], w_r);
      if (warp == 1) attn_helper(cx, qb, hs, read_lane(), wo, &maps.m[8]);
      else bar_sync(BAR_OA, 352);
      attn_finish8(cx, qb, hs, warp - 1, read_lane(), out);
    } else {
      aux_helper(cx, blockIdx.x - N_ATT_CTA, warp, read_lane());
    }
    __syncwarp();
    cluster_arrive();
    cluster_wait();
    if (threadIdx.x == 32) { dly(cx, 201); dly(cx, 251); }
  } else {
    asm volatile("setmaxnreg.inc.sync.aligned.u32 240;");
    cluster_wait();
    const int cw = warp - 4, wg = cw >> 2;
    if (is_aux) aux_consumer(cx, blockIdx.x - N_ATT_CTA, wg, cw, read_lane());
    else attn_consumer(cx, qb, hs, wg, cw, read_lane(), x, kc, out);
  }
}

typedef CUresult (*EncodeFn)(CUtensorMap*, CUtensorMapDataType, cuuint32_t, void*, const cuuint64_t*, const cuuint64_t*,
                             const cuuint32_t*, const cuuint32_t*, CUtensorMapInterleave, CUtensorMapSwizzle,
                             CUtensorMapL2promotion, CUtensorMapFloatOOBfill);

void encode(EncodeFn fn, CUtensorMap* m, const void* p, int rank, const cuuint64_t* dims, const cuuint64_t* strides,
            const cuuint32_t* box) {
  const cuuint32_t es[5] = {1, 1, 1, 1, 1};
  fn(m, CU_TENSOR_MAP_DATA_TYPE_BFLOAT16, rank, const_cast<void*>(p), dims, strides, box, es, CU_TENSOR_MAP_INTERLEAVE_NONE,
     CU_TENSOR_MAP_SWIZZLE_128B, CU_TENSOR_MAP_L2_PROMOTION_L2_128B, CU_TENSOR_MAP_FLOAT_OOB_FILL_NONE);
}
void encode2d(EncodeFn fn, CUtensorMap* m, const void* p, uint64_t rows, uint64_t cols, uint32_t box_rows) {
  const cuuint64_t dims[2] = {cols, rows}, strides[1] = {cols * 2};
  const cuuint32_t box[2] = {64, box_rows};
  encode(fn, m, p, 2, dims, strides, box);
}

}

extern "C" void kernel_launch(void* const* d_in, const int* in_sizes, int n_in, void* d_out, int out_size) {
  (void)in_sizes; (void)n_in; (void)out_size;
  void* fnp = nullptr;
  cudaDriverEntryPointQueryResult qr;
  cudaGetDriverEntryPoint("cuTensorMapEncodeTiled", &fnp, cudaEnableDefault, &qr);
  EncodeFn fn = (EncodeFn)fnp;
  void* gs = nullptr;
  cudaGetSymbolAddress(&gs, g_scratch);
  Maps maps;
  CUtensorMap &tmX = maps.m[0], &tmWq = maps.m[1], &tmK = maps.m[2], &tmV = maps.m[3], &tmWo = maps.m[4], &tmG = maps.m[5],
              &tmU = maps.m[6], &tmD = maps.m[7];
  encode2d(fn, &tmK, d_in[1], 16 * SEQ, DH, 128);
  encode2d(fn, &tmV, d_in[2], 16 * SEQ, DH, 128);
  encode2d(fn, &tmWq, d_in[3], DM, 4096, 64);
  {
    const cuuint64_t dims[3] = {64, SEQ, 9}, strides[2] = {DM * 2, 128};
    const cuuint32_t box[3] = {64, 64, 3};
    encode(fn, &tmX, d_in[0], 3, dims, strides, box);
  }
  encode2d(fn, &maps.m[8], d_in[0], SEQ, DM, 16);
  encode2d(fn, &tmWo, d_in[4], 4096, DM, 128);
  encode2d(fn, &tmG, d_in[7], DM, FF, 192);
  encode2d(fn, &tmU, d_in[8], DM, FF, 192);
  encode2d(fn, &tmD, d_in[9], FF, DM, 192);
  cudaFuncSetAttribute(fused_kernel, cudaFuncAttributeMaxDynamicSharedMemorySize, SM_TOTAL);
  fused_kernel<<<N_CTA, THREADS, SM_TOTAL>>>((const __nv_bfloat16*)d_in[0], (const __nv_bfloat16*)d_in[6], (const __nv_bfloat16*)d_in[1],
                                            (const __nv_bfloat16*)d_in[4], (__nv_bfloat16*)d_out, (Scratch*)gs, maps);
}
```

```cpp
#include <cuda_runtime.h>
#include <cuda_bf16.h>
#include <cuda.h>
#include <stdint.h>

namespace {

constexpr int SEQ = 2048, DM = 576, DH = 128, FF = 4608, TOPC = 8;
constexpr int N_ATT_CTA = 128, N_CTA = 132;
constexpr int THREADS = 384;

constexpr uint32_t SM_RING = 0;
constexpr uint32_t STAGE = 32768;
constexpr uint32_t SM_SLOT = 131072;
constexpr uint32_t FSTAGE = 24576;
constexpr uint32_t SM_XSEL = 196608;
constexpr uint32_t SM_H = 205824;
constexpr uint32_t SM_MISC = 229376;
constexpr uint32_t SM_FULL = SM_MISC, SM_BAR_MISC = SM_MISC + 64, SM_BAR_XG = SM_MISC + 72, SM_BAR_P8 = SM_MISC + 80, SM_BAR_Q3 = SM_MISC + 88, SM_XFULL = SM_MISC + 96,
                   SM_EMPTY = SM_MISC + 120, SM_BAR_ROWS = SM_MISC + 216, SM_TAG = SM_MISC + 288,
                   SM_ROWS = SM_MISC + 304, SM_BOX8 = SM_MISC + 1024;
constexpr uint32_t SM_TOTAL = SM_MISC + 3072;
constexpr uint32_t SM_X = SM_MISC - 147456;

constexpr int BAR_ROWS = 6, BAR_HELPER = 7, BAR_OA = 8;
constexpr int NST_Q = 18, NST_KV = 128, NST_O = 18;
constexpr uint32_t SL_KE = (NST_Q - 1) & 3, SL_VE = NST_Q & 3, SL_KO = (NST_Q + 1) & 3, SL_VO = (NST_Q + 2) & 3;
#define X_N1 5
#define X_SPLIT 44
#define X_SPLIT3 38
#define X_PARK 5
#define X_C0 24
#define X_C1 32
#define X_C2 56
constexpr float SM_SCALE_LOG2 = 0.08838834764831845f * 1.4426950408889634f;

struct Scratch {
  uint4 part[16 * 64 * 2 * 4 * 128];
  uint4 gate[N_ATT_CTA * 144 * 8];
  uint4 q3[N_ATT_CTA * 1024];
  uint4 xn[SEQ * DM / 8];
  uint32_t key[SEQ];
  float ypart[4 * TOPC * DM];
  uint32_t top[32];
  unsigned launch[160];
  unsigned rows[16 * 32];
  unsigned q3_flag[N_ATT_CTA];
  unsigned ycnt;
};
__device__ __align__(1024) Scratch g_scratch;

__device__ __forceinline__ void prof(int, int, int = 0) {}
__device__ __forceinline__ void profc(int, int) {}

__device__ __forceinline__ uint32_t smem_u32(const void* p) { return (uint32_t)__cvta_generic_to_shared(p); }
__device__ __forceinline__ void mbar_init(uint32_t bar, uint32_t cnt) {
  asm volatile("mbarrier.init.shared::cta.b64 [%0], %1;" ::"r"(bar), "r"(cnt) : "memory");
}
__device__ __forceinline__ void mbar_expect_tx(uint32_t bar, uint32_t bytes) {
  asm volatile("mbarrier.arrive.expect_tx.shared::cta.b64 _, [%0], %1;" ::"r"(bar), "r"(bytes) : "memory");
}
__device__ __forceinline__ void mbar_arrive(uint32_t bar) {
  asm volatile("mbarrier.arrive.shared::cta.b64 _, [%0];" ::"r"(bar) : "memory");
}
__device__ __forceinline__ void mbar_arrive_cluster(uint32_t bar_cluster_addr) {
  asm volatile("mbarrier.arrive.shared::cluster.b64 _, [%0];" ::"r"(bar_cluster_addr) : "memory");
}
template <int ID>
__device__ __forceinline__ void mbar_arrive_cluster_now(uint32_t bar_cluster_addr, bool pred, uint32_t zero) {
  asm volatile("{\n.reg .pred p, q;\nsetp.ne.u32 p, %1, 0;\nsetp.eq.u32 q, %2, %3;\n"
               "ARR_LOOP:\n@p mbarrier.arrive.shared::cluster.b64 _, [%0];\n@q bra.uni ARR_LOOP;\n}"
               ::"r"(bar_cluster_addr), "r"((uint32_t)pred), "r"(zero), "n"(ID) : "memory");
}
__device__ __forceinline__ void block_fence(int id, uint32_t zero = blockIdx.y) {
  asm volatile("{\n.reg .pred q;\nsetp.eq.u32 q, %0, %1;\nBF_LOOP:\n@q st.volatile.shared.u32 [%0], %0;\n@q bra.uni BF_LOOP;\n}"
               ::"r"(zero), "r"(id) : "memory");
}
__device__ __forceinline__ bool mbar_test(uint32_t bar, uint32_t parity) {
  uint32_t ok;
  asm volatile("{\n.reg .pred p;\nmbarrier.test_wait.parity.shared::cta.b64 p, [%1], %2;\nselp.u32 %0, 1, 0, p;\n}"
               : "=r"(ok) : "r"(bar), "r"(parity) : "memory");
  return ok;
}
__device__ __forceinline__ void mbar_wait(uint32_t bar, uint32_t parity) {
  asm volatile("{\n.reg .pred p, q;\n.reg .u32 n;\nmov.u32 n, 0;\n"
               "WAIT_LOOP:\nmbarrier.try_wait.parity.shared::cta.b64 p, [%0], %1;\n"
               "add.u32 n, n, 1;\nsetp.lt.u32 q, n, 4194304;\nand.pred q, q, !p;\n@q bra WAIT_LOOP;\n}"
               ::"r"(bar), "r"(parity) : "memory");
}
__device__ __forceinline__ uint32_t mapa(uint32_t addr, uint32_t rank) {
  uint32_t r;
  asm volatile("mapa.shared::cluster.u32 %0, %1, %2;" : "=r"(r) : "r"(addr), "r"(rank));
  return r;
}
__device__ __forceinline__ void cluster_arrive() { asm volatile("barrier.cluster.arrive.relaxed.aligned;" ::: "memory"); }
__device__ __forceinline__ bool elect_one() {
  uint32_t p;
  asm volatile("{\n.reg .pred p;\nelect.sync _|p, 0xffffffff;\nselp.u32 %0, 1, 0, p;\n}" : "=r"(p));
  return p;
}
__device__ __forceinline__ int read_lane() { return threadIdx.x & 31; }
__device__ __forceinline__ void cluster_wait() { asm volatile("barrier.cluster.wait.acquire.aligned;" ::: "memory"); }
__device__ __forceinline__ void bar_sync(int id, int n) { asm volatile("barrier.cta.sync %0, %1;" ::"r"(id), "r"(n) : "memory"); }
__device__ __forceinline__ void bar_arrive(int id, int n) { asm volatile("barrier.cta.arrive %0, %1;" ::"r"(id), "r"(n) : "memory"); }

__device__ __forceinline__ uint64_t policy_evict_first() {
  uint64_t p;
  asm("createpolicy.fractional.L2::evict_first.b64 %0, 1.0;" : "=l"(p));
  return p;
}
__device__ __forceinline__ uint64_t policy_evict_normal() {
  uint64_t p;
  asm("createpolicy.fractional.L2::evict_normal.b64 %0, 1.0;" : "=l"(p));
  return p;
}
__device__ __forceinline__ void tma3d(uint32_t dst, const CUtensorMap* tm, int c1, int c2, uint32_t bar) {
  asm volatile("cp.async.bulk.tensor.3d.shared::cluster.global.mbarrier::complete_tx::bytes [%0], [%1, {%2, %3, %4}], [%5];"
               ::"r"(dst), "l"(tm), "r"(0), "r"(c1), "r"(c2), "r"(bar) : "memory");
}
__device__ __forceinline__ void tma2d(uint32_t dst, const CUtensorMap* tm, int c0, int c1, uint32_t bar) {
  asm volatile("cp.async.bulk.tensor.2d.shared::cluster.global.mbarrier::complete_tx::bytes [%0], [%1, {%2, %3}], [%4];"
               ::"r"(dst), "l"(tm), "r"(c0), "r"(c1), "r"(bar) : "memory");
}
__device__ __forceinline__ void tma2d_stream(uint32_t dst, const CUtensorMap* tm, int c0, int c1, uint32_t bar) {
  asm volatile("{\n.reg .b64 pol;\ncreatepolicy.fractional.L2::evict_first.b64 pol, 1.0;\n"
               "cp.async.bulk.tensor.2d.shared::cluster.global.mbarrier::complete_tx::bytes.L2::cache_hint [%0], [%1, {%2, %3}], [%4], pol;\n}"
               ::"r"(dst), "l"(tm), "r"(c0), "r"(c1), "r"(bar) : "memory");
}
__device__ __forceinline__ void tma2d_prefetch(const CUtensorMap* tm, int c0, int c1) {
  asm volatile("cp.async.bulk.prefetch.tensor.2d.L2.global [%0, {%1, %2}];" ::"l"(tm), "r"(c0), "r"(c1) : "memory");
}
__device__ __forceinline__ void prefetch_l2(const void* p, uint32_t bytes) {
  asm volatile("cp.async.bulk.prefetch.L2.global [%0], %1;" ::"l"(p), "r"(bytes) : "memory");
}
__device__ __forceinline__ void prefetch_tmap(const CUtensorMap* tm) {
  asm volatile("prefetch.tensormap [%0];" ::"l"(tm) : "memory");
}

__device__ __forceinline__ void wg_fence() { asm volatile("wgmma.fence.sync.aligned;" ::: "memory"); }
__device__ __forceinline__ void wg_commit() { asm volatile("wgmma.commit_group.sync.aligned;" ::: "memory"); }
template <int N> __device__ __forceinline__ void wg_wait() { asm volatile("wgmma.wait_group.sync.aligned %0;" ::"n"(N) : "memory"); }

__device__ __forceinline__ uint64_t mkdesc(uint32_t addr, uint32_t lbo_bytes) {
  return (uint64_t)(((addr & 0x3FFFF) >> 4) | ((lbo_bytes >> 4) << 16)) | ((uint64_t)0x40000040u << 32);
}
template <int N> __device__ __forceinline__ void pin(float (&a)[N]) {
#pragma unroll
  for (int i = 0; i < N; i++) asm volatile("" : "+f"(a[i])::"memory");
}
template <int N> __device__ __forceinline__ void pin(uint32_t (&a)[N]) {
#pragma unroll
  for (int i = 0; i < N; i++) asm volatile("" : "+r"(a[i])::"memory");
}

#define F8(d, o) "+f"(d[o]), "+f"(d[o + 1]), "+f"(d[o + 2]), "+f"(d[o + 3]), "+f"(d[o + 4]), "+f"(d[o + 5]), "+f"(d[o + 6]), "+f"(d[o + 7])
#define R32A "%0, %1, %2, %3, %4, %5, %6, %7, %8, %9, %10, %11, %12, %13, %14, %15, %16, %17, %18, %19, %20, %21, %22, %23, %24, %25, %26, %27, %28, %29, %30, %31"
#define R32B "%32, %33, %34, %35, %36, %37, %38, %39, %40, %41, %42, %43, %44, %45, %46, %47, %48, %49, %50, %51, %52, %53, %54, %55, %56, %57, %58, %59, %60, %61, %62, %63"

template <int TB>
__device__ __forceinline__ void mma_n128(float (&d)[64], uint32_t a0, uint32_t a1, uint32_t a2, uint32_t a3, uint64_t db, int acc) {
  asm volatile("{\n.reg .pred p;\nsetp.ne.b32 p, %69, 0;\n"
               "wgmma.mma_async.sync.aligned.m64n128k16.f32.bf16.bf16 {" R32A ", " R32B "}, {%64, %65, %66, %67}, %68, p, 1, 1, %70;\n}\n"
               : F8(d, 0), F8(d, 8), F8(d, 16), F8(d, 24), F8(d, 32), F8(d, 40), F8(d, 48), F8(d, 56)
               : "r"(a0), "r"(a1), "r"(a2), "r"(a3), "l"(db), "r"(acc), "n"(TB));
}
template <int TB>
__device__ __forceinline__ void mma_n128_ss(float (&d)[64], uint64_t da, uint64_t db, int acc) {
  asm volatile("{\n.reg .pred p;\nsetp.ne.b32 p, %66, 0;\n"
               "wgmma.mma_async.sync.aligned.m64n128k16.f32.bf16.bf16 {" R32A ", " R32B "}, %64, %65, p, 1, 1, 0, %67;\n}\n"
               : F8(d, 0), F8(d, 8), F8(d, 16), F8(d, 24), F8(d, 32), F8(d, 40), F8(d, 48), F8(d, 56)
               : "l"(da), "l"(db), "r"(acc), "n"(TB));
}
template <int TB>
__device__ __forceinline__ void mma_n64(float (&d)[32], uint32_t a0, uint32_t a1, uint32_t a2, uint32_t a3, uint64_t db, int acc) {
  asm volatile("{\n.reg .pred p;\nsetp.ne.b32 p, %37, 0;\n"
               "wgmma.mma_async.sync.aligned.m64n64k16.f32.bf16.bf16 {" R32A "}, {%32, %33, %34, %35}, %36, p, 1, 1, %38;\n}\n"
               : F8(d, 0), F8(d, 8), F8(d, 16), F8(d, 24)
               : "r"(a0), "r"(a1), "r"(a2), "r"(a3), "l"(db), "r"(acc), "n"(TB));
}
__device__ __forceinline__ void mma_n8(float (&d)[4], uint64_t da, uint64_t db, int acc) {
  asm volatile("{\n.reg .pred p;\nsetp.ne.b32 p, %6, 0;\n"
               "wgmma.mma_async.sync.aligned.m64n8k16.f32.bf16.bf16 {%0, %1, %2, %3}, %4, %5, p, 1, 1, 1, 0;\n}\n"
               : "+f"(d[0]), "+f"(d[1]), "+f"(d[2]), "+f"(d[3])
               : "l"(da), "l"(db), "r"(acc));
}
__device__ __forceinline__ void hmma_k16(float (&d)[4], uint32_t a0, uint32_t a1, uint32_t a2, uint32_t a3, uint32_t b0, uint32_t b1) {
  asm volatile("mma.sync.aligned.m16n8k16.row.col.f32.bf16.bf16.f32 {%0, %1, %2, %3}, {%4, %5, %6, %7}, {%8, %9}, {%0, %1, %2, %3};"
               : "+f"(d[0]), "+f"(d[1]), "+f"(d[2]), "+f"(d[3]) : "r"(a0), "r"(a1), "r"(a2), "r"(a3), "r"(b0), "r"(b1));
}

__device__ __forceinline__ uint32_t pack2(float lo, float hi) {
  uint32_t r;
  asm("cvt.rn.bf16x2.f32 %0, %1, %2;" : "=r"(r) : "f"(hi), "f"(lo));
  return r;
}
__device__ __forceinline__ float bf_lo(uint32_t w) { return __uint_as_float(w << 16); }
__device__ __forceinline__ float bf_hi(uint32_t w) { return __uint_as_float(w & 0xFFFF0000u); }
__device__ __forceinline__ float bfr(float x) { return __uint_as_float(pack2(0.f, x)); }
__device__ __forceinline__ uint32_t sub2(uint32_t a, uint32_t b) {
  uint32_t r;
  asm("sub.rn.bf16x2 %0, %1, %2;" : "=r"(r) : "r"(a), "r"(b));
  return r;
}
__device__ __forceinline__ uint32_t add2(uint32_t a, uint32_t b) {
  uint32_t r;
  asm("add.rn.bf16x2 %0, %1, %2;" : "=r"(r) : "r"(a), "r"(b));
  return r;
}
__device__ __forceinline__ uint32_t mul2(uint32_t a, uint32_t b) {
  uint32_t r;
  asm("mul.rn.bf16x2 %0, %1, %2;" : "=r"(r) : "r"(a), "r"(b));
  return r;
}
__device__ __forceinline__ uint32_t fma2(uint32_t a, uint32_t b, uint32_t c) {
  uint32_t r;
  asm("fma.rn.bf16x2 %0, %1, %2, %3;" : "=r"(r) : "r"(a), "r"(b), "r"(c));
  return r;
}
__device__ __forceinline__ float ex2(float x) {
  float r;
  asm("ex2.approx.ftz.f32 %0, %1;" : "=f"(r) : "f"(x));
  return r;
}
__device__ __forceinline__ float rcp(float x) {
  float r;
  asm("rcp.approx.ftz.f32 %0, %1;" : "=f"(r) : "f"(x));
  return r;
}
__device__ __forceinline__ float silu_f(float t) { return t * rcp(1.0f + ex2(-1.4426950408889634f * t)); }
__device__ __forceinline__ void lds128(uint32_t a, uint32_t& x, uint32_t& y, uint32_t& z, uint32_t& w) {
  asm volatile("ld.shared.v4.u32 {%0, %1, %2, %3}, [%4];" : "=r"(x), "=r"(y), "=r"(z), "=r"(w) : "r"(a) : "memory");
}
__device__ __forceinline__ void ldsm4(uint32_t a, uint32_t& x, uint32_t& y, uint32_t& z, uint32_t& w) {
  asm volatile("ldmatrix.sync.aligned.m8n8.x4.shared.b16 {%0, %1, %2, %3}, [%4];" : "=r"(x), "=r"(y), "=r"(z), "=r"(w) : "r"(a) : "memory");
}
constexpr uint32_t TAG_BIT = 0x10000;
__device__ __forceinline__ void st_gran(uint4* p, uint32_t x, uint32_t y, uint32_t z, uint32_t w) {
  asm volatile("st.relaxed.gpu.global.v4.b32 [%0], {%1, %2, %3, %4};" ::"l"(p), "r"(x), "r"(y), "r"(z), "r"(w) : "memory");
}
__device__ __forceinline__ void ld_gran(const uint4* p, uint32_t& x, uint32_t& y, uint32_t& z, uint32_t& w) {
  asm volatile("ld.relaxed.gpu.global.v4.b32 {%0, %1, %2, %3}, [%4];" : "=r"(x), "=r"(y), "=r"(z), "=r"(w) : "l"(p) : "memory");
}
__device__ __forceinline__ void ldsm4t(uint32_t a, uint32_t& x, uint32_t& y, uint32_t& z, uint32_t& w) {
  asm volatile("ldmatrix.sync.aligned.m8n8.x4.trans.shared.b16 {%0, %1, %2, %3}, [%4];" : "=r"(x), "=r"(y), "=r"(z), "=r"(w) : "r"(a) : "memory");
}
__device__ __forceinline__ void stsm4t(uint32_t a, uint32_t x, uint32_t y, uint32_t z, uint32_t w) {
  asm volatile("stmatrix.sync.aligned.m8n8.x4.trans.shared.b16 [%0], {%1, %2, %3, %4};" ::"r"(a), "r"(x), "r"(y), "r"(z), "r"(w) : "memory");
}
__device__ __forceinline__ void stsm4(uint32_t a, uint32_t x, uint32_t y, uint32_t z, uint32_t w) {
  asm volatile("stmatrix.sync.aligned.m8n8.x4.shared.b16 [%0], {%1, %2, %3, %4};" ::"r"(a), "r"(x), "r"(y), "r"(z), "r"(w) : "memory");
}
template <class T>
__device__ __forceinline__ T* at(const void* base, uint32_t off) {
  uint64_t r;
  asm("{\n.reg .u32 lo, hi;\nmov.b64 {lo, hi}, %1;\nadd.cc.u32 lo, lo, %2;\naddc.u32 hi, hi, 0;\nmov.b64 %0, {lo, hi};\n}"
      : "=l"(r) : "l"(base), "r"(off));
  return (T*)__cvta_global_to_generic(r);
}
__device__ __forceinline__ void add_granules(float (&red)[32], const uint32_t (&g)[16]) {
#pragma unroll
  for (int i = 0; i < 16; i++) { red[2 * i] += bf_lo(g[i]); red[2 * i + 1] += bf_hi((i & 3) ? g[i] : g[i] & ~TAG_BIT); }
}
__device__ __forceinline__ bool granules_ok(const uint32_t (&g)[16], uint32_t tag) {
  uint32_t u, v;
  asm("lop3.b32 %0, %1, %2, %3, 0x7E;" : "=r"(u) : "r"(g[0]), "r"(g[4]), "r"(tag));
  asm("lop3.b32 %0, %1, %2, %3, 0x7E;" : "=r"(v) : "r"(g[8]), "r"(g[12]), "r"(tag));
  return __all_sync(0xffffffffu, ((u | v) & TAG_BIT) == 0);
}
__device__ __forceinline__ unsigned ld_acquire(const unsigned* p) {
  unsigned v;
  asm volatile("ld.acquire.gpu.global.u32 %0, [%1];" : "=r"(v) : "l"(p) : "memory");
  return v;
}
__device__ __forceinline__ void red_release(unsigned* p) {
  asm volatile("red.release.gpu.global.add.u32 [%0], 1;" ::"l"(p) : "memory");
}
__device__ __forceinline__ void st_release(unsigned* p, unsigned v) {
  asm volatile("st.release.gpu.global.u32 [%0], %1;" ::"l"(p), "r"(v) : "memory");
}

template <int K0, int K1>
__device__ __forceinline__ void ln_fetch(uint32_t (&xa)[144], uint32_t boxes, uint32_t lo) {
#pragma unroll
  for (int k = K0; k < K1; k++) ldsm4(((boxes + lo) ^ ((k & 3) << 5)) + (k >> 2) * 8192, xa[4 * k], xa[4 * k + 1], xa[4 * k + 2], xa[4 * k + 3]);
}
template <int K0, int K1>
__device__ __forceinline__ void ln_sums(const uint32_t (&xa)[144], float (&sm)[4][4]) {
#pragma unroll
  for (int k = K0; k < K1; k++) hmma_k16(sm[k & 3], xa[4 * k], xa[4 * k + 1], xa[4 * k + 2], xa[4 * k + 3], 0x3F803F80u, 0x3F803F80u);
}
__device__ __forceinline__ uint32_t sq8(const uint32_t* a) {
  uint32_t t, u;
  asm("mul.rn.bf16x2 %0, %1, %1;" : "=r"(t) : "r"(a[0]));
  asm("mul.rn.bf16x2 %0, %1, %1;" : "=r"(u) : "r"(a[2]));
#pragma unroll
  for (int i = 4; i < 16; i += 4) {
    asm("fma.rn.bf16x2 %0, %1, %1, %0;" : "+r"(t) : "r"(a[i]));
    asm("fma.rn.bf16x2 %0, %1, %1, %0;" : "+r"(u) : "r"(a[i + 2]));
  }
  return add2(t, u);
}
__device__ __forceinline__ void ln_centre(uint32_t (&xa)[144], int j0, int j1, uint32_t mm0, uint32_t mm1, float& sq0, float& sq1) {
#pragma unroll
  for (int j = 0; j < 72; j += 8)
    if (j >= j0 && j < j1) {
#pragma unroll
      for (int k = j; k < j + 8; k++) {
        xa[2 * k] = sub2(xa[2 * k], mm0);
        xa[2 * k + 1] = sub2(xa[2 * k + 1], mm1);
      }
      const uint32_t t0 = sq8(xa + 2 * j), t1 = sq8(xa + 2 * j + 1);
      sq0 += bf_lo(t0) + bf_hi(t0);
      sq1 += bf_lo(t1) + bf_hi(t1);
    }
}
__device__ __forceinline__ float ln_rstd(float var) {
  float sd;
  asm("sqrt.approx.ftz.f32 %0, %1;" : "=f"(sd) : "f"(bfr(bfr(fmaxf(var, 0.0f)) + 1e-5f)));
  return rcp(bfr(sd));
}
__device__ __forceinline__ uint32_t silu2(uint32_t t) { return pack2(silu_f(bf_lo(t)), silu_f(bf_hi(t))); }
__device__ __forceinline__ float sum8(float v) {
#pragma unroll
  for (int d = 4; d; d >>= 1) v += __shfl_xor_sync(0xffffffffu, v, d);
  return v;
}
__device__ __forceinline__ void await_count(const unsigned* p, unsigned target, unsigned sleep_ns) {
#pragma unroll 1
  for (int n = 0; n < (1 << 18) && __any_sync(0xffffffffu, (int)(ld_acquire(p) - target) < 0); n++) __nanosleep(sleep_ns);
}
__device__ __forceinline__ void bulk_load(uint32_t dst, const void* src, uint32_t bytes, uint32_t bar) {
  asm volatile("cp.async.bulk.shared::cluster.global.mbarrier::complete_tx::bytes [%0], [%1], %2, [%3];"
               ::"r"(dst), "l"(src), "r"(bytes), "r"(bar) : "memory");
}
__device__ __forceinline__ void proxy_fence() { asm volatile("fence.proxy.async;" ::: "memory"); }

template <int V> struct IC { static constexpr int value = V; };

struct Ctx {
  uint32_t sb;
  uint8_t* sp;
  uint32_t rank;
  Scratch* gs;
};

__device__ __forceinline__ void dly(const Ctx&, int) {}
__device__ __forceinline__ void load_box(uint32_t dst, const CUtensorMap* tm, int c0, int c1, uint32_t bar, uint64_t pol) {
  asm volatile("{\n.reg .pred p;\nelect.sync _|p, 0xffffffff;\n"
               "@p cp.async.bulk.tensor.2d.shared::cluster.global.mbarrier::complete_tx::bytes.multicast::cluster.L2::cache_hint"
               " [%0], [%1, {%2, %3}], [%4], %5, %6;\n}"
               ::"r"(dst), "l"(tm), "r"(c0), "r"(c1), "r"(bar), "h"((uint16_t)3), "l"(pol) : "memory");
}
template <int BOXES>
__device__ __forceinline__ void load_stage(uint32_t dst, const CUtensorMap* tm, int c0, int c1, uint32_t bar, uint32_t bytes, uint64_t pol) {
  asm volatile("{\n.reg .pred p;\nelect.sync _|p, 0xffffffff;\n"
               "@p mbarrier.arrive.expect_tx.shared::cta.b64 _, [%4], %7;\n"
               "@p cp.async.bulk.tensor.2d.shared::cluster.global.mbarrier::complete_tx::bytes.multicast::cluster.L2::cache_hint"
               " [%0], [%1, {%2, %3}], [%4], %5, %6;\n}"
               ::"r"(dst), "l"(tm), "r"(c0), "r"(c1), "r"(bar), "h"((uint16_t)3), "l"(pol), "r"(bytes) : "memory");
  if (BOXES == 2) load_box(dst + 8192, tm, c0, c1 + 64, bar, pol);
}
__device__ __forceinline__ void attn_producer(const Ctx& cx, int qb, int hs, const CUtensorMap* tmX, const CUtensorMap* tmK,
                                              const CUtensorMap* tmV, const CUtensorMap* tmWq, const CUtensorMap* tmWo) {
  const uint32_t full = cx.sb + SM_FULL, empty = cx.sb + SM_EMPTY, ring = cx.sb + SM_RING + cx.rank * 16384;
  const uint64_t keep = policy_evict_normal(), last_use = policy_evict_first();
  auto acquire = [&](int st) {
    mbar_wait(empty + 8 * (st & 3), ((st >> 2) ^ ((st & 3) >> 1) ^ 1) & 1);
    if (st > 3) dly(cx, st);
  };
  if (elect_one()) {
#pragma unroll
    for (int j = 0; j < 3; j++) {
      mbar_expect_tx(cx.sb + SM_XFULL + 96 + 8 * j, 24576);
      tma3d(cx.sb + SM_X + 73728 + j * 24576, tmX, qb * 128 + 64, j * 3, cx.sb + SM_XFULL + 96 + 8 * j);
    }
  }
  __syncwarp();
  const int c0 = cx.rank * 64;
#pragma unroll 1
  for (int st = 0; st < NST_Q - 1; st++) {
    const bool half = st >= 10 && st < 13;
    const int i = st - (st < 5 ? 0 : st < 10 ? 5 : half ? 10 : 13), sl = st & 3;
    const int n0 = (hs * 4 + (st < 5 ? 0 : st < 10 ? 2 : half ? 3 : 1)) * DH + (half ? 0 : c0);
    const int k0 = half ? (i < 2 ? 256 * i + 2 * c0 : 448 + c0) : (i < 3 ? 128 * i : 128 * i - 64);
    if (st == 1) mbar_wait(cx.sb + SM_XFULL + 16, 0);
    acquire(st);
    load_stage<1>(ring + sl * STAGE, tmWq, n0, k0, full + 8 * sl, i == 2 ? 16384 : (half && i) ? 24576 : 32768, last_use);
    if (i != 2 && !(half && i && c0)) load_box(ring + sl * STAGE + 8192, tmWq, n0, k0 + 64, full + 8 * sl, last_use);
    if ((st == 3 || st == 4 || st == 8) && elect_one()) {
      if (st != 4) tma2d_prefetch(tmWq, (hs * 4 + 2 - (st >> 3)) * DH + (qb & 1) * 64, (qb >> 1) * 64);
      else if (qb < 9) tma2d_prefetch(tmWq, (hs * 4 + 3) * DH, qb * 64);
    }
    __syncwarp();
  }
  int vrow = 0;
  uint64_t vpol = keep;
#pragma unroll 1
  for (int j = 0; j < 32; j++) {
    const int st = NST_Q - 1 + 4 * j, row = (hs * 2 + (j >> 4)) * SEQ + (j & 7) * 256;
    const uint64_t pol = (j & 8) ? last_use : keep;
    if (j < 7 && qb < 8 && elect_one()) tma2d_prefetch((qb & 4) ? tmV : tmK, (qb & 1) * 64, row + 256 + (qb & 2) * 64);
    __syncwarp();
    if (j == 24) mbar_wait(cx.sb + SM_BAR_Q3, 0);
    acquire(st);
    load_stage<1>(ring + SL_KE * STAGE, tmK, c0, row, full + 8 * SL_KE, 32768, pol);
    acquire(st + 1);
    if (j) load_stage<1>(ring + SL_VE * STAGE, tmV, c0, vrow, full + 8 * SL_VE, 32768, vpol);
    else load_stage<2>(ring + SL_VE * STAGE, tmWq, (hs * 4 + 1) * DH + c0, 448, full + 8 * SL_VE, 32768, last_use);
    vrow = row + 128;
    vpol = pol;
    acquire(st + 2);
    load_stage<1>(ring + SL_KO * STAGE, tmK, c0, vrow, full + 8 * SL_KO, 32768, pol);
    acquire(st + 3);
    load_stage<1>(ring + SL_VO * STAGE, tmV, c0, row, full + 8 * SL_VO, 32768, pol);
  }
  acquire(NST_Q + NST_KV - 1);
  load_stage<1>(ring + SL_KE * STAGE, tmV, c0, vrow, full + 8 * SL_KE, 32768, last_use);
#pragma unroll 1
  for (int u = 0; u < NST_O; u++) {
    const int st = NST_Q + NST_KV + u, sl = st & 3;
    const int blk = u < 4 && cx.rank ? 8 : ((hs + max(u >> 1, 1)) & 7);
    const int head = u < 4 ? u ^ (u >> 1) : ((u & 1) * 2 + cx.rank + 3) & 3;
    acquire(st);
    load_stage<1>(ring + sl * STAGE, tmWo, blk * 64, hs * 512 + head * 128, full + 8 * sl, 32768, last_use);
  }
}

__device__ __forceinline__ uint32_t xn_offset(uint32_t row, int lane) {
  return (row >> 6) * (9 * 8192) + (row & 63) * 128 + ((((lane >> 2) ^ row) & 7) << 4) + (lane & 3) * 4;
}

__device__ __forceinline__ void attn_rows(const Ctx& cx, int qb, int hs, int hw, int lane, const CUtensorMap* tmX16,
                                          const __nv_bfloat16* w_r) {
  extern __shared__ __align__(1024) uint8_t smem_rows[];
  auto box = [&](int blk) { return blk < 8 ? SM_SLOT + 2 * STAGE + 8192 + (blk >> 2) * 16384 + (blk & 3) * 2048 : SM_BOX8; };
  const uint32_t sb = smem_u32(smem_rows);
  if (hw == 0) {
    bar_sync(BAR_HELPER, 160);
    if (elect_one()) {
      mbar_expect_tx(sb + SM_BAR_ROWS, 9 * 2048);
#pragma unroll 1
      for (int i = 0; i < 9; i++) tma2d(sb + box(i), tmX16, i * 64, qb * 128 + hs * 16, sb + SM_BAR_ROWS);
    }
    __syncwarp();
  }
  uint32_t g = (lane >> 3) * 128 + (((lane ^ (lane >> 3)) & 7) << 4);
  auto next = [&]() {
    g = ((g + 512) & 2047) ^ 64;
    asm volatile("" : "+r"(g));
  };
  float* const part = (float*)(smem_rows + SM_ROWS);
  mbar_wait(sb + SM_BAR_ROWS, 0);
  if (hw == 0) dly(cx, 190);
#pragma unroll 1
  for (int i = 0; i < 4; i++) {
    float a = 0.f, b = 0.f;
#pragma unroll
    for (int j = 0; j < 3; j++) {
      const uint4 v = *(const uint4*)(smem_rows + box(hw * 3 + j) + g);
      const uint32_t w[4] = {v.x, v.y, v.z, v.w};
#pragma unroll
      for (int k = 0; k < 4; k++) {
        a += bf_lo(w[k]) + bf_hi(w[k]);
        b = fmaf(bf_lo(w[k]), bf_lo(w[k]), fmaf(bf_hi(w[k]), bf_hi(w[k]), b));
      }
    }
    a = sum8(a);
    b = sum8(b);
    float* p = part + hw * 16 + (g >> 7);
    p[0] = a;
    p[48] = b;
    next();
  }
  bar_sync(BAR_ROWS, 96);
  if (hw == 0) dly(cx, 191);
  {
    const float* p = part + (lane & 15);
    const float mean = (p[0] + p[16] + p[32]) * (1.0f / DM), rstd = ln_rstd((p[48] + p[64] + p[80]) * (1.0f / DM) - mean * mean);
    const uint32_t mm = pack2(mean, mean), rr = pack2(rstd - bfr(rstd), rstd);
#pragma unroll 1
    for (int u = hw * 12; u < hw * 12 + 12; u++) {
      const int blk = u >> 2;
      uint4* q = (uint4*)(smem_rows + box(blk) + g);
      uint4 v = *q;
      const uint32_t m = __shfl_sync(0xffffffffu, mm, g >> 7), r = __shfl_sync(0xffffffffu, rr, g >> 7);
      const uint32_t hi = __byte_perm(r, 0, 0x3232), lo = __byte_perm(r, 0, 0x1010);
      auto norm = [&](uint32_t w) {
        const uint32_t xc = sub2(w, m);
        return fma2(xc, hi, mul2(xc, lo));
      };
      v = make_uint4(norm(v.x), norm(v.y), norm(v.z), norm(v.w));
      *q = v;
      *at<uint4>(cx.gs->xn + ((qb * 2 + (hs >> 2)) * 9 + blk) * 512 + (hs & 3) * 128, g) = v;
      next();
    }
  }
  bar_sync(BAR_ROWS, 96);
  if (hw == 0) {
    dly(cx, 192);
    if (lane == 0) red_release(&cx.gs->rows[qb * 32]);
    dly(cx, 193);
  }
#pragma unroll 1
  for (int u = hw ? 13 * hw - 3 : 0; u < 13 * hw + 10; u++) {
    const int blk = u >> 2;
    const uint32_t o = (g + (u & 3) * 512) ^ ((u & 1) << 6);
    const uint4 v = *(const uint4*)(smem_rows + box(blk) + o);
    *at<uint4>(cx.gs->gate + (blk < 8 ? (qb * 8 + blk) * 144 + hs * 16 : (qb * 8 + hs) * 144 + 128) * 8, o) =
        make_uint4(silu2(v.x), silu2(v.y), silu2(v.z), silu2(v.w));
  }
  if (hw) dly(cx, 194 + hw);
  __nanosleep(5000);
#pragma unroll 1
  for (int blk = hw * 3; blk < hw * 3 + 3; blk++) {
    const uint4 c = __ldg(at<const uint4>(w_r, blk * 128 + ((g ^ (g >> 3)) & 0x70)));
#pragma unroll 1
    for (int i = 0; i < 4; i++) {
      const uint4 v = *(const uint4*)(smem_rows + box(blk) + g);
      part[blk * 16 + (g >> 7)] =
          sum8(fmaf(bf_lo(v.x), bf_lo(c.x), fmaf(bf_hi(v.x), bf_hi(c.x), fmaf(bf_lo(v.y), bf_lo(c.y), bf_hi(v.y) * bf_hi(c.y)))) +
               fmaf(bf_lo(v.z), bf_lo(c.z), fmaf(bf_hi(v.z), bf_hi(c.z), fmaf(bf_lo(v.w), bf_lo(c.w), bf_hi(v.w) * bf_hi(c.w)))));
      next();
    }
  }
  bar_sync(BAR_ROWS, 96);
  if (hw == 0) {
    dly(cx, 194);
    float d = 0.f;
#pragma unroll
    for (int j = 0; j < 9; j++) d += part[j * 16 + (lane & 15)];
    const uint32_t row = qb * 128 + hs * 16 + (lane & 15), b = pack2(0.f, d);
    *at<uint32_t>(cx.gs->key, row * 4) = (b ^ ((int)b < 0 ? 0xFFFF0000u : 0x80000000u)) + 0xFFFF - row;
    __syncwarp();
    if (lane == 0) red_release(&cx.gs->rows[qb * 32 + 1]);
  }
}

constexpr uint32_t SM_XO = SM_SLOT, SM_GO = SM_SLOT + STAGE, SM_P8 = SM_SLOT + 2 * STAGE;
__device__ __forceinline__ void attn_helper(const Ctx& cx, int qb, int hs, int lane, const __nv_bfloat16* wo, const CUtensorMap* tmX16) {
  unsigned e = 0;
  if (lane == 0) {
    e = cx.gs->launch[blockIdx.x];
    cx.gs->launch[blockIdx.x] = e + 1;
  }
  e = __shfl_sync(0xffffffffu, e, 0);
  if (lane == 0) {
    *(uint32_t*)(cx.sp + SM_TAG) = (~e & 1) * TAG_BIT;
    mbar_arrive(cx.sb + SM_BAR_MISC);
  }
  bar_sync(BAR_HELPER, 64);
  await_count(&cx.gs->rows[qb * 32 + 1], 8 * (e + 1), 1000);
  await_count(&cx.gs->q3_flag[qb * 8 + hs], e + 1, 1000);
  proxy_fence();
  if (elect_one()) {
    mbar_expect_tx(cx.sb + SM_BAR_Q3, 16384);
#pragma unroll
    for (int i = 0; i < 2; i++) bulk_load(cx.sb + SM_SLOT + 2 * STAGE + i * 16384 + 8192, cx.gs->q3 + (qb * 16 + hs * 2 + i) * 512, 8192, cx.sb + SM_BAR_Q3);
  }
  __syncwarp();
  bar_sync(BAR_HELPER, 64);
  prefetch_l2(at<const void>(wo, (hs * 512 + qb * 32 + lane) * (DM * 2)), DM * 2);
  await_count(&cx.gs->ycnt, 4 * (e + 1), 500);
  const uint32_t mykey = __ldcg(at<const uint32_t>(cx.gs->top, (lane >> 1) * 4)), myrow = 0xFFFF - (mykey & 0xFFFF);
#pragma unroll 1
  for (uint32_t todo = __ballot_sync(0xffffffffu, lane < 16 && ((lane & 1) ? myrow >> 4 == qb * 8 + hs : myrow >> 7 == qb)); todo; todo &= todo - 1) {
    const int i = __ffs(todo) - 1, blk = (i & 1) ? 8 : hs;
    const uint32_t key = __shfl_sync(0xffffffffu, mykey, i), row = 0xFFFF - (key & 0xFFFF), o = xn_offset(row, lane);
    const uint32_t t = __ldcg(at<const uint32_t>(cx.gs->xn, o + blk * 8192));
    const float2* p = at<const float2>(cx.gs->ypart, ((i >> 1) * DM + blk * 64 + 2 * lane) * 4);
    const float2 y0 = __ldcg(p), y1 = __ldcg(p + TOPC * DM / 2), y2 = __ldcg(p + TOPC * DM), y3 = __ldcg(p + 3 * TOPC * DM / 2);
    const float rs = bfr(rcp(1.0f + ex2(-1.4426950408889634f * bf_hi(key ^ ((int)key < 0 ? 0x80000000u : 0xFFFF0000u)))));
    const uint32_t y = pack2((y0.x + y1.x) + (y2.x + y3.x), (y0.y + y1.y) + (y2.y + y3.y));
    const uint32_t u = pack2(bf_lo(y) * rs, bf_hi(y) * rs);
    *at<uint32_t>(cx.gs->gate, ((qb * 8 + hs) * 144 + ((i & 1) ? 128 + (row & 15) : row & 127)) * 128 + (o & 127)) = silu2(add2(t, u));
  }
  proxy_fence();
  bar_sync(BAR_OA, 352);
  if (elect_one()) {
    const uint32_t bar = cx.sb + SM_BAR_XG;
    mbar_expect_tx(bar, 2 * 144 * 128);
    bulk_load(cx.sb + SM_GO, cx.gs->gate + (qb * 8 + hs) * (144 * 8), 144 * 128, bar);
#pragma unroll 1
    for (int i = 0; i < 9; i++) tma2d_stream(cx.sb + SM_XO + i * 2048, tmX16, i < 8 ? hs * 64 : 512, qb * 128 + (i < 8 ? i : hs) * 16, bar);
  }
  __syncwarp();
  const uint4* src = cx.gs->part + (qb * 64 + 56 + hs) * 1024;
#pragma unroll 1
  for (int n = 0; n < (1 << 16); n++) {
    __nanosleep(n ? 400 : 700);
    uint32_t a, b, d, t;
    ld_gran(at<const uint4>(src, (lane & 7) * 2048 + 2032), a, b, d, t);
    if (__all_sync(0xffffffffu, ((a >> 16) ^ e) & 1)) break;
  }
  if (elect_one()) {
    mbar_expect_tx(cx.sb + SM_BAR_P8, 16384);
    bulk_load(cx.sb + SM_P8, src, 16384, cx.sb + SM_BAR_P8);
  }
  __syncwarp();
}
__device__ __forceinline__ void attn_finish8(const Ctx& cx, int qb, int hs, int hw, int lane, __nv_bfloat16* out) {
  const uint32_t tag = *(const uint32_t*)(cx.sp + SM_TAG);
  mbar_wait(cx.sb + SM_BAR_P8, 0);
  mbar_wait(cx.sb + SM_BAR_XG, 0);
#pragma unroll 1
  for (int g = 2 - hw; g < 4; g += 3) {
    float acc[8] = {0.f, 0.f, 0.f, 0.f, 0.f, 0.f, 0.f, 0.f};
    uint32_t a[4];
#pragma unroll 1
    for (uint32_t o = g * 512 + lane * 16; o < 16384; o += 2048) {
      lds128(cx.sb + SM_P8 + o, a[0], a[1], a[2], a[3]);
#pragma unroll 1
      for (int n = 0; n < (1 << 16) && __any_sync(0xffffffffu, (a[0] & TAG_BIT) != tag); n++)
        ld_gran(at<const uint4>(cx.gs->part, (qb * 64 + 56 + hs) * 16384 + o), a[0], a[1], a[2], a[3]);
      a[0] &= ~TAG_BIT;
#pragma unroll
      for (int j = 0; j < 4; j++) { acc[2 * j] += bf_lo(a[j]); acc[2 * j + 1] += bf_hi(a[j]); }
    }
    asm volatile("" : "+r"(lane));
    const uint32_t tile = cx.sb + SM_XO + (128 + (lane & 15)) * 128 + (((lane >> 4) ^ (lane & 7)) << 4);
    uint32_t b[4];
    ldsm4((tile ^ (g << 5)) + STAGE, a[0], a[1], a[2], a[3]);
    ldsm4(tile ^ (g << 5), b[0], b[1], b[2], b[3]);
    stsm4(tile ^ (g << 5), fma2(pack2(acc[0], acc[1]), a[0], b[0]), fma2(pack2(acc[2], acc[3]), a[1], b[1]),
          fma2(pack2(acc[4], acc[5]), a[2], b[2]), fma2(pack2(acc[6], acc[7]), a[3], b[3]));
  }
  bar_sync(BAR_ROWS, 96);
#pragma unroll 1
  for (int ch = threadIdx.x - 32; ch < 128; ch += 96)
    *at<uint4>(out, ((qb * 128 + hs * 16 + (ch >> 3)) * DM + 512 + (ch & 7) * 8) * 2) =
        *(const uint4*)(cx.sp + SM_XO + (128 + (ch >> 3)) * 128 + (((ch ^ (ch >> 3)) & 7) << 4));
}

constexpr float SUM_HI = 1.8446744e19f, SUM_LO = 9.0949470e-13f;

__device__ __forceinline__ void softmax_shift(float (&s)[64], float n0, float n1) {
#pragma unroll
  for (int i = 0; i < 64; i++) s[i] += (i & 2) ? n1 : n0;
}
template <int LO, int HI>
__device__ __forceinline__ void softmax_exp(float (&s)[64]) {
#pragma unroll
  for (int i = LO; i < HI; i++) s[i] = ex2(s[i]);
}
__device__ __forceinline__ void row_sums(const uint32_t (&pf)[32], float& l0, float& l1) {
  uint32_t t[16];
#pragma unroll
  for (int i = 0; i < 16; i++) t[i] = add2(pf[(i >> 1) * 4 + (i & 1)], pf[(i >> 1) * 4 + 2 + (i & 1)]);
#pragma unroll
  for (int i = 0; i < 8; i++) t[i] = add2(t[(i >> 1) * 4 + (i & 1)], t[(i >> 1) * 4 + 2 + (i & 1)]);
#pragma unroll
  for (int i = 0; i < 4; i++) t[i] = add2(t[(i >> 1) * 4 + (i & 1)], t[(i >> 1) * 4 + 2 + (i & 1)]);
  l0 += (bf_lo(t[0]) + bf_lo(t[2])) + (bf_hi(t[0]) + bf_hi(t[2]));
  l1 += (bf_lo(t[1]) + bf_lo(t[3])) + (bf_hi(t[1]) + bf_hi(t[3]));
}
__device__ __forceinline__ void softmax_redo(uint32_t (&pf)[32], const uint32_t (&q)[32], const __nv_bfloat16* kblk, int lane, float& n0,
                                             float& n1, float& l0, float& l1, float& sc0, float& sc1) {
  float x0 = -n0, x1 = -n1;
#pragma unroll 1
  for (int u = 0; u < 16; u++) {
    const uint32_t* kp = (const uint32_t*)(kblk + ((u & 7) * 16 + (lane >> 2)) * DH) + (lane & 3);
    float d[2][4] = {};
#pragma unroll
    for (int k = 0; k < 16; k++)
      hmma_k16(d[k & 1], q[2 * (k & 14)], q[2 * (k & 14) + 1], q[2 * (k & 14) + 2], q[2 * (k & 14) + 3],
               kp[(k & 1) * 4 * DH + (k >> 1) * 8], kp[(k & 1) * 4 * DH + (k >> 1) * 8 + 4]);
    if (u < 8) {
      x0 = fmaxf(fmaxf(x0, fmaxf(d[0][0], d[0][1])), fmaxf(d[1][0], d[1][1]));
      x1 = fmaxf(fmaxf(x1, fmaxf(d[0][2], d[0][3])), fmaxf(d[1][2], d[1][3]));
      if (u == 7) {
#pragma unroll
        for (int m = 1; m < 4; m <<= 1) {
          x0 = fmaxf(x0, __shfl_xor_sync(0xffffffffu, x0, m));
          x1 = fmaxf(x1, __shfl_xor_sync(0xffffffffu, x1, m));
        }
        sc0 = ex2(-x0 - n0);
        sc1 = ex2(-x1 - n1);
        n0 = -x0;
        n1 = -x1;
        l0 *= sc0;
        l1 *= sc1;
      }
    } else {
#pragma unroll
      for (int i = 0; i < 28; i++) pf[i] = pf[i + 4];
#pragma unroll
      for (int i = 0; i < 4; i++) {
        const float n = (i & 1) ? n1 : n0;
        pf[28 + i] = pack2(ex2(d[i >> 1][(i & 1) * 2] + n), ex2(d[i >> 1][(i & 1) * 2 + 1] + n));
        ((i & 1) ? l1 : l0) += bf_lo(pf[28 + i]) + bf_hi(pf[28 + i]);
      }
    }
  }
}

__device__ __forceinline__ void attn_consumer(const Ctx& cx, int qb, int hs, int wg, int cw, int lane, const __nv_bfloat16* x,
                                              const __nv_bfloat16* kc, __nv_bfloat16* out) {
  const uint32_t full = cx.sb + SM_FULL;
  const uint32_t ring = cx.sb + SM_RING;
  uint32_t lo = ((cw & 3) * 16 + (lane & 15)) * 128 + (((lane >> 4) ^ (lane & 7)) << 4);
  const uint32_t slot = cx.sb + SM_SLOT + wg * 16384;
  auto frag = [&](int sl, int k) { return ((slot + sl * STAGE + lo) ^ ((k & 3) << 5)) + (k >> 2) * 8192; };
  auto park = [&](const float (&a)[64], int sl, int k0, int k1, float f0, float f1) {
#pragma unroll
    for (int k = 0; k < 8; k++)
      if (k >= k0 && k < k1)
        stsm4(frag(sl, k), pack2(a[8 * k] * f0, a[8 * k + 1] * f0), pack2(a[8 * k + 2] * f1, a[8 * k + 3] * f1),
              pack2(a[8 * k + 4] * f0, a[8 * k + 5] * f0), pack2(a[8 * k + 6] * f1, a[8 * k + 7] * f1));
  };
  const bool signaller = lane == 0 && (cw & 3) < 2;
  int my_turn = 1 + wg, other_turn = 2 - wg;

  uint32_t pf[32], q[32], empty_c;
  float o[64], l0, l1;
  {
    uint32_t xa[144];
    float rstd0, rstd1;
    {
      const uint32_t xb = cx.sb + SM_X + wg * 73728, xf = cx.sb + SM_XFULL + wg * 96;
      float sm[4][4] = {};
      prof(wg, 0);
      empty_c = mapa(cx.sb + SM_EMPTY, cw & 1);
      mbar_wait(xf, 0);
      if ((threadIdx.x & 127) == 0) profc(wg, 30);
      ln_fetch<0, 12>(xa, xb, lo);
      mbar_wait(xf + 8, 0);
      ln_fetch<12, 24>(xa, xb, lo);
      ln_sums<0, 12>(xa, sm);
      mbar_wait(xf + 16, 0);
      if ((threadIdx.x & 127) == 0) profc(wg, 1);
      ln_fetch<24, 36>(xa, xb, lo);
      ln_sums<12, 36>(xa, sm);
      block_fence(36);
      if (wg) bar_arrive(other_turn, 256);
      block_fence(35);
      rstd0 = ((sm[0][0] + sm[1][0]) + (sm[2][0] + sm[3][0])) * (1.0f / DM);
      rstd1 = ((sm[0][2] + sm[1][2]) + (sm[2][2] + sm[3][2])) * (1.0f / DM);
    }
    const uint32_t mm0 = pack2(rstd0, rstd0), mm1 = pack2(rstd1, rstd1);
    rstd0 -= bf_lo(mm0);
    rstd1 -= bf_lo(mm1);
    rstd0 *= rstd0 * (-0.25f * DM);
    rstd1 *= rstd1 * (-0.25f * DM);
    auto ln_finish = [&]() {
      rstd0 += __shfl_xor_sync(0xffffffffu, rstd0, 1); rstd1 += __shfl_xor_sync(0xffffffffu, rstd1, 1);
      rstd0 += __shfl_xor_sync(0xffffffffu, rstd0, 2); rstd1 += __shfl_xor_sync(0xffffffffu, rstd1, 2);
      rstd0 = ln_rstd(rstd0 * (1.0f / DM)) * SM_SCALE_LOG2;
      rstd1 = ln_rstd(rstd1 * (1.0f / DM)) * SM_SCALE_LOG2;
    };
    ln_centre(xa, 0, X_C0, mm0, mm1, rstd0, rstd1);
    if (wg == 0) {
      bar_sync(4, 128);
      if (signaller) {
        asm volatile("mbarrier.arrive.shared::cluster.b64 _, [%0], 2;" ::"r"(empty_c + 16) : "memory");
        asm volatile("mbarrier.arrive.shared::cluster.b64 _, [%0], 2;" ::"r"(empty_c + 24) : "memory");
      }
      block_fence(37);
      pin(xa);
      ln_centre(xa, X_C0, X_C1, mm0, mm1, rstd0, rstd1);
    }
    pin(xa);
    if ((threadIdx.x & 127) == 0) profc(wg, 2);

    extern __shared__ __align__(1024) uint8_t smem_q[];
    const uint32_t ring = smem_u32(smem_q) + SM_RING;
    auto release = [&](int st) { if (signaller) mbar_arrive_cluster(empty_c + 8 * (st & 3)); };
    auto q_stage = [&](float (&acc)[64], int st, int i, int last) {
      mbar_wait(full + 8 * (st & 3), (st >> 2) & 1);
      if (i != (wg ? last : 1)) bar_sync(my_turn, 256);
      wg_fence();
      const uint64_t db = mkdesc(ring + (st & 3) * STAGE, 16384);
#pragma unroll
      for (int k = 0; k < 8; k++) {
        const int kb = (i < 3 ? 8 * i : 8 * i - 4) + k;
        if (i != 2 || k < 4) mma_n128<1>(acc, xa[4 * kb], xa[4 * kb + 1], xa[4 * kb + 2], xa[4 * kb + 3], db + k * 128, kb > 0);
      }
      wg_commit();
      if (i != (wg ? last - 1 : 0)) bar_arrive(other_turn, 256);
    };
    auto q_release = [&](int st, int i, int last) {
      if (i == 1 || i == last) {
        wg_wait<1>();
        if (i == last || !wg) release(st - 1);
      }
      if (i != last - 1 && (i || wg)) {
        wg_wait<0>();
        release(st);
      }
    };
    {
      float (&acc)[64] = o;
#pragma unroll 1
      for (int p = 0; p < 2; p++) {
#pragma unroll
        for (int i = 0; i < 5; i++) {
          q_stage(acc, 5 * p + i, i, 4);
          if (p == 0 && i != 3) {
            if (i == 0 && wg) bar_arrive(BAR_HELPER, 160);
            if ((wg || i) && i < 3) ln_centre(xa, i == 0 ? X_C0 : i == 1 ? X_C1 : X_C2, i == 0 ? X_C1 : i == 1 ? X_C2 : 72, mm0, mm1, rstd0, rstd1);
            if (i == 4) ln_finish();
            pin(xa);
          }
          q_release(5 * p + i, i, 4);
        }
        pin(acc);
#pragma unroll
        for (int k = 0; k < 8; k += 2) {
          park(acc, p, k, k + 2, rstd0, rstd1);
          if (k < 6) block_fence(40 + k);
        }
      }
    }
    {
      float (&h)[32] = *(float (*)[32])&o[0];
#pragma unroll
      for (int i = 0; i < 3; i++) {
        const uint32_t sl = (10 + i) & 3;
        mbar_wait(full + 8 * sl, ((10 + i) >> 2) & 1);
        if (i != (wg ? 2 : 1)) bar_sync(my_turn, 256);
        wg_fence();
#pragma unroll
        for (int k = 0; k < 16 - 4 * i; k++) {
          const int kb = (i == 2 ? 28 : 16 * i) + k;
          const uint64_t db = mkdesc(ring + sl * STAGE, 16) + (i == 2 && k >= 4 ? k + 4 : k) * 128;
          mma_n64<1>(h, xa[4 * kb], xa[4 * kb + 1], xa[4 * kb + 2], xa[4 * kb + 3], db, kb > 0);
        }
        wg_commit();
        if (i != (wg ? 1 : 0)) bar_arrive(other_turn, 256);
        q_release(10 + i, i, 2);
      }
      pin(h);
      park(o, 2, 0, 2, rstd0, rstd1);
      block_fence(49);
      park(o, 2, 2, 4, rstd0, rstd1);
    }
#pragma unroll
    for (int i = 0; i < 4; i++) {
      q_stage(o, 13 + i, i, 3);
      q_release(13 + i, i, 3);
    }
    prof(wg, 6);
#pragma unroll
    for (int i = 0; i < 32; i++) pf[i] = xa[112 + i];
    l0 = 0.25f * rcp(rstd0);
    l1 = 0.25f * rcp(rstd1);
  }

  uint32_t oa[96];
  const uint32_t zero = __shfl_sync(0xffffffffu, blockIdx.y, lane);
  my_turn = __shfl_sync(0xffffffffu, my_turn, lane);
  other_turn = __shfl_sync(0xffffffffu, other_turn, lane);
  lo = __shfl_sync(0xffffffffu, lo, lane);
  {
    float s[64], n0 = 0.f, n1 = 0.f;
    float lp0, lp1;
    float i0 = 0.f, i1 = 0.f;
    bool redo, shift = false;
    auto turn = [&](int it, auto kc_) -> bool {
      constexpr int KIND = decltype(kc_)::value;
      constexpr uint32_t slk = KIND == 1 ? SL_KO : SL_KE, slv = KIND == 1 ? SL_VO : SL_VE, slkn = KIND == 1 ? SL_KE : SL_KO;
      constexpr int SPLIT = KIND == 3 ? X_SPLIT3 : X_SPLIT, PARK1 = X_PARK;
      const uint32_t par = ((it + NST_Q / 2) >> 1) & 1;
      const int hsl = max((it >> 4) - 1, 0);
      const uint64_t dk = mkdesc(ring + slk * STAGE, 16), dv = mkdesc(ring + slv * STAGE, 16384);
      auto qk = [&]() {
#pragma unroll
        for (int k = 0; k < 8; k++) {
          if (KIND == 3) mma_n128_ss<0>(s, mkdesc(slot + hsl * STAGE, 16) + (k >> 2) * 512 + (k & 3) * 2, dk + (k >> 2) * 1024 + (k & 3) * 2, k > 0);
          else mma_n128<0>(s, q[4 * k], q[4 * k + 1], q[4 * k + 2], q[4 * k + 3], dk + (k >> 2) * 1024 + (k & 3) * 2, k > 0);
        }
        wg_commit();
      };
      auto pv = [&]() {
#pragma unroll
        for (int k = 0; k < 8; k++)
          mma_n128<1>(o, pf[4 * k], pf[4 * k + 1], pf[4 * k + 2], pf[4 * k + 3], dv + k * 128, k > 0 || KIND != 1 || (it & 15) != 1);
        wg_commit();
      };
      lp0 = l0; lp1 = l1;
#define TS(i)
      {
        TS(0)
        if (KIND == 3) {
          asm volatile("fence.proxy.async.shared::cta;" ::: "memory");
          const float t0 = lp0 + __shfl_xor_sync(0xffffffffu, lp0, 1), t1 = lp1 + __shfl_xor_sync(0xffffffffu, lp1, 1);
          i0 = rcp(t0 + __shfl_xor_sync(0xffffffffu, t0, 2));
          i1 = rcp(t1 + __shfl_xor_sync(0xffffffffu, t1, 2));
          asm volatile("" : "+f"(i0), "+f"(i1)::"memory");
          block_fence(31, zero);
#pragma unroll
          for (int k = 0; k < X_N1; k++) ldsm4(frag(hsl, k), q[4 * k], q[4 * k + 1], q[4 * k + 2], q[4 * k + 3]);
        }
        bar_sync(my_turn, 256);
        TS(1)
        if (KIND != 3) pin(q);
        pin(pf); pin(o);
        wg_fence();
        qk();
        TS(2)
        mbar_wait(full + 8 * slv, par);
        if (KIND == 1 && (it & 15) == 1) {
          park(o, hsl, PARK1, 8, i0, i1);
          wg_fence();
        }
        if (KIND == 3) {
#pragma unroll
          for (int k = X_N1; k < 8; k++) ldsm4(frag(hsl, k), q[4 * k], q[4 * k + 1], q[4 * k + 2], q[4 * k + 3]);
          block_fence(32, zero);
        }
        TS(3)
        pv();
        bar_arrive(other_turn, 256);
        TS(4)
        wg_wait<1>();
      }
      pin(s);
      mbar_arrive_cluster_now<10 * KIND + 3>(empty_c + 8 * slk, signaller, zero);
      TS(5)
      if (KIND == 3) {
        shift = false;
        n0 = n1 = l0 = l1 = 0.f;
      } else if (shift) {
        softmax_shift(s, n0, n1);
        pin(s);
      }
      softmax_exp<0, SPLIT>(s);
      pin(s);
      block_fence(10 * KIND + 4, zero);
      TS(6)
      wg_wait<0>();
      pin(o); pin(pf);
      mbar_arrive_cluster_now<10 * KIND + 5>(empty_c + 8 * slv, signaller, zero);
      TS(7)
      const bool kready = mbar_test(full + 8 * slkn, par);
      softmax_exp<SPLIT, 64>(s);
#pragma unroll
      for (int i = 0; i < 32; i++) pf[i] = pack2(s[2 * i], s[2 * i + 1]);
      row_sums(pf, l0, l1);
      if (KIND == 3) {
        park(o, hsl, 0, PARK1, i0, i1);
        if (it) prof(wg, 6 + (it >> 4));
        if (it >= 32 && cw == 0) bar_arrive(BAR_HELPER, 64);
      }
      redo = !(l0 + l1 <= SUM_HI) || (KIND == 3 && fminf(l0, l1) < SUM_LO);
      const bool leave = __any_sync(0xffffffffu, redo || !kready);
      return leave;
    };
    int it = -1;
#pragma unroll 1
    while (true) {
      mbar_wait(full + 8 * ((it & 1) ? SL_KE : SL_KO), ((it + NST_Q / 2) >> 1) & 1);
      it++;
#pragma unroll 1
      while (true) {
        if (it & 1) {
          if (turn(it, IC<1>()) || it == 63) break;
          it++;
        }
        if (it & 15) {
          if (turn(it, IC<2>())) break;
        } else {
          if (turn(it, IC<3>())) break;
        }
        it++;
      }
      if (__any_sync(0xffffffffu, redo)) {
        const int j = it & 15;
        float sc0 = 1.f, sc1 = 1.f;
        if (j == 0) n0 = n1 = 3.0e38f;
        l0 = j ? lp0 : 0.f;
        l1 = j ? lp1 : 0.f;
        softmax_redo(pf, q, kc + (size_t)((hs * 2 + (it >> 5)) * SEQ + j * 128) * DH, lane, n0, n1, l0, l1, sc0, sc1);
        shift = true;
        if (j == 0) sc0 = sc1 = 1.f;
#pragma unroll
        for (int i = 0; i < 16; i++) { o[4 * i] *= sc0; o[4 * i + 1] *= sc0; o[4 * i + 2] *= sc1; o[4 * i + 3] *= sc1; }
      }
      if (it == 63) break;
    }
  }

#define TE(i) {}
  {
    constexpr int ST0 = NST_Q + NST_KV;
    float acc[32], red[32], first[32];
    uint32_t tag;
    uint4* xch;
    auto await = [&](int st) { mbar_wait(full + 8 * (st & 3), (st >> 2) & 1); };
    auto release = [&](int st) { if (signaller) mbar_arrive_cluster(empty_c + 8 * (st & 3)); };
    auto unpark = [&](int h, int k0, int k1) {
#pragma unroll
      for (int k = 0; k < 8; k++)
        if (k >= k0 && k < k1) ldsm4(frag(h, k), oa[32 * h + 4 * k], oa[32 * h + 4 * k + 1], oa[32 * h + 4 * k + 2], oa[32 * h + 4 * k + 3]);
    };
    {
      float ar[64];
      asm volatile("fence.proxy.async.shared::cta;" ::: "memory");
      l0 += __shfl_xor_sync(0xffffffffu, l0, 1); l1 += __shfl_xor_sync(0xffffffffu, l1, 1);
      l0 += __shfl_xor_sync(0xffffffffu, l0, 2); l1 += __shfl_xor_sync(0xffffffffu, l1, 2);
      float f0 = rcp(l0), f1 = rcp(l1);
      asm volatile("" : "+f"(f0), "+f"(f1)::"memory");
      await(ST0 - 1);
      unpark(1, 0, 4);
      bar_sync(my_turn, 256);
      pin(pf); pin(o);
      wg_fence();
#pragma unroll
      for (int k = 0; k < 8; k++)
        mma_n128<1>(o, pf[4 * k], pf[4 * k + 1], pf[4 * k + 2], pf[4 * k + 3], mkdesc(ring + SL_KE * STAGE, 16384) + k * 128, 1);
      wg_commit();
      await(ST0);
      unpark(1, 4, 8);
      block_fence(61, zero);
#pragma unroll
      for (int k = 0; k < 8; k++) mma_n128_ss<1>(ar, mkdesc(slot, 16) + (k >> 2) * 512 + (k & 3) * 2, mkdesc(ring + (ST0 & 3) * STAGE, 16384) + k * 128, k > 0);
      wg_commit();
      bar_arrive(other_turn, 256);
      wg_wait<1>();
      pin(o); pin(pf);
      mbar_arrive_cluster_now<62>(empty_c + 8 * SL_KE, signaller, zero);
#pragma unroll
      for (int i = 0; i < 16; i++) {
        pf[2 * i] = pack2(o[4 * i] * f0, o[4 * i + 1] * f0);
        pf[2 * i + 1] = pack2(o[4 * i + 2] * f1, o[4 * i + 3] * f1);
      }
      pin(pf);
      prof(wg, 10);
#pragma unroll
      for (int u = 1; u < 4; u++) {
        await(ST0 + u);
        wg_wait<0>();
        release(ST0 + u - 1);
        bar_sync(my_turn, 256);
        wg_fence();
#pragma unroll
        for (int k = 0; k < 8; k++) {
          const uint32_t* a = (u == 1 ? oa + 32 : u == 2 ? pf : oa + 64) + 4 * k;
          mma_n128<1>(ar, a[0], a[1], a[2], a[3], mkdesc(ring + ((ST0 + u) & 3) * STAGE, 16384) + k * 128, 1);
        }
        wg_commit();
        bar_arrive(other_turn, 256);
        if (u < 3) {
          block_fence(62 + u, zero);
          unpark(u == 1 ? 2 : 0, 0, 8);
        }
      }
      mbar_wait(cx.sb + SM_BAR_MISC, 0);
      tag = *(const volatile uint32_t*)(cx.sp + SM_TAG);
      xch = at<uint4>(cx.gs->part, (qb << 20) + lane * 16 + zero);
      tag = __shfl_sync(0xffffffffu, tag, lane);
      await(ST0 + 4);
      wg_wait<0>();
      release(ST0 + 3);
      pin(ar);
#pragma unroll
      for (int i = 0; i < 32; i++) { first[i] = ar[i]; red[i] = ar[32 + i]; }
    }
    auto send = [&](const float (&v)[32], int dst, int idx) {
      uint4* p = at<uint4>(xch, (dst * 8 + idx) * 2048);
#pragma unroll
      for (int i = 0; i < 4; i++)
        st_gran(p + i * 32, (pack2(v[8 * i], v[8 * i + 1]) & ~TAG_BIT) | tag, pack2(v[8 * i + 2], v[8 * i + 3]),
                pack2(v[8 * i + 4], v[8 * i + 5]), pack2(v[8 * i + 6], v[8 * i + 7]));
    };
    send(first, ((hs + 1) & 7) * 7, cw);
    int nrx = 1;
    auto half_step = [&](int s, auto hc, bool arrive) {
      constexpr int h = decltype(hc)::value;
      const int st = ST0 + 2 * s + h;
      const uint64_t db = mkdesc(ring + (st & 3) * STAGE, 16);
      bar_sync(my_turn, 256);
      if (h == 0) pin(pf);
#pragma unroll
      for (int i = 32 * h; i < 32 + 64 * h; i++) asm volatile("" : "+r"(oa[i])::"memory");
      wg_fence();
#pragma unroll
      for (int k = 0; k < 16; k++) {
        const int kb = h * 16 + k - 8;
        if (kb >= 0) mma_n64<1>(acc, oa[4 * kb], oa[4 * kb + 1], oa[4 * kb + 2], oa[4 * kb + 3], db + k * 128, 1);
        else mma_n64<1>(acc, pf[4 * k], pf[4 * k + 1], pf[4 * k + 2], pf[4 * k + 3], db + k * 128, k > 0);
      }
      wg_commit();
      if (arrive) bar_arrive(other_turn, 256);
    };
    auto source = [&](int n) { return at<const uint4>(xch, ((hs * 7 + n - 1) * 8 + cw) * 2048); };
    auto fetch = [&](uint32_t (&g)[16], const uint4* p) {
#pragma unroll
      for (int i = 0; i < 4; i++) ld_gran(p + i * 32, g[4 * i], g[4 * i + 1], g[4 * i + 2], g[4 * i + 3]);
    };
    uint32_t g[16];
#pragma unroll 1
    for (int s = 2; s < 8; s++) {
      const int st = ST0 + 2 * s;
      half_step(s, IC<0>(), true);
      if (s == 2) {
        bar_arrive(BAR_OA, 352);
        send(red, 56 + cw, hs);
#pragma unroll
        for (int i = 0; i < 32; i++) red[i] = 0.f;
      }
      await(st + 1);
      if (s > 3 && granules_ok(g, tag)) { add_granules(red, g); nrx++; }
      wg_wait<0>();
      if (s < 7) release(st);
      if (s > 2) fetch(g, source(nrx));
      half_step(s, IC<1>(), true);
      await(st + 2);
      wg_wait<0>();
      if (s < 7) release(st + 1);
      pin(acc);
      if (s == 7) prof(wg, 19);
      send(acc, ((hs + s) & 7) * 7 + s - 1, cw);
    }
    TE(1)
    uint32_t xv[16], gt[16];
    {
      const int s = 8;
      uint32_t g2[16];
      half_step(s, IC<0>(), true);
      TE(2)
      await(NST_Q + NST_KV + NST_O - 1);
      cluster_arrive();
      mbar_wait(cx.sb + SM_BAR_XG, 0);
      const uint32_t tile = cx.sb + SM_XO + wg * 8192 + lo;
      if (granules_ok(g, tag)) { add_granules(red, g); nrx++; }
      fetch(g, source(nrx));
      block_fence(58, zero);
      wg_wait<0>();
      TE(3)
#pragma unroll
      for (int k = 0; k < 4; k++) ldsm4((tile ^ (k << 5)) + STAGE, gt[4 * k], gt[4 * k + 1], gt[4 * k + 2], gt[4 * k + 3]);
      half_step(s, IC<1>(), wg == 0);
      TE(4)
      block_fence(56, zero);
      const bool ok = granules_ok(g, tag);
      block_fence(57, zero + ok * 1000);
      const uint4* src = source(7);
      fetch(g2, src);
#pragma unroll
      for (int k = 0; k < 4; k++) ldsm4(tile ^ (k << 5), xv[4 * k], xv[4 * k + 1], xv[4 * k + 2], xv[4 * k + 3]);
      if (ok) { add_granules(red, g); nrx++; }
      TE(5)
      block_fence(59, zero);
      wg_wait<0>();
      pin(acc);
      TE(6)
#pragma unroll
      for (int i = 0; i < 32; i++) red[i] += acc[i];
      pin(red);
      TE(7)
      int n = 7;
#pragma unroll 1
      for (int spins = 0; spins < (1 << 16); spins++) {
        if (granules_ok(g2, tag)) {
          add_granules(red, g2);
          if (--n < nrx) {
            break;
          }
          src -= 1024;
        }
        fetch(g2, src);
      }
      TE(8)
    }
    prof(wg, 20);
    TE(9)
    const uint32_t ot = ring + ((ST0 + NST_O) & 3) * STAGE + cw * (16 * 144);
    uint32_t ow[16];
#pragma unroll
    for (int i = 0; i < 16; i++) ow[i] = fma2(pack2(red[2 * i], red[2 * i + 1]), gt[i], xv[i]);
#pragma unroll
    for (int i = 0; i < 4; i++)
      stsm4(ot + (lane & 15) * 144 + (2 * i + (lane >> 4)) * 16, ow[4 * i], ow[4 * i + 1], ow[4 * i + 2], ow[4 * i + 3]);
    __syncwarp();
#pragma unroll
    for (int i = 0; i < 4; i++) {
      uint4 v;
      lds128(ot + (i * 4 + (lane >> 3)) * 144 + (lane & 7) * 16, v.x, v.y, v.z, v.w);
      at<uint4>(out, ((qb * 128 + cw * 16 + (lane >> 3)) * DM + hs * 64 + (lane & 7) * 8) * 2)[i * (4 * DM / 8)] = v;
    }
    TE(10)
    prof(wg, 22);
  }
}

constexpr int AST_X = 6, AST_F = AST_X + 96;
__device__ __forceinline__ void aux_producer(const Ctx& cx, int f, const CUtensorMap* tmWq, const CUtensorMap* tmG) {
  const uint32_t full = cx.sb + SM_FULL, empty = cx.sb + SM_EMPTY;
  __nanosleep(3000);
  if (elect_one()) {
#pragma unroll 1
    for (int st = 0; st < AST_X; st++) {
      mbar_expect_tx(full + 8 * st, FSTAGE);
#pragma unroll
      for (int i = 0; i < 3; i++)
        tma2d_stream(cx.sb + st * FSTAGE + i * 8192, tmWq, (2 * f + (st & 1)) * 512 + 448, (st >> 1) * 192 + i * 64, full + 8 * st);
    }
  }
  __syncwarp();
  mbar_wait(cx.sb + SM_BAR_MISC, 0);
  proxy_fence();
  int st = AST_X;
#pragma unroll 1
  for (; st < AST_F; st++) {
    const uint32_t sl = st & 7;
    mbar_wait(empty + 8 * sl, ((st >> 3) & 1) ^ 1);
    if (elect_one()) {
      mbar_expect_tx(full + 8 * sl, FSTAGE);
      bulk_load(cx.sb + sl * FSTAGE, cx.gs->xn + (st - AST_X) * (FSTAGE / 16), FSTAGE, full + 8 * sl);
    }
    __syncwarp();
  }
#pragma unroll 1
  for (int pair = 0; pair < 14; pair++) {
#pragma unroll 1
    for (int u = 0; u < 12; u++, st++) {
      const uint32_t sl = st & 7;
      const int unit = pair * 2 + (u & 1), k = u >> 1;
      if (unit == 27) continue;
      const bool gu = pair < 9;
      mbar_wait(empty + 8 * sl, ((st >> 3) & 1) ^ 1);
      if (elect_one()) {
        mbar_expect_tx(full + 8 * sl, FSTAGE);
        tma2d_stream(cx.sb + sl * FSTAGE, tmG + (gu ? k >= 3 : 2), gu ? f * 1152 + unit * 64 : (unit - 18) * 64,
                     gu ? (k >= 3 ? k - 3 : k) * 192 : f * 1152 + k * 192, full + 8 * sl);
      }
      __syncwarp();
    }
  }
}

constexpr int BAR_FREE = 4, BAR_TILE = 6;
__device__ __forceinline__ void aux_helper(const Ctx& cx, int f, int warp, int lane) {
  unsigned epoch = 0;
  if (lane == 0) epoch = cx.gs->launch[blockIdx.x] + 1;
  epoch = __shfl_sync(0xffffffffu, epoch, 0);
  bar_sync(BAR_OA, 96);
  if (warp == 3) {
    if (lane == 0) cx.gs->launch[blockIdx.x] = epoch;
    await_count(at<const unsigned>(cx.gs->rows, (lane & 15) * 128), 8 * epoch, 200);
    if (lane == 0) mbar_arrive(cx.sb + SM_BAR_MISC);
    prof(0, 1, 31);
    await_count(at<const unsigned>(cx.gs->rows, (lane & 15) * 128 + 4), 8 * epoch, 500);
    uint32_t bound = 0xFFFFFFFFu, m0 = 0, m1 = 0;
#pragma unroll 1
    for (int k = 0; k < TOPC; k++) {
      if (__any_sync(0xffffffffu, m0 == 0)) {
        m0 = m1 = 0;
#pragma unroll 2
        for (int i = 0; i < 16; i++) {
          const uint4 v = __ldcg(at<const uint4>(cx.gs->key, lane * 16 + i * 512));
          const uint32_t w[4] = {v.x, v.y, v.z, v.w};
#pragma unroll
          for (int j = 0; j < 4; j++) {
            const uint32_t t = w[j] <= bound ? w[j] : 0;
            m1 = max(m1, min(m0, t));
            m0 = max(m0, t);
          }
        }
      }
      uint32_t m = m0;
      m = __reduce_max_sync(0xffffffffu, m);
      bound = m - 1;
      if (m0 == m) { m0 = m1; m1 = 0; }
      if (f == 0 && lane == 0) *at<uint32_t>(cx.gs->top, k * 4) = m;
#pragma unroll
      for (int j = 0; j < 3; j++) {
        const uint32_t row = 0xFFFF - (m & 0xFFFF), i = min(j * 4 + (lane >> 3), 8);
        *(uint4*)(cx.sp + SM_XSEL + i * 1024 + k * 128 + (((lane ^ k) & 7) << 4)) =
            __ldcg(at<const uint4>(cx.gs->xn, xn_offset(row, (lane & 7) * 4) + i * 8192));
      }
    }
    asm volatile("fence.proxy.async.shared::cta;" ::: "memory");
    prof(0, 2, 31);
  } else {
    const int wg = warp - 1;
#pragma unroll 1
    for (int u = 0; u < 32; u++) {
      bar_arrive(BAR_FREE + wg, 160);
      bar_sync(BAR_TILE + wg, 160);
      if (elect_one()) {
        const int n = (u >> 1) * 8 + 2 * f + wg;
        asm volatile("cp.async.bulk.global.shared::cta.bulk_group [%0], [%1], 8192;\ncp.async.bulk.commit_group;\ncp.async.bulk.wait_group 0;"
                     ::"l"(cx.gs->q3 + (n * 2 + (u & 1)) * 512), "r"(cx.sb + SM_H + wg * 8192) : "memory");
        if (u & 1) st_release(&cx.gs->q3_flag[n], epoch);
      }
      __syncwarp();
    }
  }
  bar_arrive(3, 352);
}

__device__ __forceinline__ void aux_consumer(const Ctx& cx, int f, int wg, int cw, int lane) {
  const int r = lane >> 2, c = lane & 3, tid = cw * 32 + lane;
  const uint32_t full = cx.sb + SM_FULL, empty = cx.sb + SM_EMPTY;
  const bool signaller = (tid & 127) == 0;
  auto await = [&](int st) { mbar_wait(full + 8 * (st & 7), (st >> 3) & 1); };
  auto release = [&](int st, int cnt) {
    asm volatile("{\n.reg .pred p;\nsetp.ne.u32 p, %2, 0;\n@p mbarrier.arrive.shared::cta.b64 _, [%0], %1;\n}"
                 ::"r"(empty + 8 * (st & 7)), "r"(cnt), "r"((uint32_t)signaller) : "memory");
  };
  prof(wg, 0);
  {
    const uint32_t lt = ((lane & 7) + (lane >> 4) * 8) * 128 + ((((cw & 3) * 2 + ((lane >> 3) & 1)) ^ (lane & 7)) << 4);
    uint32_t wa[144];
#pragma unroll
    for (int i = 0; i < 3; i++) {
      await(2 * i + wg);
#pragma unroll
      for (int k = 0; k < 12; k++) {
        const int kb = 12 * i + k;
        ldsm4t(cx.sb + (2 * i + wg) * FSTAGE + k * 2048 + lt, wa[4 * kb], wa[4 * kb + 1], wa[4 * kb + 2], wa[4 * kb + 3]);
      }
    }
    bar_sync(1, 256);
#pragma unroll
    for (int i = 0; i < 3; i++) release(2 * i + wg, 2);
    if (wg) bar_arrive(1, 256);
#pragma unroll 1
    for (int st = AST_X; st < AST_F; st += 3) {
      float acc[32];
      await(st);
      await(st + 1);
      await(st + 2);
      bar_sync(1 + wg, 256);
      wg_fence();
#pragma unroll
      for (int kb = 0; kb < 36; kb++) {
        const int i = kb / 12, k = kb % 12;
        mma_n64<0>(acc, wa[4 * kb], wa[4 * kb + 1], wa[4 * kb + 2], wa[4 * kb + 3],
                   mkdesc(cx.sb + ((st + i) & 7) * FSTAGE, 16) + (k >> 2) * 512 + (k & 3) * 2, kb > 0);
        if (k == 11) wg_commit();
      }
      if (st < AST_F - 3 || !wg) bar_arrive(2 - wg, 256);
      wg_wait<1>();
      release(st, 1);
      release(st + 1, 1);
      bar_sync(BAR_FREE + wg, 160);
      wg_wait<0>();
      pin(acc);
      release(st + 2, 1);
#pragma unroll
      for (int k = 0; k < 4; k++)
        stsm4t(cx.sb + SM_H + wg * 8192 + k * 2048 + lt, pack2(acc[8 * k] * SM_SCALE_LOG2, acc[8 * k + 1] * SM_SCALE_LOG2),
               pack2(acc[8 * k + 2] * SM_SCALE_LOG2, acc[8 * k + 3] * SM_SCALE_LOG2),
               pack2(acc[8 * k + 4] * SM_SCALE_LOG2, acc[8 * k + 5] * SM_SCALE_LOG2),
               pack2(acc[8 * k + 6] * SM_SCALE_LOG2, acc[8 * k + 7] * SM_SCALE_LOG2));
      asm volatile("fence.proxy.async.shared::cta;" ::: "memory");
      bar_arrive(BAR_TILE + wg, 160);
    }
    bar_sync(3, 352);
  }
  prof(wg, 3);
#pragma unroll 1
  for (int unit = wg; unit < 27; unit += 2) {
    if (unit >> 1 == 9) {
      asm volatile("fence.proxy.async.shared::cta;" ::: "memory");
      bar_sync(3, 256);
      prof(wg, 4);
    }
    const bool gu = unit < 18;
    float a0[4], a1[4];
#pragma unroll 1
    for (int m = 0; m < 2; m++) {
      float p0[4], p1[4];
      int st = AST_F + (unit >> 1) * 12 + m * 6 + wg;
      uint32_t b = cx.sb + (gu ? SM_XSEL : SM_H + m * 9216);
#pragma unroll 1
      for (int u = 0; u < 3; u++, st += 2, b += 3072) {
        await(st);
        wg_fence();
        const uint64_t da = mkdesc(cx.sb + (st & 7) * FSTAGE, 16), db = mkdesc(b, 16);
#pragma unroll
        for (int k = 0; k < 12; k++) mma_n8((k & 1) ? p1 : p0, da + k * 128, db + (k >> 2) * 64 + (k & 3) * 2, u > 0 || k > 1);
        wg_commit();
        wg_wait<1>();
        if (u) release(st - 2, 2);
      }
      wg_wait<0>();
      release(st - 2, 2);
      pin(p0); pin(p1);
#pragma unroll
      for (int i = 0; i < 4; i++) { a0[i] = a1[i]; a1[i] = p0[i] + p1[i]; }
    }
#pragma unroll
    for (int i = 0; i < 4; i++) {
      const int fl = (cw & 3) * 16 + r + (i >> 1) * 8, tok = 2 * c + (i & 1);
      if (gu) {
        const float h = bfr(silu_f(bfr(a0[i]))) * bfr(a1[i]);
        *(__nv_bfloat16*)(cx.sp + SM_H + unit * 1024 + tok * 128 + (((fl >> 3) ^ tok) << 4) + (fl & 7) * 2) = __float2bfloat16_rn(h);
      } else {
        *at<float>(cx.gs->ypart, ((f * TOPC + tok) * DM + (unit - 18) * 64 + fl) * 4) = a0[i] + a1[i];
      }
    }
  }
  prof(wg, 5);
  bar_sync(3, 256);
  if (tid == 0) red_release(&cx.gs->ycnt);
  prof(wg, 6);
}

struct Maps { CUtensorMap m[9]; };
__global__ void __cluster_dims__(2, 1, 1) __launch_bounds__(THREADS, 1)
fused_kernel(const __nv_bfloat16* __restrict__ x, const __nv_bfloat16* __restrict__ w_r, const __nv_bfloat16* __restrict__ kc,
             const __nv_bfloat16* __restrict__ wo, __nv_bfloat16* __restrict__ out, Scratch* gs,
             const __grid_constant__ Maps maps) {
  const CUtensorMap &tmX = maps.m[0], &tmWq = maps.m[1], &tmK = maps.m[2], &tmV = maps.m[3], &tmWo = maps.m[4];
  extern __shared__ __align__(1024) uint8_t smem_raw[];
  prof(0, 23, 511);
  if (threadIdx.x < 72 && blockIdx.x < N_ATT_CTA)
    asm volatile("prefetch.global.L2 [%0];" ::"l"(at<const void>(x, ((blockIdx.x >> 3) * 128 + (blockIdx.x & 7) * 8) * (DM * 2) + threadIdx.x * 128)));
  Ctx cx;
  cx.sb = smem_u32(smem_raw);
  cx.sp = smem_raw;
  cx.gs = gs;
  cx.rank = blockIdx.x & 1;
  const int warp = __shfl_sync(0xffffffffu, threadIdx.x >> 5, 0);
  const int cluster = blockIdx.x >> 1;
  const bool is_aux = blockIdx.x >= N_ATT_CTA;
  const int c7 = ((cluster - 36) * 37) >> 8;
  const int hs = cluster < 4 ? 4 + cluster : cluster < 36 ? (cluster - 4) >> 3 : 4 + c7;
  const int qb = (cluster < 4 ? 0 : cluster < 36 ? (cluster - 4) & 7 : cluster - 35 - 7 * c7) * 2 + cx.rank;

  extern __shared__ __align__(1024) uint8_t smem_alias[];
  const uint32_t xf = smem_u32(smem_alias) + SM_MISC + warp * 24;
  if (warp == 4 && elect_one()) prefetch_tmap(&tmX);
  if (elect_one()) {
    const uint32_t cnt = (warp > 4 && warp < 8) ? (is_aux ? 2 : 4) : 1;
#pragma unroll
    for (int i = 0; i < 3; i++) mbar_init(xf + 8 * i, cnt);
    asm volatile("fence.proxy.async.shared::cta;" ::: "memory");
    asm volatile("fence.mbarrier_init.release.cluster;" ::: "memory");
  }
  __syncwarp();
  cluster_arrive();
  if (warp == 4 && !is_aux) {
    if (elect_one()) {
      profc(0, 28);
#pragma unroll
      for (int i = 0; i < 3; i++) {
        mbar_expect_tx(xf + 8 * i, 24576);
        tma3d(xf - SM_XFULL + SM_X + i * 24576, &tmX, qb * 128, i * 3, xf + 8 * i);
      }
      profc(0, 29);
    }
  } else if (warp > 7 && elect_one()) {
    prefetch_tmap(&tmX + (is_aux ? warp - 4 : warp == 8 ? 8 : warp - 8));
  }
  __syncwarp();

  if (warp < 4) {
    asm volatile("setmaxnreg.dec.sync.aligned.u32 24;");
    cluster_wait();
    prof(0, 24, 511);
    if (warp == 0) {
      if (!is_aux) attn_producer(cx, qb, hs, &tmX, &tmK, &tmV, &tmWq, &tmWo);
      else aux_producer(cx, blockIdx.x - N_ATT_CTA, &tmWq, &maps.m[5]);
      prof(0, 25, 511);
    } else if (!is_aux) {
      attn_rows(cx, qb, hs, 3 - warp, read_lane(), &maps.m[8], w_r);
      if (warp == 1) attn_helper(cx, qb, hs, read_lane(), wo, &maps.m[8]);
      else bar_sync(BAR_OA, 352);
      attn_finish8(cx, qb, hs, warp - 1, read_lane(), out);
    } else {
      aux_helper(cx, blockIdx.x - N_ATT_CTA, warp, read_lane());
    }
    __syncwarp();
    cluster_arrive();
    cluster_wait();
    if (threadIdx.x == 32) { dly(cx, 201); dly(cx, 251); }
  } else {
    asm volatile("setmaxnreg.inc.sync.aligned.u32 240;");
    cluster_wait();
    const int cw = warp - 4, wg = cw >> 2;
    if (is_aux) aux_consumer(cx, blockIdx.x - N_ATT_CTA, wg, cw, read_lane());
    else attn_consumer(cx, qb, hs, wg, cw, read_lane(), x, kc, out);
  }
}

typedef CUresult (*EncodeFn)(CUtensorMap*, CUtensorMapDataType, cuuint32_t, void*, const cuuint64_t*, const cuuint64_t*,
                             const cuuint32_t*, const cuuint32_t*, CUtensorMapInterleave, CUtensorMapSwizzle,
                             CUtensorMapL2promotion, CUtensorMapFloatOOBfill);

void encode(EncodeFn fn, CUtensorMap* m, const void* p, int rank, const cuuint64_t* dims, const cuuint64_t* strides,
            const cuuint32_t* box) {
  const cuuint32_t es[5] = {1, 1, 1, 1, 1};
  fn(m, CU_TENSOR_MAP_DATA_TYPE_BFLOAT16, rank, const_cast<void*>(p), dims, strides, box, es, CU_TENSOR_MAP_INTERLEAVE_NONE,
     CU_TENSOR_MAP_SWIZZLE_128B, CU_TENSOR_MAP_L2_PROMOTION_L2_128B, CU_TENSOR_MAP_FLOAT_OOB_FILL_NONE);
}
void encode2d(EncodeFn fn, CUtensorMap* m, const void* p, uint64_t rows, uint64_t cols, uint32_t box_rows) {
  const cuuint64_t dims[2] = {cols, rows}, strides[1] = {cols * 2};
  const cuuint32_t box[2] = {64, box_rows};
  encode(fn, m, p, 2, dims, strides, box);
}

}

extern "C" void kernel_launch(void* const* d_in, const int* in_sizes, int n_in, void* d_out, int out_size) {
  (void)in_sizes; (void)n_in; (void)out_size;
  void* fnp = nullptr;
  cudaDriverEntryPointQueryResult qr;
  cudaGetDriverEntryPoint("cuTensorMapEncodeTiled", &fnp, cudaEnableDefault, &qr);
  EncodeFn fn = (EncodeFn)fnp;
  void* gs = nullptr;
  cudaGetSymbolAddress(&gs, g_scratch);
  Maps maps;
  CUtensorMap &tmX = maps.m[0], &tmWq = maps.m[1], &tmK = maps.m[2], &tmV = maps.m[3], &tmWo = maps.m[4], &tmG = maps.m[5],
              &tmU = maps.m[6], &tmD = maps.m[7];
  encode2d(fn, &tmK, d_in[1], 16 * SEQ, DH, 128);
  encode2d(fn, &tmV, d_in[2], 16 * SEQ, DH, 128);
  encode2d(fn, &tmWq, d_in[3], DM, 4096, 64);
  {
    const cuuint64_t dims[3] = {64, SEQ, 9}, strides[2] = {DM * 2, 128};
    const cuuint32_t box[3] = {64, 64, 3};
    encode(fn, &tmX, d_in[0], 3, dims, strides, box);
  }
  encode2d(fn, &maps.m[8], d_in[0], SEQ, DM, 16);
  encode2d(fn, &tmWo, d_in[4], 4096, DM, 128);
  encode2d(fn, &tmG, d_in[7], DM, FF, 192);
  encode2d(fn, &tmU, d_in[8], DM, FF, 192);
  encode2d(fn, &tmD, d_in[9], FF, DM, 192);
  cudaFuncSetAttribute(fused_kernel, cudaFuncAttributeMaxDynamicSharedMemorySize, SM_TOTAL);
  fused_kernel<<<N_CTA, THREADS, SM_TOTAL>>>((const __nv_bfloat16*)d_in[0], (const __nv_bfloat16*)d_in[6], (const __nv_bfloat16*)d_in[1],
                                            (const __nv_bfloat16*)d_in[4], (__nv_bfloat16*)d_out, (Scratch*)gs, maps);
}
```

```cpp
#include <cuda_runtime.h>
#include <cuda_bf16.h>
#include <cuda.h>
#include <stdint.h>

namespace {

constexpr int SEQ = 2048, DM = 576, DH = 128, FF = 4608, TOPC = 8;
constexpr int N_ATT_CTA = 128, N_CTA = 132;
constexpr int THREADS = 384;

constexpr uint32_t SM_RING = 0;
constexpr uint32_t STAGE = 32768;
constexpr uint32_t SM_SLOT = 131072;
constexpr uint32_t FSTAGE = 24576;
constexpr uint32_t SM_XSEL = 196608;
constexpr uint32_t SM_H = 205824;
constexpr uint32_t SM_MISC = 229376;
constexpr uint32_t SM_FULL = SM_MISC, SM_BAR_MISC = SM_MISC + 64, SM_BAR_XG = SM_MISC + 72, SM_BAR_P8 = SM_MISC + 80, SM_BAR_Q3 = SM_MISC + 88, SM_XFULL = SM_MISC + 96,
                   SM_EMPTY = SM_MISC + 120, SM_BAR_ROWS = SM_MISC + 216, SM_TAG = SM_MISC + 288,
                   SM_ROWS = SM_MISC + 304, SM_BOX8 = SM_MISC + 1024;
constexpr uint32_t SM_TOTAL = SM_MISC + 3072;
constexpr uint32_t SM_X = SM_MISC - 147456;

constexpr int BAR_ROWS = 6, BAR_HELPER = 7, BAR_OA = 8;
constexpr int NST_Q = 18, NST_KV = 128, NST_O = 18;
constexpr uint32_t SL_KE = (NST_Q - 1) & 3, SL_VE = NST_Q & 3, SL_KO = (NST_Q + 1) & 3, SL_VO = (NST_Q + 2) & 3;
#define X_N1 6
#define X_SPLIT 44
#define X_SPLIT3 36
#define X_PARK 5
#define X_C0 24
#define X_C1 32
#define X_C2 56
constexpr float SM_SCALE_LOG2 = 0.08838834764831845f * 1.4426950408889634f;

struct Scratch {
  uint4 part[16 * 64 * 2 * 4 * 128];
  uint4 gate[N_ATT_CTA * 144 * 8];
  uint4 q3[N_ATT_CTA * 1024];
  uint4 xn[SEQ * DM / 8];
  uint32_t key[SEQ];
  float ypart[4 * TOPC * DM];
  uint32_t top[32];
  unsigned launch[160];
  unsigned rows[16 * 32];
  unsigned q3_flag[N_ATT_CTA];
  unsigned ycnt;
};
__device__ __align__(1024) Scratch g_scratch;

__device__ __forceinline__ void prof(int, int, int = 0) {}

__device__ __forceinline__ uint32_t smem_u32(const void* p) { return (uint32_t)__cvta_generic_to_shared(p); }
__device__ __forceinline__ void mbar_init(uint32_t bar, uint32_t cnt) {
  asm volatile("mbarrier.init.shared::cta.b64 [%0], %1;" ::"r"(bar), "r"(cnt) : "memory");
}
__device__ __forceinline__ void mbar_expect_tx(uint32_t bar, uint32_t bytes) {
  asm volatile("mbarrier.arrive.expect_tx.shared::cta.b64 _, [%0], %1;" ::"r"(bar), "r"(bytes) : "memory");
}
__device__ __forceinline__ void mbar_arrive(uint32_t bar) {
  asm volatile("mbarrier.arrive.shared::cta.b64 _, [%0];" ::"r"(bar) : "memory");
}
__device__ __forceinline__ void mbar_arrive_cluster(uint32_t bar_cluster_addr) {
  asm volatile("mbarrier.arrive.shared::cluster.b64 _, [%0];" ::"r"(bar_cluster_addr) : "memory");
}
template <int ID>
__device__ __forceinline__ void mbar_arrive_cluster_now(uint32_t bar_cluster_addr, bool pred, uint32_t zero) {
  asm volatile("{\n.reg .pred p, q;\nsetp.ne.u32 p, %1, 0;\nsetp.eq.u32 q, %2, %3;\n"
               "ARR_LOOP:\n@p mbarrier.arrive.shared::cluster.b64 _, [%0];\n@q bra.uni ARR_LOOP;\n}"
               ::"r"(bar_cluster_addr), "r"((uint32_t)pred), "r"(zero), "n"(ID) : "memory");
}
__device__ __forceinline__ void block_fence(int id, uint32_t zero = blockIdx.y) {
  asm volatile("{\n.reg .pred q;\nsetp.eq.u32 q, %0, %1;\nBF_LOOP:\n@q st.volatile.shared.u32 [%0], %0;\n@q bra.uni BF_LOOP;\n}"
               ::"r"(zero), "r"(id) : "memory");
}
__device__ __forceinline__ bool mbar_test(uint32_t bar, uint32_t parity) {
  uint32_t ok;
  asm volatile("{\n.reg .pred p;\nmbarrier.test_wait.parity.shared::cta.b64 p, [%1], %2;\nselp.u32 %0, 1, 0, p;\n}"
               : "=r"(ok) : "r"(bar), "r"(parity) : "memory");
  return ok;
}
__device__ __forceinline__ void mbar_wait(uint32_t bar, uint32_t parity) {
  asm volatile("{\n.reg .pred p, q;\n.reg .u32 n;\nmov.u32 n, 0;\n"
               "WAIT_LOOP:\nmbarrier.try_wait.parity.shared::cta.b64 p, [%0], %1;\n"
               "add.u32 n, n, 1;\nsetp.lt.u32 q, n, 4194304;\nand.pred q, q, !p;\n@q bra WAIT_LOOP;\n}"
               ::"r"(bar), "r"(parity) : "memory");
}
__device__ __forceinline__ uint32_t mapa(uint32_t addr, uint32_t rank) {
  uint32_t r;
  asm volatile("mapa.shared::cluster.u32 %0, %1, %2;" : "=r"(r) : "r"(addr), "r"(rank));
  return r;
}
__device__ __forceinline__ void cluster_arrive() { asm volatile("barrier.cluster.arrive.relaxed.aligned;" ::: "memory"); }
__device__ __forceinline__ bool elect_one() {
  uint32_t p;
  asm volatile("{\n.reg .pred p;\nelect.sync _|p, 0xffffffff;\nselp.u32 %0, 1, 0, p;\n}" : "=r"(p));
  return p;
}
__device__ __forceinline__ int read_lane() { return threadIdx.x & 31; }
__device__ __forceinline__ void cluster_wait() { asm volatile("barrier.cluster.wait.acquire.aligned;" ::: "memory"); }
__device__ __forceinline__ void bar_sync(int id, int n) { asm volatile("barrier.cta.sync %0, %1;" ::"r"(id), "r"(n) : "memory"); }
__device__ __forceinline__ void bar_arrive(int id, int n) { asm volatile("barrier.cta.arrive %0, %1;" ::"r"(id), "r"(n) : "memory"); }

__device__ __forceinline__ uint64_t policy_evict_first() {
  uint64_t p;
  asm("createpolicy.fractional.L2::evict_first.b64 %0, 1.0;" : "=l"(p));
  return p;
}
__device__ __forceinline__ uint64_t policy_evict_normal() {
  uint64_t p;
  asm("createpolicy.fractional.L2::evict_normal.b64 %0, 1.0;" : "=l"(p));
  return p;
}
__device__ __forceinline__ void tma3d(uint32_t dst, const CUtensorMap* tm, int c1, int c2, uint32_t bar) {
  asm volatile("cp.async.bulk.tensor.3d.shared::cluster.global.mbarrier::complete_tx::bytes [%0], [%1, {%2, %3, %4}], [%5];"
               ::"r"(dst), "l"(tm), "r"(0), "r"(c1), "r"(c2), "r"(bar) : "memory");
}
__device__ __forceinline__ void tma2d(uint32_t dst, const CUtensorMap* tm, int c0, int c1, uint32_t bar) {
  asm volatile("cp.async.bulk.tensor.2d.shared::cluster.global.mbarrier::complete_tx::bytes [%0], [%1, {%2, %3}], [%4];"
               ::"r"(dst), "l"(tm), "r"(c0), "r"(c1), "r"(bar) : "memory");
}
__device__ __forceinline__ void tma2d_stream(uint32_t dst, const CUtensorMap* tm, int c0, int c1, uint32_t bar) {
  asm volatile("{\n.reg .b64 pol;\ncreatepolicy.fractional.L2::evict_first.b64 pol, 1.0;\n"
               "cp.async.bulk.tensor.2d.shared::cluster.global.mbarrier::complete_tx::bytes.L2::cache_hint [%0], [%1, {%2, %3}], [%4], pol;\n}"
               ::"r"(dst), "l"(tm), "r"(c0), "r"(c1), "r"(bar) : "memory");
}
__device__ __forceinline__ void tma2d_prefetch(const CUtensorMap* tm, int c0, int c1) {
  asm volatile("cp.async.bulk.prefetch.tensor.2d.L2.global [%0, {%1, %2}];" ::"l"(tm), "r"(c0), "r"(c1) : "memory");
}
__device__ __forceinline__ void prefetch_l2(const void* p, uint32_t bytes) {
  asm volatile("cp.async.bulk.prefetch.L2.global [%0], %1;" ::"l"(p), "r"(bytes) : "memory");
}
__device__ __forceinline__ void prefetch_tmap(const CUtensorMap* tm) {
  asm volatile("prefetch.tensormap [%0];" ::"l"(tm) : "memory");
}

__device__ __forceinline__ void wg_fence() { asm volatile("wgmma.fence.sync.aligned;" ::: "memory"); }
__device__ __forceinline__ void wg_commit() { asm volatile("wgmma.commit_group.sync.aligned;" ::: "memory"); }
template <int N> __device__ __forceinline__ void wg_wait() { asm volatile("wgmma.wait_group.sync.aligned %0;" ::"n"(N) : "memory"); }

__device__ __forceinline__ uint64_t mkdesc(uint32_t addr, uint32_t lbo_bytes) {
  return (uint64_t)(((addr & 0x3FFFF) >> 4) | ((lbo_bytes >> 4) << 16)) | ((uint64_t)0x40000040u << 32);
}
template <int N> __device__ __forceinline__ void pin(float (&a)[N]) {
#pragma unroll
  for (int i = 0; i < N; i++) asm volatile("" : "+f"(a[i])::"memory");
}
template <int N> __device__ __forceinline__ void pin(uint32_t (&a)[N]) {
#pragma unroll
  for (int i = 0; i < N; i++) asm volatile("" : "+r"(a[i])::"memory");
}

#define F8(d, o) "+f"(d[o]), "+f"(d[o + 1]), "+f"(d[o + 2]), "+f"(d[o + 3]), "+f"(d[o + 4]), "+f"(d[o + 5]), "+f"(d[o + 6]), "+f"(d[o + 7])
#define R32A "%0, %1, %2, %3, %4, %5, %6, %7, %8, %9, %10, %11, %12, %13, %14, %15, %16, %17, %18, %19, %20, %21, %22, %23, %24, %25, %26, %27, %28, %29, %30, %31"
#define R32B "%32, %33, %34, %35, %36, %37, %38, %39, %40, %41, %42, %43, %44, %45, %46, %47, %48, %49, %50, %51, %52, %53, %54, %55, %56, %57, %58, %59, %60, %61, %62, %63"

template <int TB>
__device__ __forceinline__ void mma_n128(float (&d)[64], uint32_t a0, uint32_t a1, uint32_t a2, uint32_t a3, uint64_t db, int acc) {
  asm volatile("{\n.reg .pred p;\nsetp.ne.b32 p, %69, 0;\n"
               "wgmma.mma_async.sync.aligned.m64n128k16.f32.bf16.bf16 {" R32A ", " R32B "}, {%64, %65, %66, %67}, %68, p, 1, 1, %70;\n}\n"
               : F8(d, 0), F8(d, 8), F8(d, 16), F8(d, 24), F8(d, 32), F8(d, 40), F8(d, 48), F8(d, 56)
               : "r"(a0), "r"(a1), "r"(a2), "r"(a3), "l"(db), "r"(acc), "n"(TB));
}
template <int TB>
__device__ __forceinline__ void mma_n128_ss(float (&d)[64], uint64_t da, uint64_t db, int acc) {
  asm volatile("{\n.reg .pred p;\nsetp.ne.b32 p, %66, 0;\n"
               "wgmma.mma_async.sync.aligned.m64n128k16.f32.bf16.bf16 {" R32A ", " R32B "}, %64, %65, p, 1, 1, 0, %67;\n}\n"
               : F8(d, 0), F8(d, 8), F8(d, 16), F8(d, 24), F8(d, 32), F8(d, 40), F8(d, 48), F8(d, 56)
               : "l"(da), "l"(db), "r"(acc), "n"(TB));
}
template <int TB>
__device__ __forceinline__ void mma_n64(float (&d)[32], uint32_t a0, uint32_t a1, uint32_t a2, uint32_t a3, uint64_t db, int acc) {
  asm volatile("{\n.reg .pred p;\nsetp.ne.b32 p, %37, 0;\n"
               "wgmma.mma_async.sync.aligned.m64n64k16.f32.bf16.bf16 {" R32A "}, {%32, %33, %34, %35}, %36, p, 1, 1, %38;\n}\n"
               : F8(d, 0), F8(d, 8), F8(d, 16), F8(d, 24)
               : "r"(a0), "r"(a1), "r"(a2), "r"(a3), "l"(db), "r"(acc), "n"(TB));
}
__device__ __forceinline__ void mma_n8(float (&d)[4], uint64_t da, uint64_t db, int acc) {
  asm volatile("{\n.reg .pred p;\nsetp.ne.b32 p, %6, 0;\n"
               "wgmma.mma_async.sync.aligned.m64n8k16.f32.bf16.bf16 {%0, %1, %2, %3}, %4, %5, p, 1, 1, 1, 0;\n}\n"
               : "+f"(d[0]), "+f"(d[1]), "+f"(d[2]), "+f"(d[3])
               : "l"(da), "l"(db), "r"(acc));
}
__device__ __forceinline__ void hmma_k16(float (&d)[4], uint32_t a0, uint32_t a1, uint32_t a2, uint32_t a3, uint32_t b0, uint32_t b1) {
  asm volatile("mma.sync.aligned.m16n8k16.row.col.f32.bf16.bf16.f32 {%0, %1, %2, %3}, {%4, %5, %6, %7}, {%8, %9}, {%0, %1, %2, %3};"
               : "+f"(d[0]), "+f"(d[1]), "+f"(d[2]), "+f"(d[3]) : "r"(a0), "r"(a1), "r"(a2), "r"(a3), "r"(b0), "r"(b1));
}

__device__ __forceinline__ uint32_t pack2(float lo, float hi) {
  uint32_t r;
  asm("cvt.rn.bf16x2.f32 %0, %1, %2;" : "=r"(r) : "f"(hi), "f"(lo));
  return r;
}
__device__ __forceinline__ float bf_lo(uint32_t w) { return __uint_as_float(w << 16); }
__device__ __forceinline__ float bf_hi(uint32_t w) { return __uint_as_float(w & 0xFFFF0000u); }
__device__ __forceinline__ float bfr(float x) { return __uint_as_float(pack2(0.f, x)); }
__device__ __forceinline__ uint32_t sub2(uint32_t a, uint32_t b) {
  uint32_t r;
  asm("sub.rn.bf16x2 %0, %1, %2;" : "=r"(r) : "r"(a), "r"(b));
  return r;
}
__device__ __forceinline__ uint32_t add2(uint32_t a, uint32_t b) {
  uint32_t r;
  asm("add.rn.bf16x2 %0, %1, %2;" : "=r"(r) : "r"(a), "r"(b));
  return r;
}
__device__ __forceinline__ uint32_t mul2(uint32_t a, uint32_t b) {
  uint32_t r;
  asm("mul.rn.bf16x2 %0, %1, %2;" : "=r"(r) : "r"(a), "r"(b));
  return r;
}
__device__ __forceinline__ uint32_t fma2(uint32_t a, uint32_t b, uint32_t c) {
  uint32_t r;
  asm("fma.rn.bf16x2 %0, %1, %2, %3;" : "=r"(r) : "r"(a), "r"(b), "r"(c));
  return r;
}
__device__ __forceinline__ float ex2(float x) {
  float r;
  asm("ex2.approx.ftz.f32 %0, %1;" : "=f"(r) : "f"(x));
  return r;
}
__device__ __forceinline__ float rcp(float x) {
  float r;
  asm("rcp.approx.ftz.f32 %0, %1;" : "=f"(r) : "f"(x));
  return r;
}
__device__ __forceinline__ float silu_f(float t) { return t * rcp(1.0f + ex2(-1.4426950408889634f * t)); }
__device__ __forceinline__ void lds128(uint32_t a, uint32_t& x, uint32_t& y, uint32_t& z, uint32_t& w) {
  asm volatile("ld.shared.v4.u32 {%0, %1, %2, %3}, [%4];" : "=r"(x), "=r"(y), "=r"(z), "=r"(w) : "r"(a) : "memory");
}
__device__ __forceinline__ void ldsm4(uint32_t a, uint32_t& x, uint32_t& y, uint32_t& z, uint32_t& w) {
  asm volatile("ldmatrix.sync.aligned.m8n8.x4.shared.b16 {%0, %1, %2, %3}, [%4];" : "=r"(x), "=r"(y), "=r"(z), "=r"(w) : "r"(a) : "memory");
}
constexpr uint32_t TAG_BIT = 0x10000;
__device__ __forceinline__ void st_gran(uint4* p, uint32_t x, uint32_t y, uint32_t z, uint32_t w) {
  asm volatile("st.relaxed.gpu.global.v4.b32 [%0], {%1, %2, %3, %4};" ::"l"(p), "r"(x), "r"(y), "r"(z), "r"(w) : "memory");
}
__device__ __forceinline__ void ld_gran(const uint4* p, uint32_t& x, uint32_t& y, uint32_t& z, uint32_t& w) {
  asm volatile("ld.relaxed.gpu.global.v4.b32 {%0, %1, %2, %3}, [%4];" : "=r"(x), "=r"(y), "=r"(z), "=r"(w) : "l"(p) : "memory");
}
__device__ __forceinline__ void ldsm4t(uint32_t a, uint32_t& x, uint32_t& y, uint32_t& z, uint32_t& w) {
  asm volatile("ldmatrix.sync.aligned.m8n8.x4.trans.shared.b16 {%0, %1, %2, %3}, [%4];" : "=r"(x), "=r"(y), "=r"(z), "=r"(w) : "r"(a) : "memory");
}
__device__ __forceinline__ void stsm4t(uint32_t a, uint32_t x, uint32_t y, uint32_t z, uint32_t w) {
  asm volatile("stmatrix.sync.aligned.m8n8.x4.trans.shared.b16 [%0], {%1, %2, %3, %4};" ::"r"(a), "r"(x), "r"(y), "r"(z), "r"(w) : "memory");
}
__device__ __forceinline__ void stsm4(uint32_t a, uint32_t x, uint32_t y, uint32_t z, uint32_t w) {
  asm volatile("stmatrix.sync.aligned.m8n8.x4.shared.b16 [%0], {%1, %2, %3, %4};" ::"r"(a), "r"(x), "r"(y), "r"(z), "r"(w) : "memory");
}
template <class T>
__device__ __forceinline__ T* at(const void* base, uint32_t off) {
  uint64_t r;
  asm("{\n.reg .u32 lo, hi;\nmov.b64 {lo, hi}, %1;\nadd.cc.u32 lo, lo, %2;\naddc.u32 hi, hi, 0;\nmov.b64 %0, {lo, hi};\n}"
      : "=l"(r) : "l"(base), "r"(off));
  return (T*)__cvta_global_to_generic(r);
}
__device__ __forceinline__ void add_granules(float (&red)[32], const uint32_t (&g)[16]) {
#pragma unroll
  for (int i = 0; i < 16; i++) { red[2 * i] += bf_lo(g[i]); red[2 * i + 1] += bf_hi((i & 3) ? g[i] : g[i] & ~TAG_BIT); }
}
__device__ __forceinline__ bool granules_ok(const uint32_t (&g)[16], uint32_t tag) {
  uint32_t u, v;
  asm("lop3.b32 %0, %1, %2, %3, 0x7E;" : "=r"(u) : "r"(g[0]), "r"(g[4]), "r"(tag));
  asm("lop3.b32 %0, %1, %2, %3, 0x7E;" : "=r"(v) : "r"(g[8]), "r"(g[12]), "r"(tag));
  return __all_sync(0xffffffffu, ((u | v) & TAG_BIT) == 0);
}
__device__ __forceinline__ unsigned ld_acquire(const unsigned* p) {
  unsigned v;
  asm volatile("ld.acquire.gpu.global.u32 %0, [%1];" : "=r"(v) : "l"(p) : "memory");
  return v;
}
__device__ __forceinline__ void red_release(unsigned* p) {
  asm volatile("red.release.gpu.global.add.u32 [%0], 1;" ::"l"(p) : "memory");
}
__device__ __forceinline__ void st_release(unsigned* p, unsigned v) {
  asm volatile("st.release.gpu.global.u32 [%0], %1;" ::"l"(p), "r"(v) : "memory");
}

template <int K0, int K1>
__device__ __forceinline__ void ln_fetch(uint32_t (&xa)[144], uint32_t boxes, uint32_t lo) {
#pragma unroll
  for (int k = K0; k < K1; k++) ldsm4(((boxes + lo) ^ ((k & 3) << 5)) + (k >> 2) * 8192, xa[4 * k], xa[4 * k + 1], xa[4 * k + 2], xa[4 * k + 3]);
}
template <int K0, int K1>
__device__ __forceinline__ void ln_sums(const uint32_t (&xa)[144], float (&sm)[4][4]) {
#pragma unroll
  for (int k = K0; k < K1; k++) hmma_k16(sm[k & 3], xa[4 * k], xa[4 * k + 1], xa[4 * k + 2], xa[4 * k + 3], 0x3F803F80u, 0x3F803F80u);
}
__device__ __forceinline__ uint32_t sq8(const uint32_t* a) {
  uint32_t t, u;
  asm("mul.rn.bf16x2 %0, %1, %1;" : "=r"(t) : "r"(a[0]));
  asm("mul.rn.bf16x2 %0, %1, %1;" : "=r"(u) : "r"(a[2]));
#pragma unroll
  for (int i = 4; i < 16; i += 4) {
    asm("fma.rn.bf16x2 %0, %1, %1, %0;" : "+r"(t) : "r"(a[i]));
    asm("fma.rn.bf16x2 %0, %1, %1, %0;" : "+r"(u) : "r"(a[i + 2]));
  }
  return add2(t, u);
}
__device__ __forceinline__ void ln_centre(uint32_t (&xa)[144], int j0, int j1, uint32_t mm0, uint32_t mm1, float& sq0, float& sq1) {
#pragma unroll
  for (int j = 0; j < 72; j += 8)
    if (j >= j0 && j < j1) {
#pragma unroll
      for (int k = j; k < j + 8; k++) {
        xa[2 * k] = sub2(xa[2 * k], mm0);
        xa[2 * k + 1] = sub2(xa[2 * k + 1], mm1);
      }
      const uint32_t t0 = sq8(xa + 2 * j), t1 = sq8(xa + 2 * j + 1);
      sq0 += bf_lo(t0) + bf_hi(t0);
      sq1 += bf_lo(t1) + bf_hi(t1);
    }
}
__device__ __forceinline__ float ln_rstd(float var) {
  float sd;
  asm("sqrt.approx.ftz.f32 %0, %1;" : "=f"(sd) : "f"(bfr(bfr(fmaxf(var, 0.0f)) + 1e-5f)));
  return rcp(bfr(sd));
}
__device__ __forceinline__ uint32_t silu2(uint32_t t) { return pack2(silu_f(bf_lo(t)), silu_f(bf_hi(t))); }
__device__ __forceinline__ float sum8(float v) {
#pragma unroll
  for (int d = 4; d; d >>= 1) v += __shfl_xor_sync(0xffffffffu, v, d);
  return v;
}
__device__ __forceinline__ void await_count(const unsigned* p, unsigned target, unsigned sleep_ns) {
#pragma unroll 1
  for (int n = 0; n < (1 << 18) && __any_sync(0xffffffffu, (int)(ld_acquire(p) - target) < 0); n++) __nanosleep(sleep_ns);
}
__device__ __forceinline__ void bulk_load(uint32_t dst, const void* src, uint32_t bytes, uint32_t bar) {
  asm volatile("cp.async.bulk.shared::cluster.global.mbarrier::complete_tx::bytes [%0], [%1], %2, [%3];"
               ::"r"(dst), "l"(src), "r"(bytes), "r"(bar) : "memory");
}
__device__ __forceinline__ void proxy_fence() { asm volatile("fence.proxy.async;" ::: "memory"); }

template <int V> struct IC { static constexpr int value = V; };

struct Ctx {
  uint32_t sb;
  uint8_t* sp;
  uint32_t rank;
  Scratch* gs;
};

__device__ __forceinline__ void dly(const Ctx&, int) {}
__device__ __forceinline__ void load_box(uint32_t dst, const CUtensorMap* tm, int c0, int c1, uint32_t bar, uint64_t pol) {
  asm volatile("{\n.reg .pred p;\nelect.sync _|p, 0xffffffff;\n"
               "@p cp.async.bulk.tensor.2d.shared::cluster.global.mbarrier::complete_tx::bytes.multicast::cluster.L2::cache_hint"
               " [%0], [%1, {%2, %3}], [%4], %5, %6;\n}"
               ::"r"(dst), "l"(tm), "r"(c0), "r"(c1), "r"(bar), "h"((uint16_t)3), "l"(pol) : "memory");
}
template <int BOXES>
__device__ __forceinline__ void load_stage(uint32_t dst, const CUtensorMap* tm, int c0, int c1, uint32_t bar, uint32_t bytes, uint64_t pol) {
  asm volatile("{\n.reg .pred p;\nelect.sync _|p, 0xffffffff;\n"
               "@p mbarrier.arrive.expect_tx.shared::cta.b64 _, [%4], %7;\n"
               "@p cp.async.bulk.tensor.2d.shared::cluster.global.mbarrier::complete_tx::bytes.multicast::cluster.L2::cache_hint"
               " [%0], [%1, {%2, %3}], [%4], %5, %6;\n}"
               ::"r"(dst), "l"(tm), "r"(c0), "r"(c1), "r"(bar), "h"((uint16_t)3), "l"(pol), "r"(bytes) : "memory");
  if (BOXES == 2) load_box(dst + 8192, tm, c0, c1 + 64, bar, pol);
}
__device__ __forceinline__ void attn_producer(const Ctx& cx, int qb, int hs, const CUtensorMap* tmX, const CUtensorMap* tmK,
                                              const CUtensorMap* tmV, const CUtensorMap* tmWq, const CUtensorMap* tmWo) {
  const uint32_t full = cx.sb + SM_FULL, empty = cx.sb + SM_EMPTY, ring = cx.sb + SM_RING + cx.rank * 16384;
  const uint64_t keep = policy_evict_normal(), last_use = policy_evict_first();
  auto acquire = [&](int st) {
    mbar_wait(empty + 8 * (st & 3), ((st >> 2) ^ ((st & 3) >> 1) ^ 1) & 1);
    if (st > 3) dly(cx, st);
  };
  if (elect_one()) {
#pragma unroll
    for (int j = 0; j < 3; j++) {
      mbar_expect_tx(cx.sb + SM_XFULL + 96 + 8 * j, 24576);
      tma3d(cx.sb + SM_X + 73728 + j * 24576, tmX, qb * 128 + 64, j * 3, cx.sb + SM_XFULL + 96 + 8 * j);
    }
  }
  __syncwarp();
  const int c0 = cx.rank * 64;
#pragma unroll 1
  for (int st = 0; st < NST_Q - 1; st++) {
    const bool half = st >= 10 && st < 13;
    const int i = st - (st < 5 ? 0 : st < 10 ? 5 : half ? 10 : 13), sl = st & 3;
    const int n0 = (hs * 4 + (st < 5 ? 0 : st < 10 ? 2 : half ? 3 : 1)) * DH + (half ? 0 : c0);
    const int k0 = half ? (i < 2 ? 256 * i + 2 * c0 : 448 + c0) : (i < 3 ? 128 * i : 128 * i - 64);
    if (st == 1) mbar_wait(cx.sb + SM_XFULL + 16, 0);
    acquire(st);
    load_stage<1>(ring + sl * STAGE, tmWq, n0, k0, full + 8 * sl, i == 2 ? 16384 : (half && i) ? 24576 : 32768, last_use);
    if (i != 2 && !(half && i && c0)) load_box(ring + sl * STAGE + 8192, tmWq, n0, k0 + 64, full + 8 * sl, last_use);
    if ((st == 3 || st == 4 || st == 8) && elect_one()) {
      if (st != 4) tma2d_prefetch(tmWq, (hs * 4 + 2 - (st >> 3)) * DH + (qb & 1) * 64, (qb >> 1) * 64);
      else if (qb < 9) tma2d_prefetch(tmWq, (hs * 4 + 3) * DH, qb * 64);
    }
    __syncwarp();
  }
  int vrow = 0;
  uint64_t vpol = keep;
#pragma unroll 1
  for (int j = 0; j < 32; j++) {
    const int st = NST_Q - 1 + 4 * j, row = (hs * 2 + (j >> 4)) * SEQ + (j & 7) * 256;
    const uint64_t pol = (j & 8) ? last_use : keep;
    if (j < 7 && qb < 8 && elect_one()) tma2d_prefetch((qb & 4) ? tmV : tmK, (qb & 1) * 64, row + 256 + (qb & 2) * 64);
    __syncwarp();
    if (j == 24) mbar_wait(cx.sb + SM_BAR_Q3, 0);
    acquire(st);
    load_stage<1>(ring + SL_KE * STAGE, tmK, c0, row, full + 8 * SL_KE, 32768, pol);
    acquire(st + 1);
    if (j) load_stage<1>(ring + SL_VE * STAGE, tmV, c0, vrow, full + 8 * SL_VE, 32768, vpol);
    else load_stage<2>(ring + SL_VE * STAGE, tmWq, (hs * 4 + 1) * DH + c0, 448, full + 8 * SL_VE, 32768, last_use);
    vrow = row + 128;
    vpol = pol;
    acquire(st + 2);
    load_stage<1>(ring + SL_KO * STAGE, tmK, c0, vrow, full + 8 * SL_KO, 32768, pol);
    acquire(st + 3);
    load_stage<1>(ring + SL_VO * STAGE, tmV, c0, row, full + 8 * SL_VO, 32768, pol);
  }
  acquire(NST_Q + NST_KV - 1);
  load_stage<1>(ring + SL_KE * STAGE, tmV, c0, vrow, full + 8 * SL_KE, 32768, last_use);
#pragma unroll 1
  for (int u = 0; u < NST_O; u++) {
    const int st = NST_Q + NST_KV + u, sl = st & 3;
    const int blk = u < 4 && cx.rank ? 8 : ((hs + max(u >> 1, 1)) & 7);
    const int head = u < 4 ? u ^ (u >> 1) : ((u & 1) * 2 + cx.rank + 3) & 3;
    acquire(st);
    load_stage<1>(ring + sl * STAGE, tmWo, blk * 64, hs * 512 + head * 128, full + 8 * sl, 32768, last_use);
  }
}

__device__ __forceinline__ uint32_t xn_offset(uint32_t row, int lane) {
  return (row >> 6) * (9 * 8192) + (row & 63) * 128 + ((((lane >> 2) ^ row) & 7) << 4) + (lane & 3) * 4;
}

__device__ __forceinline__ void attn_rows(const Ctx& cx, int qb, int hs, int hw, int lane, const CUtensorMap* tmX16,
                                          const __nv_bfloat16* w_r) {
  extern __shared__ __align__(1024) uint8_t smem_rows[];
  auto box = [&](int blk) { return blk < 8 ? SM_SLOT + 2 * STAGE + 8192 + (blk >> 2) * 16384 + (blk & 3) * 2048 : SM_BOX8; };
  const uint32_t sb = smem_u32(smem_rows);
  if (hw == 0) {
    bar_sync(BAR_HELPER, 160);
    if (elect_one()) {
      mbar_expect_tx(sb + SM_BAR_ROWS, 9 * 2048);
#pragma unroll 1
      for (int i = 0; i < 9; i++) tma2d(sb + box(i), tmX16, i * 64, qb * 128 + hs * 16, sb + SM_BAR_ROWS);
    }
    __syncwarp();
  }
  uint32_t g = (lane >> 3) * 128 + (((lane ^ (lane >> 3)) & 7) << 4);
  auto next = [&]() {
    g = ((g + 512) & 2047) ^ 64;
    asm volatile("" : "+r"(g));
  };
  float* const part = (float*)(smem_rows + SM_ROWS);
  mbar_wait(sb + SM_BAR_ROWS, 0);
  if (hw == 0) dly(cx, 190);
#pragma unroll 1
  for (int i = 0; i < 4; i++) {
    float a = 0.f, b = 0.f;
#pragma unroll
    for (int j = 0; j < 3; j++) {
      const uint4 v = *(const uint4*)(smem_rows + box(hw * 3 + j) + g);
      const uint32_t w[4] = {v.x, v.y, v.z, v.w};
#pragma unroll
      for (int k = 0; k < 4; k++) {
        a += bf_lo(w[k]) + bf_hi(w[k]);
        b = fmaf(bf_lo(w[k]), bf_lo(w[k]), fmaf(bf_hi(w[k]), bf_hi(w[k]), b));
      }
    }
    a = sum8(a);
    b = sum8(b);
    float* p = part + hw * 16 + (g >> 7);
    p[0] = a;
    p[48] = b;
    next();
  }
  bar_sync(BAR_ROWS, 96);
  if (hw == 0) dly(cx, 191);
  {
    const float* p = part + (lane & 15);
    const float mean = (p[0] + p[16] + p[32]) * (1.0f / DM), rstd = ln_rstd((p[48] + p[64] + p[80]) * (1.0f / DM) - mean * mean);
    const uint32_t mm = pack2(mean, mean), rr = pack2(rstd - bfr(rstd), rstd);
#pragma unroll 1
    for (int u = hw * 12; u < hw * 12 + 12; u++) {
      const int blk = u >> 2;
      uint4* q = (uint4*)(smem_rows + box(blk) + g);
      uint4 v = *q;
      const uint32_t m = __shfl_sync(0xffffffffu, mm, g >> 7), r = __shfl_sync(0xffffffffu, rr, g >> 7);
      const uint32_t hi = __byte_perm(r, 0, 0x3232), lo = __byte_perm(r, 0, 0x1010);
      auto norm = [&](uint32_t w) {
        const uint32_t xc = sub2(w, m);
        return fma2(xc, hi, mul2(xc, lo));
      };
      v = make_uint4(norm(v.x), norm(v.y), norm(v.z), norm(v.w));
      *q = v;
      *at<uint4>(cx.gs->xn + ((qb * 2 + (hs >> 2)) * 9 + blk) * 512 + (hs & 3) * 128, g) = v;
      next();
    }
  }
  bar_sync(BAR_ROWS, 96);
  if (hw == 0) {
    dly(cx, 192);
    if (lane == 0) red_release(&cx.gs->rows[qb * 32]);
    dly(cx, 193);
  }
#pragma unroll 1
  for (int u = hw ? 13 * hw - 3 : 0; u < 13 * hw + 10; u++) {
    const int blk = u >> 2;
    const uint32_t o = (g + (u & 3) * 512) ^ ((u & 1) << 6);
    const uint4 v = *(const uint4*)(smem_rows + box(blk) + o);
    *at<uint4>(cx.gs->gate + (blk < 8 ? (qb * 8 + blk) * 144 + hs * 16 : (qb * 8 + hs) * 144 + 128) * 8, o) =
        make_uint4(silu2(v.x), silu2(v.y), silu2(v.z), silu2(v.w));
  }
  if (hw) dly(cx, 194 + hw);
  __nanosleep(5000);
#pragma unroll 1
  for (int blk = hw * 3; blk < hw * 3 + 3; blk++) {
    const uint4 c = __ldg(at<const uint4>(w_r, blk * 128 + ((g ^ (g >> 3)) & 0x70)));
#pragma unroll 1
    for (int i = 0; i < 4; i++) {
      const uint4 v = *(const uint4*)(smem_rows + box(blk) + g);
      part[blk * 16 + (g >> 7)] =
          sum8(fmaf(bf_lo(v.x), bf_lo(c.x), fmaf(bf_hi(v.x), bf_hi(c.x), fmaf(bf_lo(v.y), bf_lo(c.y), bf_hi(v.y) * bf_hi(c.y)))) +
               fmaf(bf_lo(v.z), bf_lo(c.z), fmaf(bf_hi(v.z), bf_hi(c.z), fmaf(bf_lo(v.w), bf_lo(c.w), bf_hi(v.w) * bf_hi(c.w)))));
      next();
    }
  }
  bar_sync(BAR_ROWS, 96);
  if (hw == 0) {
    dly(cx, 194);
    float d = 0.f;
#pragma unroll
    for (int j = 0; j < 9; j++) d += part[j * 16 + (lane & 15)];
    const uint32_t row = qb * 128 + hs * 16 + (lane & 15), b = pack2(0.f, d);
    *at<uint32_t>(cx.gs->key, row * 4) = (b ^ ((int)b < 0 ? 0xFFFF0000u : 0x80000000u)) + 0xFFFF - row;
    __syncwarp();
    if (lane == 0) red_release(&cx.gs->rows[qb * 32 + 1]);
  }
}

constexpr uint32_t SM_XO = SM_SLOT, SM_GO = SM_SLOT + STAGE, SM_P8 = SM_SLOT + 2 * STAGE;
__device__ __forceinline__ void attn_helper(const Ctx& cx, int qb, int hs, int lane, const __nv_bfloat16* wo, const CUtensorMap* tmX16) {
  unsigned e = 0;
  if (lane == 0) {
    e = cx.gs->launch[blockIdx.x];
    cx.gs->launch[blockIdx.x] = e + 1;
  }
  e = __shfl_sync(0xffffffffu, e, 0);
  if (lane == 0) {
    *(uint32_t*)(cx.sp + SM_TAG) = (~e & 1) * TAG_BIT;
    mbar_arrive(cx.sb + SM_BAR_MISC);
  }
  bar_sync(BAR_HELPER, 64);
  await_count(&cx.gs->rows[qb * 32 + 1], 8 * (e + 1), 1000);
  await_count(&cx.gs->q3_flag[qb * 8 + hs], e + 1, 1000);
  proxy_fence();
  if (elect_one()) {
    mbar_expect_tx(cx.sb + SM_BAR_Q3, 16384);
#pragma unroll
    for (int i = 0; i < 2; i++) bulk_load(cx.sb + SM_SLOT + 2 * STAGE + i * 16384 + 8192, cx.gs->q3 + (qb * 16 + hs * 2 + i) * 512, 8192, cx.sb + SM_BAR_Q3);
  }
  __syncwarp();
  bar_sync(BAR_HELPER, 64);
  prefetch_l2(at<const void>(wo, (hs * 512 + qb * 32 + lane) * (DM * 2)), DM * 2);
  await_count(&cx.gs->ycnt, 4 * (e + 1), 500);
  const uint32_t mykey = __ldcg(at<const uint32_t>(cx.gs->top, (lane >> 1) * 4)), myrow = 0xFFFF - (mykey & 0xFFFF);
#pragma unroll 1
  for (uint32_t todo = __ballot_sync(0xffffffffu, lane < 16 && ((lane & 1) ? myrow >> 4 == qb * 8 + hs : myrow >> 7 == qb)); todo; todo &= todo - 1) {
    const int i = __ffs(todo) - 1, blk = (i & 1) ? 8 : hs;
    const uint32_t key = __shfl_sync(0xffffffffu, mykey, i), row = 0xFFFF - (key & 0xFFFF), o = xn_offset(row, lane);
    const uint32_t t = __ldcg(at<const uint32_t>(cx.gs->xn, o + blk * 8192));
    const float2* p = at<const float2>(cx.gs->ypart, ((i >> 1) * DM + blk * 64 + 2 * lane) * 4);
    const float2 y0 = __ldcg(p), y1 = __ldcg(p + TOPC * DM / 2), y2 = __ldcg(p + TOPC * DM), y3 = __ldcg(p + 3 * TOPC * DM / 2);
    const float rs = bfr(rcp(1.0f + ex2(-1.4426950408889634f * bf_hi(key ^ ((int)key < 0 ? 0x80000000u : 0xFFFF0000u)))));
    const uint32_t y = pack2((y0.x + y1.x) + (y2.x + y3.x), (y0.y + y1.y) + (y2.y + y3.y));
    const uint32_t u = pack2(bf_lo(y) * rs, bf_hi(y) * rs);
    *at<uint32_t>(cx.gs->gate, ((qb * 8 + hs) * 144 + ((i & 1) ? 128 + (row & 15) : row & 127)) * 128 + (o & 127)) = silu2(add2(t, u));
  }
  proxy_fence();
  bar_sync(BAR_OA, 352);
  if (elect_one()) {
    const uint32_t bar = cx.sb + SM_BAR_XG;
    mbar_expect_tx(bar, 2 * 144 * 128);
    bulk_load(cx.sb + SM_GO, cx.gs->gate + (qb * 8 + hs) * (144 * 8), 144 * 128, bar);
#pragma unroll 1
    for (int i = 0; i < 9; i++) tma2d_stream(cx.sb + SM_XO + i * 2048, tmX16, i < 8 ? hs * 64 : 512, qb * 128 + (i < 8 ? i : hs) * 16, bar);
  }
  __syncwarp();
  const uint4* src = cx.gs->part + (qb * 64 + 56 + hs) * 1024;
#pragma unroll 1
  for (int n = 0; n < (1 << 16); n++) {
    __nanosleep(n ? 400 : 700);
    uint32_t a, b, d, t;
    ld_gran(at<const uint4>(src, (lane & 7) * 2048 + 2032), a, b, d, t);
    if (__all_sync(0xffffffffu, ((a >> 16) ^ e) & 1)) break;
  }
  if (elect_one()) {
    mbar_expect_tx(cx.sb + SM_BAR_P8, 16384);
    bulk_load(cx.sb + SM_P8, src, 16384, cx.sb + SM_BAR_P8);
  }
  __syncwarp();
}
__device__ __forceinline__ void attn_finish8(const Ctx& cx, int qb, int hs, int hw, int lane, __nv_bfloat16* out) {
  const uint32_t tag = *(const uint32_t*)(cx.sp + SM_TAG);
  mbar_wait(cx.sb + SM_BAR_P8, 0);
  mbar_wait(cx.sb + SM_BAR_XG, 0);
#pragma unroll 1
  for (int g = 2 - hw; g < 4; g += 3) {
    float acc[8] = {0.f, 0.f, 0.f, 0.f, 0.f, 0.f, 0.f, 0.f};
    uint32_t a[4];
#pragma unroll 1
    for (uint32_t o = g * 512 + lane * 16; o < 16384; o += 2048) {
      lds128(cx.sb + SM_P8 + o, a[0], a[1], a[2], a[3]);
#pragma unroll 1
      for (int n = 0; n < (1 << 16) && __any_sync(0xffffffffu, (a[0] & TAG_BIT) != tag); n++)
        ld_gran(at<const uint4>(cx.gs->part, (qb * 64 + 56 + hs) * 16384 + o), a[0], a[1], a[2], a[3]);
      a[0] &= ~TAG_BIT;
#pragma unroll
      for (int j = 0; j < 4; j++) { acc[2 * j] += bf_lo(a[j]); acc[2 * j + 1] += bf_hi(a[j]); }
    }
    asm volatile("" : "+r"(lane));
    const uint32_t tile = cx.sb + SM_XO + (128 + (lane & 15)) * 128 + (((lane >> 4) ^ (lane & 7)) << 4);
    uint32_t b[4];
    ldsm4((tile ^ (g << 5)) + STAGE, a[0], a[1], a[2], a[3]);
    ldsm4(tile ^ (g << 5), b[0], b[1], b[2], b[3]);
    stsm4(tile ^ (g << 5), fma2(pack2(acc[0], acc[1]), a[0], b[0]), fma2(pack2(acc[2], acc[3]), a[1], b[1]),
          fma2(pack2(acc[4], acc[5]), a[2], b[2]), fma2(pack2(acc[6], acc[7]), a[3], b[3]));
  }
  bar_sync(BAR_ROWS, 96);
#pragma unroll 1
  for (int ch = threadIdx.x - 32; ch < 128; ch += 96)
    *at<uint4>(out, ((qb * 128 + hs * 16 + (ch >> 3)) * DM + 512 + (ch & 7) * 8) * 2) =
        *(const uint4*)(cx.sp + SM_XO + (128 + (ch >> 3)) * 128 + (((ch ^ (ch >> 3)) & 7) << 4));
}

constexpr float SUM_HI = 1.8446744e19f, SUM_LO = 9.0949470e-13f;

__device__ __forceinline__ void softmax_shift(float (&s)[64], float n0, float n1) {
#pragma unroll
  for (int i = 0; i < 64; i++) s[i] += (i & 2) ? n1 : n0;
}
template <int LO, int HI>
__device__ __forceinline__ void softmax_exp(float (&s)[64]) {
#pragma unroll
  for (int i = LO; i < HI; i++) s[i] = ex2(s[i]);
}
__device__ __forceinline__ void row_sums(const uint32_t (&pf)[32], float& l0, float& l1) {
  uint32_t t[16];
#pragma unroll
  for (int i = 0; i < 16; i++) t[i] = add2(pf[(i >> 1) * 4 + (i & 1)], pf[(i >> 1) * 4 + 2 + (i & 1)]);
#pragma unroll
  for (int i = 0; i < 8; i++) t[i] = add2(t[(i >> 1) * 4 + (i & 1)], t[(i >> 1) * 4 + 2 + (i & 1)]);
#pragma unroll
  for (int i = 0; i < 4; i++) t[i] = add2(t[(i >> 1) * 4 + (i & 1)], t[(i >> 1) * 4 + 2 + (i & 1)]);
  l0 += (bf_lo(t[0]) + bf_lo(t[2])) + (bf_hi(t[0]) + bf_hi(t[2]));
  l1 += (bf_lo(t[1]) + bf_lo(t[3])) + (bf_hi(t[1]) + bf_hi(t[3]));
}
__device__ __forceinline__ void softmax_redo(uint32_t (&pf)[32], const uint32_t (&q)[32], const __nv_bfloat16* kblk, int lane, float& n0,
                                             float& n1, float& l0, float& l1, float& sc0, float& sc1) {
  float x0 = -n0, x1 = -n1;
#pragma unroll 1
  for (int u = 0; u < 16; u++) {
    const uint32_t* kp = (const uint32_t*)(kblk + ((u & 7) * 16 + (lane >> 2)) * DH) + (lane & 3);
    float d[2][4] = {};
#pragma unroll
    for (int k = 0; k < 16; k++)
      hmma_k16(d[k & 1], q[2 * (k & 14)], q[2 * (k & 14) + 1], q[2 * (k & 14) + 2], q[2 * (k & 14) + 3],
               kp[(k & 1) * 4 * DH + (k >> 1) * 8], kp[(k & 1) * 4 * DH + (k >> 1) * 8 + 4]);
    if (u < 8) {
      x0 = fmaxf(fmaxf(x0, fmaxf(d[0][0], d[0][1])), fmaxf(d[1][0], d[1][1]));
      x1 = fmaxf(fmaxf(x1, fmaxf(d[0][2], d[0][3])), fmaxf(d[1][2], d[1][3]));
      if (u == 7) {
#pragma unroll
        for (int m = 1; m < 4; m <<= 1) {
          x0 = fmaxf(x0, __shfl_xor_sync(0xffffffffu, x0, m));
          x1 = fmaxf(x1, __shfl_xor_sync(0xffffffffu, x1, m));
        }
        sc0 = ex2(-x0 - n0);
        sc1 = ex2(-x1 - n1);
        n0 = -x0;
        n1 = -x1;
        l0 *= sc0;
        l1 *= sc1;
      }
    } else {
#pragma unroll
      for (int i = 0; i < 28; i++) pf[i] = pf[i + 4];
#pragma unroll
      for (int i = 0; i < 4; i++) {
        const float n = (i & 1) ? n1 : n0;
        pf[28 + i] = pack2(ex2(d[i >> 1][(i & 1) * 2] + n), ex2(d[i >> 1][(i & 1) * 2 + 1] + n));
        ((i & 1) ? l1 : l0) += bf_lo(pf[28 + i]) + bf_hi(pf[28 + i]);
      }
    }
  }
}

#define TH(i)
__device__ __forceinline__ void attn_consumer(const Ctx& cx, int qb, int hs, int wg, int cw, int lane, const __nv_bfloat16* x,
                                              const __nv_bfloat16* kc, __nv_bfloat16* out) {
  const uint32_t full = cx.sb + SM_FULL;
  const uint32_t ring = cx.sb + SM_RING;
  uint32_t lo = ((cw & 3) * 16 + (lane & 15)) * 128 + (((lane >> 4) ^ (lane & 7)) << 4);
  const uint32_t slot = cx.sb + SM_SLOT + wg * 16384;
  auto frag = [&](int sl, int k) { return ((slot + sl * STAGE + lo) ^ ((k & 3) << 5)) + (k >> 2) * 8192; };
  auto park = [&](const float (&a)[64], int sl, int k0, int k1, float f0, float f1) {
#pragma unroll
    for (int k = 0; k < 8; k++)
      if (k >= k0 && k < k1)
        stsm4(frag(sl, k), pack2(a[8 * k] * f0, a[8 * k + 1] * f0), pack2(a[8 * k + 2] * f1, a[8 * k + 3] * f1),
              pack2(a[8 * k + 4] * f0, a[8 * k + 5] * f0), pack2(a[8 * k + 6] * f1, a[8 * k + 7] * f1));
  };
  const bool signaller = lane == 0 && (cw & 3) < 2;
  int my_turn = 1 + wg, other_turn = 2 - wg;

  uint32_t pf[32], q[32], empty_c;
  float o[64], l0, l1;
  {
    uint32_t xa[144];
    float rstd0, rstd1;
    {
      const uint32_t xb = cx.sb + SM_X + wg * 73728, xf = cx.sb + SM_XFULL + wg * 96;
      float sm[4][4] = {};
      prof(wg, 0);
      empty_c = mapa(cx.sb + SM_EMPTY, cw & 1);
      mbar_wait(xf, 0);
      TH(0)
      ln_fetch<0, 12>(xa, xb, lo);
      mbar_wait(xf + 8, 0);
      TH(1)
      ln_fetch<12, 24>(xa, xb, lo);
      ln_sums<0, 12>(xa, sm);
      mbar_wait(xf + 16, 0);
      TH(2)
      ln_fetch<24, 36>(xa, xb, lo);
      ln_sums<12, 36>(xa, sm);
      block_fence(36);
      if (wg) bar_arrive(other_turn, 256);
      block_fence(35);
      TH(3)
      rstd0 = ((sm[0][0] + sm[1][0]) + (sm[2][0] + sm[3][0])) * (1.0f / DM);
      rstd1 = ((sm[0][2] + sm[1][2]) + (sm[2][2] + sm[3][2])) * (1.0f / DM);
    }
    const uint32_t mm0 = pack2(rstd0, rstd0), mm1 = pack2(rstd1, rstd1);
    rstd0 -= bf_lo(mm0);
    rstd1 -= bf_lo(mm1);
    rstd0 *= rstd0 * (-0.25f * DM);
    rstd1 *= rstd1 * (-0.25f * DM);
    auto ln_finish = [&]() {
      rstd0 += __shfl_xor_sync(0xffffffffu, rstd0, 1); rstd1 += __shfl_xor_sync(0xffffffffu, rstd1, 1);
      rstd0 += __shfl_xor_sync(0xffffffffu, rstd0, 2); rstd1 += __shfl_xor_sync(0xffffffffu, rstd1, 2);
      rstd0 = ln_rstd(rstd0 * (1.0f / DM)) * SM_SCALE_LOG2;
      rstd1 = ln_rstd(rstd1 * (1.0f / DM)) * SM_SCALE_LOG2;
    };
    ln_centre(xa, 0, X_C0, mm0, mm1, rstd0, rstd1);
    if (wg == 0) {
      bar_sync(4, 128);
      if (signaller) {
        asm volatile("mbarrier.arrive.shared::cluster.b64 _, [%0], 2;" ::"r"(empty_c + 16) : "memory");
        asm volatile("mbarrier.arrive.shared::cluster.b64 _, [%0], 2;" ::"r"(empty_c + 24) : "memory");
      }
      block_fence(37);
      pin(xa);
      ln_centre(xa, X_C0, X_C1, mm0, mm1, rstd0, rstd1);
    }
    pin(xa);

    extern __shared__ __align__(1024) uint8_t smem_q[];
    const uint32_t ring = smem_u32(smem_q) + SM_RING;
    auto release = [&](int st) { if (signaller) mbar_arrive_cluster(empty_c + 8 * (st & 3)); };
    auto q_stage = [&](float (&acc)[64], int st, int i, int last) {
      mbar_wait(full + 8 * (st & 3), (st >> 2) & 1);
      if (i != (wg ? last : 1)) bar_sync(my_turn, 256);
      wg_fence();
      const uint64_t db = mkdesc(ring + (st & 3) * STAGE, 16384);
#pragma unroll
      for (int k = 0; k < 8; k++) {
        const int kb = (i < 3 ? 8 * i : 8 * i - 4) + k;
        if (i != 2 || k < 4) mma_n128<1>(acc, xa[4 * kb], xa[4 * kb + 1], xa[4 * kb + 2], xa[4 * kb + 3], db + k * 128, kb > 0);
      }
      wg_commit();
      if (i != (wg ? last - 1 : 0)) bar_arrive(other_turn, 256);
    };
    auto q_release = [&](int st, int i, int last) {
      if (i == 1 || i == last) {
        wg_wait<1>();
        if (i == last || !wg) release(st - 1);
      }
      if (i != last - 1 && (i || wg)) {
        wg_wait<0>();
        release(st);
      }
    };
    {
      float (&acc)[64] = o;
#pragma unroll 1
      for (int p = 0; p < 2; p++) {
#pragma unroll
        for (int i = 0; i < 5; i++) {
          q_stage(acc, 5 * p + i, i, 4);
          if (p == 0 && i != 3) {
            if (i == 0 && wg) bar_arrive(BAR_HELPER, 160);
            if ((wg || i) && i < 3) ln_centre(xa, i == 0 ? X_C0 : i == 1 ? X_C1 : X_C2, i == 0 ? X_C1 : i == 1 ? X_C2 : 72, mm0, mm1, rstd0, rstd1);
            if (i == 4) ln_finish();
            pin(xa);
          }
          q_release(5 * p + i, i, 4);
        }
        pin(acc);
#pragma unroll
        for (int k = 0; k < 8; k += 2) {
          park(acc, p, k, k + 2, rstd0, rstd1);
          if (k < 6) block_fence(40 + k);
        }
      }
    }
    {
      float (&h)[32] = *(float (*)[32])&o[0];
#pragma unroll
      for (int i = 0; i < 3; i++) {
        const uint32_t sl = (10 + i) & 3;
        mbar_wait(full + 8 * sl, ((10 + i) >> 2) & 1);
        if (i != (wg ? 2 : 1)) bar_sync(my_turn, 256);
        wg_fence();
#pragma unroll
        for (int k = 0; k < 16 - 4 * i; k++) {
          const int kb = (i == 2 ? 28 : 16 * i) + k;
          const uint64_t db = mkdesc(ring + sl * STAGE, 16) + (i == 2 && k >= 4 ? k + 4 : k) * 128;
          mma_n64<1>(h, xa[4 * kb], xa[4 * kb + 1], xa[4 * kb + 2], xa[4 * kb + 3], db, kb > 0);
        }
        wg_commit();
        if (i != (wg ? 1 : 0)) bar_arrive(other_turn, 256);
        q_release(10 + i, i, 2);
      }
      pin(h);
      park(o, 2, 0, 2, rstd0, rstd1);
      block_fence(49);
      park(o, 2, 2, 4, rstd0, rstd1);
    }
#pragma unroll
    for (int i = 0; i < 4; i++) {
      q_stage(o, 13 + i, i, 3);
      q_release(13 + i, i, 3);
    }
    prof(wg, 6);
#pragma unroll
    for (int i = 0; i < 32; i++) pf[i] = xa[112 + i];
    l0 = 0.25f * rcp(rstd0);
    l1 = 0.25f * rcp(rstd1);
  }

  uint32_t oa[96];
  const uint32_t zero = __shfl_sync(0xffffffffu, blockIdx.y, lane);
  my_turn = __shfl_sync(0xffffffffu, my_turn, lane);
  other_turn = __shfl_sync(0xffffffffu, other_turn, lane);
  lo = __shfl_sync(0xffffffffu, lo, lane);
  {
    float s[64], n0 = 0.f, n1 = 0.f;
    float lp0, lp1;
    float i0 = 0.f, i1 = 0.f;
    bool redo, shift = false;
    auto turn = [&](int it, auto kc_) -> bool {
      constexpr int KIND = decltype(kc_)::value;
      constexpr uint32_t slk = KIND == 1 ? SL_KO : SL_KE, slv = KIND == 1 ? SL_VO : SL_VE, slkn = KIND == 1 ? SL_KE : SL_KO;
      constexpr int SPLIT = KIND == 3 ? X_SPLIT3 : X_SPLIT, PARK1 = X_PARK;
      const uint32_t par = ((it + NST_Q / 2) >> 1) & 1;
      const int hsl = max((it >> 4) - 1, 0);
      const uint64_t dk = mkdesc(ring + slk * STAGE, 16), dv = mkdesc(ring + slv * STAGE, 16384);
      auto qk = [&]() {
#pragma unroll
        for (int k = 0; k < 8; k++) {
          if (KIND == 3) mma_n128_ss<0>(s, mkdesc(slot + hsl * STAGE, 16) + (k >> 2) * 512 + (k & 3) * 2, dk + (k >> 2) * 1024 + (k & 3) * 2, k > 0);
          else mma_n128<0>(s, q[4 * k], q[4 * k + 1], q[4 * k + 2], q[4 * k + 3], dk + (k >> 2) * 1024 + (k & 3) * 2, k > 0);
        }
        wg_commit();
      };
      auto pv = [&]() {
#pragma unroll
        for (int k = 0; k < 8; k++)
          mma_n128<1>(o, pf[4 * k], pf[4 * k + 1], pf[4 * k + 2], pf[4 * k + 3], dv + k * 128, k > 0 || KIND != 1 || (it & 15) != 1);
        wg_commit();
      };
      lp0 = l0; lp1 = l1;
#define TS(i)
      {
        TS(0)
        if (KIND == 3) {
          asm volatile("fence.proxy.async.shared::cta;" ::: "memory");
          const float t0 = lp0 + __shfl_xor_sync(0xffffffffu, lp0, 1), t1 = lp1 + __shfl_xor_sync(0xffffffffu, lp1, 1);
          i0 = rcp(t0 + __shfl_xor_sync(0xffffffffu, t0, 2));
          i1 = rcp(t1 + __shfl_xor_sync(0xffffffffu, t1, 2));
          asm volatile("" : "+f"(i0), "+f"(i1)::"memory");
          block_fence(31, zero);
#pragma unroll
          for (int k = 0; k < X_N1; k++) ldsm4(frag(hsl, k), q[4 * k], q[4 * k + 1], q[4 * k + 2], q[4 * k + 3]);
        }
        bar_sync(my_turn, 256);
        TS(1)
        if (KIND != 3) pin(q);
        pin(pf); pin(o);
        wg_fence();
        qk();
        TS(2)
        mbar_wait(full + 8 * slv, par);
        if (KIND == 1 && (it & 15) == 1) {
          park(o, hsl, PARK1, 8, i0, i1);
          wg_fence();
        }
        if (KIND == 3) {
#pragma unroll
          for (int k = X_N1; k < 8; k++) ldsm4(frag(hsl, k), q[4 * k], q[4 * k + 1], q[4 * k + 2], q[4 * k + 3]);
          block_fence(32, zero);
        }
        TS(3)
        pv();
        bar_arrive(other_turn, 256);
        TS(4)
        wg_wait<1>();
      }
      pin(s);
      mbar_arrive_cluster_now<10 * KIND + 3>(empty_c + 8 * slk, signaller, zero);
      TS(5)
      if (KIND == 3) {
        shift = false;
        n0 = n1 = l0 = l1 = 0.f;
      } else if (shift) {
        softmax_shift(s, n0, n1);
        pin(s);
      }
      softmax_exp<0, SPLIT>(s);
      pin(s);
      block_fence(10 * KIND + 4, zero);
      TS(6)
      wg_wait<0>();
      pin(o); pin(pf);
      mbar_arrive_cluster_now<10 * KIND + 5>(empty_c + 8 * slv, signaller, zero);
      TS(7)
      const bool kready = mbar_test(full + 8 * slkn, par);
      softmax_exp<SPLIT, 64>(s);
#pragma unroll
      for (int i = 0; i < 32; i++) pf[i] = pack2(s[2 * i], s[2 * i + 1]);
      row_sums(pf, l0, l1);
      if (KIND == 3) {
        park(o, hsl, 0, PARK1, i0, i1);
        if (it) prof(wg, 6 + (it >> 4));
        if (it >= 32 && cw == 0) bar_arrive(BAR_HELPER, 64);
      }
      redo = !(l0 + l1 <= SUM_HI) || (KIND == 3 && fminf(l0, l1) < SUM_LO);
      const bool leave = __any_sync(0xffffffffu, redo || !kready);
      return leave;
    };
    int it = -1;
#pragma unroll 1
    while (true) {
      mbar_wait(full + 8 * ((it & 1) ? SL_KE : SL_KO), ((it + NST_Q / 2) >> 1) & 1);
      it++;
#pragma unroll 1
      while (true) {
        if (it & 1) {
          if (turn(it, IC<1>()) || it == 63) break;
          it++;
        }
        if (it & 15) {
          if (turn(it, IC<2>())) break;
        } else {
          if (turn(it, IC<3>())) break;
        }
        it++;
      }
      if (__any_sync(0xffffffffu, redo)) {
        const int j = it & 15;
        float sc0 = 1.f, sc1 = 1.f;
        if (j == 0) n0 = n1 = 3.0e38f;
        l0 = j ? lp0 : 0.f;
        l1 = j ? lp1 : 0.f;
        softmax_redo(pf, q, kc + (size_t)((hs * 2 + (it >> 5)) * SEQ + j * 128) * DH, lane, n0, n1, l0, l1, sc0, sc1);
        shift = true;
        if (j == 0) sc0 = sc1 = 1.f;
#pragma unroll
        for (int i = 0; i < 16; i++) { o[4 * i] *= sc0; o[4 * i + 1] *= sc0; o[4 * i + 2] *= sc1; o[4 * i + 3] *= sc1; }
      }
      if (it == 63) break;
    }
  }

#define TE(i) {}
  {
    constexpr int ST0 = NST_Q + NST_KV;
    float acc[32], red[32], first[32];
    uint32_t tag;
    uint4* xch;
    auto await = [&](int st) { mbar_wait(full + 8 * (st & 3), (st >> 2) & 1); };
    auto release = [&](int st) { if (signaller) mbar_arrive_cluster(empty_c + 8 * (st & 3)); };
    auto unpark = [&](int h, int k0, int k1) {
#pragma unroll
      for (int k = 0; k < 8; k++)
        if (k >= k0 && k < k1) ldsm4(frag(h, k), oa[32 * h + 4 * k], oa[32 * h + 4 * k + 1], oa[32 * h + 4 * k + 2], oa[32 * h + 4 * k + 3]);
    };
    {
      float ar[64];
      asm volatile("fence.proxy.async.shared::cta;" ::: "memory");
      await(ST0 - 1);
      unpark(1, 0, 4);
      bar_sync(my_turn, 256);
      pin(pf); pin(o);
      wg_fence();
#pragma unroll
      for (int k = 0; k < 8; k++)
        mma_n128<1>(o, pf[4 * k], pf[4 * k + 1], pf[4 * k + 2], pf[4 * k + 3], mkdesc(ring + SL_KE * STAGE, 16384) + k * 128, 1);
      wg_commit();
      block_fence(66, zero);
      l0 += __shfl_xor_sync(0xffffffffu, l0, 1); l1 += __shfl_xor_sync(0xffffffffu, l1, 1);
      l0 += __shfl_xor_sync(0xffffffffu, l0, 2); l1 += __shfl_xor_sync(0xffffffffu, l1, 2);
      float f0 = rcp(l0), f1 = rcp(l1);
      asm volatile("" : "+f"(f0), "+f"(f1)::"memory");
      await(ST0);
      unpark(1, 4, 8);
      block_fence(61, zero);
#pragma unroll
      for (int k = 0; k < 8; k++) mma_n128_ss<1>(ar, mkdesc(slot, 16) + (k >> 2) * 512 + (k & 3) * 2, mkdesc(ring + (ST0 & 3) * STAGE, 16384) + k * 128, k > 0);
      wg_commit();
      bar_arrive(other_turn, 256);
      wg_wait<1>();
      pin(o); pin(pf);
      mbar_arrive_cluster_now<62>(empty_c + 8 * SL_KE, signaller, zero);
#pragma unroll
      for (int i = 0; i < 16; i++) {
        pf[2 * i] = pack2(o[4 * i] * f0, o[4 * i + 1] * f0);
        pf[2 * i + 1] = pack2(o[4 * i + 2] * f1, o[4 * i + 3] * f1);
      }
      pin(pf);
      prof(wg, 10);
#pragma unroll
      for (int u = 1; u < 4; u++) {
        await(ST0 + u);
        wg_wait<0>();
        release(ST0 + u - 1);
        bar_sync(my_turn, 256);
        wg_fence();
#pragma unroll
        for (int k = 0; k < 8; k++) {
          const uint32_t* a = (u == 1 ? oa + 32 : u == 2 ? pf : oa + 64) + 4 * k;
          mma_n128<1>(ar, a[0], a[1], a[2], a[3], mkdesc(ring + ((ST0 + u) & 3) * STAGE, 16384) + k * 128, 1);
        }
        wg_commit();
        bar_arrive(other_turn, 256);
        if (u < 3) {
          block_fence(62 + u, zero);
          unpark(u == 1 ? 2 : 0, 0, 8);
        }
      }
      mbar_wait(cx.sb + SM_BAR_MISC, 0);
      tag = *(const volatile uint32_t*)(cx.sp + SM_TAG);
      xch = at<uint4>(cx.gs->part, (qb << 20) + lane * 16 + zero);
      tag = __shfl_sync(0xffffffffu, tag, lane);
      await(ST0 + 4);
      wg_wait<0>();
      release(ST0 + 3);
      pin(ar);
#pragma unroll
      for (int i = 0; i < 32; i++) { first[i] = ar[i]; red[i] = ar[32 + i]; }
    }
    auto send = [&](const float (&v)[32], int dst, int idx) {
      uint4* p = at<uint4>(xch, (dst * 8 + idx) * 2048);
#pragma unroll
      for (int i = 0; i < 4; i++)
        st_gran(p + i * 32, (pack2(v[8 * i], v[8 * i + 1]) & ~TAG_BIT) | tag, pack2(v[8 * i + 2], v[8 * i + 3]),
                pack2(v[8 * i + 4], v[8 * i + 5]), pack2(v[8 * i + 6], v[8 * i + 7]));
    };
    send(first, ((hs + 1) & 7) * 7, cw);
    int nrx = 1;
    auto half_step = [&](int s, auto hc, bool arrive) {
      constexpr int h = decltype(hc)::value;
      const int st = ST0 + 2 * s + h;
      const uint64_t db = mkdesc(ring + (st & 3) * STAGE, 16);
      bar_sync(my_turn, 256);
      if (h == 0) pin(pf);
#pragma unroll
      for (int i = 32 * h; i < 32 + 64 * h; i++) asm volatile("" : "+r"(oa[i])::"memory");
      wg_fence();
#pragma unroll
      for (int k = 0; k < 16; k++) {
        const int kb = h * 16 + k - 8;
        if (kb >= 0) mma_n64<1>(acc, oa[4 * kb], oa[4 * kb + 1], oa[4 * kb + 2], oa[4 * kb + 3], db + k * 128, 1);
        else mma_n64<1>(acc, pf[4 * k], pf[4 * k + 1], pf[4 * k + 2], pf[4 * k + 3], db + k * 128, k > 0);
      }
      wg_commit();
      if (arrive) bar_arrive(other_turn, 256);
    };
    auto source = [&](int n) { return at<const uint4>(xch, ((hs * 7 + n - 1) * 8 + cw) * 2048); };
    auto fetch = [&](uint32_t (&g)[16], const uint4* p) {
#pragma unroll
      for (int i = 0; i < 4; i++) ld_gran(p + i * 32, g[4 * i], g[4 * i + 1], g[4 * i + 2], g[4 * i + 3]);
    };
    uint32_t g[16];
#pragma unroll 1
    for (int s = 2; s < 8; s++) {
      const int st = ST0 + 2 * s;
      half_step(s, IC<0>(), true);
      if (s == 2) {
        bar_arrive(BAR_OA, 352);
        send(red, 56 + cw, hs);
#pragma unroll
        for (int i = 0; i < 32; i++) red[i] = 0.f;
      }
      await(st + 1);
      if (s > 3 && granules_ok(g, tag)) { add_granules(red, g); nrx++; }
      wg_wait<0>();
      if (s < 7) release(st);
      if (s > 2) fetch(g, source(nrx));
      half_step(s, IC<1>(), true);
      await(st + 2);
      wg_wait<0>();
      if (s < 7) release(st + 1);
      pin(acc);
      if (s == 7) prof(wg, 19);
      send(acc, ((hs + s) & 7) * 7 + s - 1, cw);
    }
    TE(1)
    uint32_t xv[16], gt[16];
    {
      const int s = 8;
      uint32_t g2[16];
      half_step(s, IC<0>(), true);
      TE(2)
      await(NST_Q + NST_KV + NST_O - 1);
      cluster_arrive();
      mbar_wait(cx.sb + SM_BAR_XG, 0);
      const uint32_t tile = cx.sb + SM_XO + wg * 8192 + lo;
      if (granules_ok(g, tag)) { add_granules(red, g); nrx++; }
      fetch(g, source(nrx));
      block_fence(58, zero);
      wg_wait<0>();
      TE(3)
#pragma unroll
      for (int k = 0; k < 4; k++) ldsm4((tile ^ (k << 5)) + STAGE, gt[4 * k], gt[4 * k + 1], gt[4 * k + 2], gt[4 * k + 3]);
      half_step(s, IC<1>(), wg == 0);
      TE(4)
      block_fence(56, zero);
      const bool ok = granules_ok(g, tag);
      block_fence(57, zero + ok * 1000);
      const uint4* src = source(7);
      fetch(g2, src);
#pragma unroll
      for (int k = 0; k < 4; k++) ldsm4(tile ^ (k << 5), xv[4 * k], xv[4 * k + 1], xv[4 * k + 2], xv[4 * k + 3]);
      if (ok) { add_granules(red, g); nrx++; }
      TE(5)
      block_fence(59, zero);
      wg_wait<0>();
      pin(acc);
      TE(6)
#pragma unroll
      for (int i = 0; i < 32; i++) red[i] += acc[i];
      pin(red);
      TE(7)
      int n = 7;
#pragma unroll 1
      for (int spins = 0; spins < (1 << 16); spins++) {
        if (granules_ok(g2, tag)) {
          add_granules(red, g2);
          if (--n < nrx) {
            break;
          }
          src -= 1024;
        }
        fetch(g2, src);
      }
      TE(8)
    }
    prof(wg, 20);
    TE(9)
    const uint32_t ot = ring + ((ST0 + NST_O) & 3) * STAGE + cw * (16 * 144);
    uint32_t ow[16];
#pragma unroll
    for (int i = 0; i < 16; i++) ow[i] = fma2(pack2(red[2 * i], red[2 * i + 1]), gt[i], xv[i]);
#pragma unroll
    for (int i = 0; i < 4; i++)
      stsm4(ot + (lane & 15) * 144 + (2 * i + (lane >> 4)) * 16, ow[4 * i], ow[4 * i + 1], ow[4 * i + 2], ow[4 * i + 3]);
    __syncwarp();
#pragma unroll
    for (int i = 0; i < 4; i++) {
      uint4 v;
      lds128(ot + (i * 4 + (lane >> 3)) * 144 + (lane & 7) * 16, v.x, v.y, v.z, v.w);
      at<uint4>(out, ((qb * 128 + cw * 16 + (lane >> 3)) * DM + hs * 64 + (lane & 7) * 8) * 2)[i * (4 * DM / 8)] = v;
    }
    TE(10)
    prof(wg, 22);
  }
}

constexpr int AST_X = 6, AST_F = AST_X + 96;
__device__ __forceinline__ void aux_producer(const Ctx& cx, int f, const CUtensorMap* tmWq, const CUtensorMap* tmG) {
  const uint32_t full = cx.sb + SM_FULL, empty = cx.sb + SM_EMPTY;
  __nanosleep(3000);
  if (elect_one()) {
#pragma unroll 1
    for (int st = 0; st < AST_X; st++) {
      mbar_expect_tx(full + 8 * st, FSTAGE);
#pragma unroll
      for (int i = 0; i < 3; i++)
        tma2d_stream(cx.sb + st * FSTAGE + i * 8192, tmWq, (2 * f + (st & 1)) * 512 + 448, (st >> 1) * 192 + i * 64, full + 8 * st);
    }
  }
  __syncwarp();
  mbar_wait(cx.sb + SM_BAR_MISC, 0);
  proxy_fence();
  int st = AST_X;
#pragma unroll 1
  for (; st < AST_F; st++) {
    const uint32_t sl = st & 7;
    mbar_wait(empty + 8 * sl, ((st >> 3) & 1) ^ 1);
    if (elect_one()) {
      mbar_expect_tx(full + 8 * sl, FSTAGE);
      bulk_load(cx.sb + sl * FSTAGE, cx.gs->xn + (st - AST_X) * (FSTAGE / 16), FSTAGE, full + 8 * sl);
    }
    __syncwarp();
  }
#pragma unroll 1
  for (int pair = 0; pair < 14; pair++) {
#pragma unroll 1
    for (int u = 0; u < 12; u++, st++) {
      const uint32_t sl = st & 7;
      const int unit = pair * 2 + (u & 1), k = u >> 1;
      if (unit == 27) continue;
      const bool gu = pair < 9;
      mbar_wait(empty + 8 * sl, ((st >> 3) & 1) ^ 1);
      if (elect_one()) {
        mbar_expect_tx(full + 8 * sl, FSTAGE);
        tma2d_stream(cx.sb + sl * FSTAGE, tmG + (gu ? k >= 3 : 2), gu ? f * 1152 + unit * 64 : (unit - 18) * 64,
                     gu ? (k >= 3 ? k - 3 : k) * 192 : f * 1152 + k * 192, full + 8 * sl);
      }
      __syncwarp();
    }
  }
}

constexpr int BAR_FREE = 4, BAR_TILE = 6;
__device__ __forceinline__ void aux_helper(const Ctx& cx, int f, int warp, int lane) {
  unsigned epoch = 0;
  if (lane == 0) epoch = cx.gs->launch[blockIdx.x] + 1;
  epoch = __shfl_sync(0xffffffffu, epoch, 0);
  bar_sync(BAR_OA, 96);
  if (warp == 3) {
    if (lane == 0) cx.gs->launch[blockIdx.x] = epoch;
    await_count(at<const unsigned>(cx.gs->rows, (lane & 15) * 128), 8 * epoch, 200);
    if (lane == 0) mbar_arrive(cx.sb + SM_BAR_MISC);
    prof(0, 1, 31);
    await_count(at<const unsigned>(cx.gs->rows, (lane & 15) * 128 + 4), 8 * epoch, 500);
    uint32_t bound = 0xFFFFFFFFu, m0 = 0, m1 = 0;
#pragma unroll 1
    for (int k = 0; k < TOPC; k++) {
      if (__any_sync(0xffffffffu, m0 == 0)) {
        m0 = m1 = 0;
#pragma unroll 2
        for (int i = 0; i < 16; i++) {
          const uint4 v = __ldcg(at<const uint4>(cx.gs->key, lane * 16 + i * 512));
          const uint32_t w[4] = {v.x, v.y, v.z, v.w};
#pragma unroll
          for (int j = 0; j < 4; j++) {
            const uint32_t t = w[j] <= bound ? w[j] : 0;
            m1 = max(m1, min(m0, t));
            m0 = max(m0, t);
          }
        }
      }
      uint32_t m = m0;
      m = __reduce_max_sync(0xffffffffu, m);
      bound = m - 1;
      if (m0 == m) { m0 = m1; m1 = 0; }
      if (f == 0 && lane == 0) *at<uint32_t>(cx.gs->top, k * 4) = m;
#pragma unroll
      for (int j = 0; j < 3; j++) {
        const uint32_t row = 0xFFFF - (m & 0xFFFF), i = min(j * 4 + (lane >> 3), 8);
        *(uint4*)(cx.sp + SM_XSEL + i * 1024 + k * 128 + (((lane ^ k) & 7) << 4)) =
            __ldcg(at<const uint4>(cx.gs->xn, xn_offset(row, (lane & 7) * 4) + i * 8192));
      }
    }
    asm volatile("fence.proxy.async.shared::cta;" ::: "memory");
    prof(0, 2, 31);
  } else {
    const int wg = warp - 1;
#pragma unroll 1
    for (int u = 0; u < 32; u++) {
      bar_arrive(BAR_FREE + wg, 160);
      bar_sync(BAR_TILE + wg, 160);
      if (elect_one()) {
        const int n = (u >> 1) * 8 + 2 * f + wg;
        asm volatile("cp.async.bulk.global.shared::cta.bulk_group [%0], [%1], 8192;\ncp.async.bulk.commit_group;\ncp.async.bulk.wait_group 0;"
                     ::"l"(cx.gs->q3 + (n * 2 + (u & 1)) * 512), "r"(cx.sb + SM_H + wg * 8192) : "memory");
        if (u & 1) st_release(&cx.gs->q3_flag[n], epoch);
      }
      __syncwarp();
    }
  }
  bar_arrive(3, 352);
}

__device__ __forceinline__ void aux_consumer(const Ctx& cx, int f, int wg, int cw, int lane) {
  const int r = lane >> 2, c = lane & 3, tid = cw * 32 + lane;
  const uint32_t full = cx.sb + SM_FULL, empty = cx.sb + SM_EMPTY;
  const bool signaller = (tid & 127) == 0;
  auto await = [&](int st) { mbar_wait(full + 8 * (st & 7), (st >> 3) & 1); };
  auto release = [&](int st, int cnt) {
    asm volatile("{\n.reg .pred p;\nsetp.ne.u32 p, %2, 0;\n@p mbarrier.arrive.shared::cta.b64 _, [%0], %1;\n}"
                 ::"r"(empty + 8 * (st & 7)), "r"(cnt), "r"((uint32_t)signaller) : "memory");
  };
  prof(wg, 0);
  {
    const uint32_t lt = ((lane & 7) + (lane >> 4) * 8) * 128 + ((((cw & 3) * 2 + ((lane >> 3) & 1)) ^ (lane & 7)) << 4);
    uint32_t wa[144];
#pragma unroll
    for (int i = 0; i < 3; i++) {
      await(2 * i + wg);
#pragma unroll
      for (int k = 0; k < 12; k++) {
        const int kb = 12 * i + k;
        ldsm4t(cx.sb + (2 * i + wg) * FSTAGE + k * 2048 + lt, wa[4 * kb], wa[4 * kb + 1], wa[4 * kb + 2], wa[4 * kb + 3]);
      }
    }
    bar_sync(1, 256);
#pragma unroll
    for (int i = 0; i < 3; i++) release(2 * i + wg, 2);
    if (wg) bar_arrive(1, 256);
#pragma unroll 1
    for (int st = AST_X; st < AST_F; st += 3) {
      float acc[32];
      await(st);
      await(st + 1);
      await(st + 2);
      bar_sync(1 + wg, 256);
      wg_fence();
#pragma unroll
      for (int kb = 0; kb < 36; kb++) {
        const int i = kb / 12, k = kb % 12;
        mma_n64<0>(acc, wa[4 * kb], wa[4 * kb + 1], wa[4 * kb + 2], wa[4 * kb + 3],
                   mkdesc(cx.sb + ((st + i) & 7) * FSTAGE, 16) + (k >> 2) * 512 + (k & 3) * 2, kb > 0);
        if (k == 11) wg_commit();
      }
      if (st < AST_F - 3 || !wg) bar_arrive(2 - wg, 256);
      wg_wait<1>();
      release(st, 1);
      release(st + 1, 1);
      bar_sync(BAR_FREE + wg, 160);
      wg_wait<0>();
      pin(acc);
      release(st + 2, 1);
#pragma unroll
      for (int k = 0; k < 4; k++)
        stsm4t(cx.sb + SM_H + wg * 8192 + k * 2048 + lt, pack2(acc[8 * k] * SM_SCALE_LOG2, acc[8 * k + 1] * SM_SCALE_LOG2),
               pack2(acc[8 * k + 2] * SM_SCALE_LOG2, acc[8 * k + 3] * SM_SCALE_LOG2),
               pack2(acc[8 * k + 4] * SM_SCALE_LOG2, acc[8 * k + 5] * SM_SCALE_LOG2),
               pack2(acc[8 * k + 6] * SM_SCALE_LOG2, acc[8 * k + 7] * SM_SCALE_LOG2));
      asm volatile("fence.proxy.async.shared::cta;" ::: "memory");
      bar_arrive(BAR_TILE + wg, 160);
    }
    bar_sync(3, 352);
  }
  prof(wg, 3);
#pragma unroll 1
  for (int unit = wg; unit < 27; unit += 2) {
    if (unit >> 1 == 9) {
      asm volatile("fence.proxy.async.shared::cta;" ::: "memory");
      bar_sync(3, 256);
      prof(wg, 4);
    }
    const bool gu = unit < 18;
    float a0[4], a1[4];
#pragma unroll 1
    for (int m = 0; m < 2; m++) {
      float p0[4], p1[4];
      int st = AST_F + (unit >> 1) * 12 + m * 6 + wg;
      uint32_t b = cx.sb + (gu ? SM_XSEL : SM_H + m * 9216);
#pragma unroll 1
      for (int u = 0; u < 3; u++, st += 2, b += 3072) {
        await(st);
        wg_fence();
        const uint64_t da = mkdesc(cx.sb + (st & 7) * FSTAGE, 16), db = mkdesc(b, 16);
#pragma unroll
        for (int k = 0; k < 12; k++) mma_n8((k & 1) ? p1 : p0, da + k * 128, db + (k >> 2) * 64 + (k & 3) * 2, u > 0 || k > 1);
        wg_commit();
        wg_wait<0>();
        release(st, 2);
      }
      pin(p0); pin(p1);
#pragma unroll
      for (int i = 0; i < 4; i++) { a0[i] = a1[i]; a1[i] = p0[i] + p1[i]; }
    }
#pragma unroll
    for (int i = 0; i < 4; i++) {
      const int fl = (cw & 3) * 16 + r + (i >> 1) * 8, tok = 2 * c + (i & 1);
      if (gu) {
        const float h = bfr(silu_f(bfr(a0[i]))) * bfr(a1[i]);
        *(__nv_bfloat16*)(cx.sp + SM_H + unit * 1024 + tok * 128 + (((fl >> 3) ^ tok) << 4) + (fl & 7) * 2) = __float2bfloat16_rn(h);
      } else {
        *at<float>(cx.gs->ypart, ((f * TOPC + tok) * DM + (unit - 18) * 64 + fl) * 4) = a0[i] + a1[i];
      }
    }
  }
  prof(wg, 5);
  bar_sync(3, 256);
  if (tid == 0) red_release(&cx.gs->ycnt);
  prof(wg, 6);
}

struct Maps { CUtensorMap m[9]; };
__global__ void __cluster_dims__(2, 1, 1) __launch_bounds__(THREADS, 1)
fused_kernel(const __nv_bfloat16* __restrict__ x, const __nv_bfloat16* __restrict__ w_r, const __nv_bfloat16* __restrict__ kc,
             const __nv_bfloat16* __restrict__ wo, __nv_bfloat16* __restrict__ out, Scratch* gs,
             const __grid_constant__ Maps maps) {
  const CUtensorMap &tmX = maps.m[0], &tmWq = maps.m[1], &tmK = maps.m[2], &tmV = maps.m[3], &tmWo = maps.m[4];
  extern __shared__ __align__(1024) uint8_t smem_raw[];
  prof(0, 23, 511);
  if (threadIdx.x < 72 && blockIdx.x < N_ATT_CTA)
    asm volatile("prefetch.global.L2 [%0];" ::"l"(at<const void>(x, ((blockIdx.x >> 3) * 128 + (blockIdx.x & 7) * 8) * (DM * 2) + threadIdx.x * 128)));
  Ctx cx;
  cx.sb = smem_u32(smem_raw);
  cx.sp = smem_raw;
  cx.gs = gs;
  cx.rank = blockIdx.x & 1;
  const int warp = __shfl_sync(0xffffffffu, threadIdx.x >> 5, 0);
  const int cluster = blockIdx.x >> 1;
  const bool is_aux = blockIdx.x >= N_ATT_CTA;
  const int c7 = ((cluster - 36) * 37) >> 8;
  const int hs = cluster < 4 ? 4 + cluster : cluster < 36 ? (cluster - 4) >> 3 : 4 + c7;
  const int qb = (cluster < 4 ? 0 : cluster < 36 ? (cluster - 4) & 7 : cluster - 35 - 7 * c7) * 2 + cx.rank;

  extern __shared__ __align__(1024) uint8_t smem_alias[];
  const uint32_t xf = smem_u32(smem_alias) + SM_MISC + warp * 24;
  if (warp == 4 && elect_one()) prefetch_tmap(&tmX);
  if (elect_one()) {
    const uint32_t cnt = (warp > 4 && warp < 8) ? (is_aux ? 2 : 4) : 1;
#pragma unroll
    for (int i = 0; i < 3; i++) mbar_init(xf + 8 * i, cnt);
    asm volatile("fence.proxy.async.shared::cta;" ::: "memory");
    asm volatile("fence.mbarrier_init.release.cluster;" ::: "memory");
  }
  __syncwarp();
  cluster_arrive();
  if (warp == 4 && !is_aux) {
    if (elect_one()) {
#pragma unroll
      for (int i = 0; i < 3; i++) {
        mbar_expect_tx(xf + 8 * i, 24576);
        tma3d(xf - SM_XFULL + SM_X + i * 24576, &tmX, qb * 128, i * 3, xf + 8 * i);
      }
    }
  } else if (warp > 7 && elect_one()) {
    prefetch_tmap(&tmX + (is_aux ? warp - 4 : warp == 8 ? 8 : warp - 8));
  }
  __syncwarp();

  if (warp < 4) {
    asm volatile("setmaxnreg.dec.sync.aligned.u32 24;");
    cluster_wait();
    prof(0, 24, 511);
    if (warp == 0) {
      if (!is_aux) attn_producer(cx, qb, hs, &tmX, &tmK, &tmV, &tmWq, &tmWo);
      else aux_producer(cx, blockIdx.x - N_ATT_CTA, &tmWq, &maps.m[5]);
      prof(0, 25, 511);
    } else if (!is_aux) {
      attn_rows(cx, qb, hs, 3 - warp, read_lane(), &maps.m[8], w_r);
      if (warp == 1) attn_helper(cx, qb, hs, read_lane(), wo, &maps.m[8]);
      else bar_sync(BAR_OA, 352);
      attn_finish8(cx, qb, hs, warp - 1, read_lane(), out);
    } else {
      aux_helper(cx, blockIdx.x - N_ATT_CTA, warp, read_lane());
    }
    __syncwarp();
    cluster_arrive();
    cluster_wait();
    if (threadIdx.x == 32) { dly(cx, 201); dly(cx, 251); }
  } else {
    asm volatile("setmaxnreg.inc.sync.aligned.u32 240;");
    cluster_wait();
    const int cw = warp - 4, wg = cw >> 2;
    if (is_aux) aux_consumer(cx, blockIdx.x - N_ATT_CTA, wg, cw, read_lane());
    else attn_consumer(cx, qb, hs, wg, cw, read_lane(), x, kc, out);
  }
}

typedef CUresult (*EncodeFn)(CUtensorMap*, CUtensorMapDataType, cuuint32_t, void*, const cuuint64_t*, const cuuint64_t*,
                             const cuuint32_t*, const cuuint32_t*, CUtensorMapInterleave, CUtensorMapSwizzle,
                             CUtensorMapL2promotion, CUtensorMapFloatOOBfill);

void encode(EncodeFn fn, CUtensorMap* m, const void* p, int rank, const cuuint64_t* dims, const cuuint64_t* strides,
            const cuuint32_t* box) {
  const cuuint32_t es[5] = {1, 1, 1, 1, 1};
  fn(m, CU_TENSOR_MAP_DATA_TYPE_BFLOAT16, rank, const_cast<void*>(p), dims, strides, box, es, CU_TENSOR_MAP_INTERLEAVE_NONE,
     CU_TENSOR_MAP_SWIZZLE_128B, CU_TENSOR_MAP_L2_PROMOTION_L2_128B, CU_TENSOR_MAP_FLOAT_OOB_FILL_NONE);
}
void encode2d(EncodeFn fn, CUtensorMap* m, const void* p, uint64_t rows, uint64_t cols, uint32_t box_rows) {
  const cuuint64_t dims[2] = {cols, rows}, strides[1] = {cols * 2};
  const cuuint32_t box[2] = {64, box_rows};
  encode(fn, m, p, 2, dims, strides, box);
}

}

extern "C" void kernel_launch(void* const* d_in, const int* in_sizes, int n_in, void* d_out, int out_size) {
  (void)in_sizes; (void)n_in; (void)out_size;
  void* fnp = nullptr;
  cudaDriverEntryPointQueryResult qr;
  cudaGetDriverEntryPoint("cuTensorMapEncodeTiled", &fnp, cudaEnableDefault, &qr);
  EncodeFn fn = (EncodeFn)fnp;
  void* gs = nullptr;
  cudaGetSymbolAddress(&gs, g_scratch);
  Maps maps;
  CUtensorMap &tmX = maps.m[0], &tmWq = maps.m[1], &tmK = maps.m[2], &tmV = maps.m[3], &tmWo = maps.m[4], &tmG = maps.m[5],
              &tmU = maps.m[6], &tmD = maps.m[7];
  encode2d(fn, &tmK, d_in[1], 16 * SEQ, DH, 128);
  encode2d(fn, &tmV, d_in[2], 16 * SEQ, DH, 128);
  encode2d(fn, &tmWq, d_in[3], DM, 4096, 64);
  {
    const cuuint64_t dims[3] = {64, SEQ, 9}, strides[2] = {DM * 2, 128};
    const cuuint32_t box[3] = {64, 64, 3};
    encode(fn, &tmX, d_in[0], 3, dims, strides, box);
  }
  encode2d(fn, &maps.m[8], d_in[0], SEQ, DM, 16);
  encode2d(fn, &tmWo, d_in[4], 4096, DM, 128);
  encode2d(fn, &tmG, d_in[7], DM, FF, 192);
  encode2d(fn, &tmU, d_in[8], DM, FF, 192);
  encode2d(fn, &tmD, d_in[9], FF, DM, 192);
  cudaFuncSetAttribute(fused_kernel, cudaFuncAttributeMaxDynamicSharedMemorySize, SM_TOTAL);
  fused_kernel<<<N_CTA, THREADS, SM_TOTAL>>>((const __nv_bfloat16*)d_in[0], (const __nv_bfloat16*)d_in[6], (const __nv_bfloat16*)d_in[1],
                                            (const __nv_bfloat16*)d_in[4], (__nv_bfloat16*)d_out, (Scratch*)gs, maps);
}
```

```cpp
#include <cuda_runtime.h>
#include <cuda_bf16.h>
#include <cuda.h>
#include <stdint.h>

namespace {

constexpr int SEQ = 2048, DM = 576, DH = 128, FF = 4608, TOPC = 8;
constexpr int N_ATT_CTA = 128, N_CTA = 132;
constexpr int THREADS = 384;

constexpr uint32_t SM_RING = 0;
constexpr uint32_t STAGE = 32768;
constexpr uint32_t SM_SLOT = 131072;
constexpr uint32_t FSTAGE = 24576;
constexpr uint32_t SM_XSEL = 196608;
constexpr uint32_t SM_H = 205824;
constexpr uint32_t SM_MISC = 229376;
constexpr uint32_t SM_FULL = SM_MISC, SM_BAR_MISC = SM_MISC + 64, SM_BAR_XG = SM_MISC + 72, SM_BAR_P8 = SM_MISC + 80, SM_BAR_Q3 = SM_MISC + 88, SM_XFULL = SM_MISC + 96,
                   SM_EMPTY = SM_MISC + 120, SM_BAR_ROWS = SM_MISC + 216, SM_TAG = SM_MISC + 288,
                   SM_ROWS = SM_MISC + 304, SM_BOX8 = SM_MISC + 1024;
constexpr uint32_t SM_TOTAL = SM_MISC + 3072;
constexpr uint32_t SM_X = SM_MISC - 147456;

constexpr int BAR_ROWS = 6, BAR_HELPER = 7, BAR_OA = 8;
constexpr int NST_Q = 18, NST_KV = 128, NST_O = 18;
constexpr uint32_t SL_KE = (NST_Q - 1) & 3, SL_VE = NST_Q & 3, SL_KO = (NST_Q + 1) & 3, SL_VO = (NST_Q + 2) & 3;
#define X_N1 6
#define X_SPLIT 44
#define X_SPLIT3 36
#define X_PARK 5
#define X_SC 24.f
#define X_SB 1
#define X_OK 48.f
#define X_OS 0
#define X_T4 1
#define X_DS 8000
#define X_DR 700
#define X_C0 24
#define X_C1 32
#define X_C2 56
constexpr float SM_SCALE_LOG2 = 0.08838834764831845f * 1.4426950408889634f;

struct Scratch {
  uint4 part[16 * 64 * 2 * 4 * 128];
  uint4 gate[N_ATT_CTA * 144 * 8];
  uint4 q3[N_ATT_CTA * 1024];
  uint4 xn[SEQ * DM / 8];
  uint32_t key[SEQ];
  float ypart[4 * TOPC * DM];
  uint32_t top[32];
  unsigned launch[160];
  unsigned rows[16 * 32];
  unsigned q3_flag[N_ATT_CTA];
  unsigned ycnt;
};
__device__ __align__(1024) Scratch g_scratch;

__device__ __forceinline__ void prof(int, int, int = 0) {}

__device__ __forceinline__ uint32_t smem_u32(const void* p) { return (uint32_t)__cvta_generic_to_shared(p); }
__device__ __forceinline__ void mbar_init(uint32_t bar, uint32_t cnt) {
  asm volatile("mbarrier.init.shared::cta.b64 [%0], %1;" ::"r"(bar), "r"(cnt) : "memory");
}
__device__ __forceinline__ void mbar_expect_tx(uint32_t bar, uint32_t bytes) {
  asm volatile("mbarrier.arrive.expect_tx.shared::cta.b64 _, [%0], %1;" ::"r"(bar), "r"(bytes) : "memory");
}
__device__ __forceinline__ void mbar_arrive(uint32_t bar) {
  asm volatile("mbarrier.arrive.shared::cta.b64 _, [%0];" ::"r"(bar) : "memory");
}
__device__ __forceinline__ void mbar_arrive_cluster(uint32_t bar_cluster_addr) {
  asm volatile("mbarrier.arrive.shared::cluster.b64 _, [%0];" ::"r"(bar_cluster_addr) : "memory");
}
template <int ID>
__device__ __forceinline__ void mbar_arrive_cluster_now(uint32_t bar_cluster_addr, bool pred, uint32_t zero) {
  asm volatile("{\n.reg .pred p, q;\nsetp.ne.u32 p, %1, 0;\nsetp.eq.u32 q, %2, %3;\n"
               "ARR_LOOP:\n@p mbarrier.arrive.shared::cluster.b64 _, [%0];\n@q bra.uni ARR_LOOP;\n}"
               ::"r"(bar_cluster_addr), "r"((uint32_t)pred), "r"(zero), "n"(ID) : "memory");
}
__device__ __forceinline__ void block_fence(int id, uint32_t zero = blockIdx.y) {
  asm volatile("{\n.reg .pred q;\nsetp.eq.u32 q, %0, %1;\nBF_LOOP:\n@q st.volatile.shared.u32 [%0], %0;\n@q bra.uni BF_LOOP;\n}"
               ::"r"(zero), "r"(id) : "memory");
}
__device__ __forceinline__ bool mbar_test(uint32_t bar, uint32_t parity) {
  uint32_t ok;
  asm volatile("{\n.reg .pred p;\nmbarrier.test_wait.parity.shared::cta.b64 p, [%1], %2;\nselp.u32 %0, 1, 0, p;\n}"
               : "=r"(ok) : "r"(bar), "r"(parity) : "memory");
  return ok;
}
__device__ __forceinline__ void mbar_wait(uint32_t bar, uint32_t parity) {
  asm volatile("{\n.reg .pred p, q;\n.reg .u32 n;\nmov.u32 n, 0;\n"
               "WAIT_LOOP:\nmbarrier.try_wait.parity.shared::cta.b64 p, [%0], %1;\n"
               "add.u32 n, n, 1;\nsetp.lt.u32 q, n, 4194304;\nand.pred q, q, !p;\n@q bra WAIT_LOOP;\n}"
               ::"r"(bar), "r"(parity) : "memory");
}
__device__ __forceinline__ uint32_t mapa(uint32_t addr, uint32_t rank) {
  uint32_t r;
  asm volatile("mapa.shared::cluster.u32 %0, %1, %2;" : "=r"(r) : "r"(addr), "r"(rank));
  return r;
}
__device__ __forceinline__ void cluster_arrive() { asm volatile("barrier.cluster.arrive.relaxed.aligned;" ::: "memory"); }
__device__ __forceinline__ bool elect_one() {
  uint32_t p;
  asm volatile("{\n.reg .pred p;\nelect.sync _|p, 0xffffffff;\nselp.u32 %0, 1, 0, p;\n}" : "=r"(p));
  return p;
}
__device__ __forceinline__ int read_lane() { return threadIdx.x & 31; }
__device__ __forceinline__ void cluster_wait() { asm volatile("barrier.cluster.wait.acquire.aligned;" ::: "memory"); }
__device__ __forceinline__ void bar_sync(int id, int n) { asm volatile("barrier.cta.sync %0, %1;" ::"r"(id), "r"(n) : "memory"); }
__device__ __forceinline__ void bar_arrive(int id, int n) { asm volatile("barrier.cta.arrive %0, %1;" ::"r"(id), "r"(n) : "memory"); }

__device__ __forceinline__ uint64_t policy_evict_first() {
  uint64_t p;
  asm("createpolicy.fractional.L2::evict_first.b64 %0, 1.0;" : "=l"(p));
  return p;
}
__device__ __forceinline__ uint64_t policy_evict_normal() {
  uint64_t p;
  asm("createpolicy.fractional.L2::evict_normal.b64 %0, 1.0;" : "=l"(p));
  return p;
}
__device__ __forceinline__ void tma3d(uint32_t dst, const CUtensorMap* tm, int c1, int c2, uint32_t bar) {
  asm volatile("cp.async.bulk.tensor.3d.shared::cluster.global.mbarrier::complete_tx::bytes [%0], [%1, {%2, %3, %4}], [%5];"
               ::"r"(dst), "l"(tm), "r"(0), "r"(c1), "r"(c2), "r"(bar) : "memory");
}
__device__ __forceinline__ void tma2d(uint32_t dst, const CUtensorMap* tm, int c0, int c1, uint32_t bar) {
  asm volatile("cp.async.bulk.tensor.2d.shared::cluster.global.mbarrier::complete_tx::bytes [%0], [%1, {%2, %3}], [%4];"
               ::"r"(dst), "l"(tm), "r"(c0), "r"(c1), "r"(bar) : "memory");
}
__device__ __forceinline__ void tma2d_stream(uint32_t dst, const CUtensorMap* tm, int c0, int c1, uint32_t bar) {
  asm volatile("{\n.reg .b64 pol;\ncreatepolicy.fractional.L2::evict_first.b64 pol, 1.0;\n"
               "cp.async.bulk.tensor.2d.shared::cluster.global.mbarrier::complete_tx::bytes.L2::cache_hint [%0], [%1, {%2, %3}], [%4], pol;\n}"
               ::"r"(dst), "l"(tm), "r"(c0), "r"(c1), "r"(bar) : "memory");
}
__device__ __forceinline__ void tma2d_prefetch(const CUtensorMap* tm, int c0, int c1) {
  asm volatile("cp.async.bulk.prefetch.tensor.2d.L2.global [%0, {%1, %2}];" ::"l"(tm), "r"(c0), "r"(c1) : "memory");
}
__device__ __forceinline__ void prefetch_l2(const void* p, uint32_t bytes) {
  asm volatile("cp.async.bulk.prefetch.L2.global [%0], %1;" ::"l"(p), "r"(bytes) : "memory");
}
__device__ __forceinline__ void prefetch_tmap(const CUtensorMap* tm) {
  asm volatile("prefetch.tensormap [%0];" ::"l"(tm) : "memory");
}

__device__ __forceinline__ void wg_fence() { asm volatile("wgmma.fence.sync.aligned;" ::: "memory"); }
__device__ __forceinline__ void wg_commit() { asm volatile("wgmma.commit_group.sync.aligned;" ::: "memory"); }
template <int N> __device__ __forceinline__ void wg_wait() { asm volatile("wgmma.wait_group.sync.aligned %0;" ::"n"(N) : "memory"); }

__device__ __forceinline__ uint64_t mkdesc(uint32_t addr, uint32_t lbo_bytes) {
  return (uint64_t)(((addr & 0x3FFFF) >> 4) | ((lbo_bytes >> 4) << 16)) | ((uint64_t)0x40000040u << 32);
}
template <int N> __device__ __forceinline__ void pin(float (&a)[N]) {
#pragma unroll
  for (int i = 0; i < N; i++) asm volatile("" : "+f"(a[i])::"memory");
}
template <int N> __device__ __forceinline__ void pin(uint32_t (&a)[N]) {
#pragma unroll
  for (int i = 0; i < N; i++) asm volatile("" : "+r"(a[i])::"memory");
}

#define F8(d, o) "+f"(d[o]), "+f"(d[o + 1]), "+f"(d[o + 2]), "+f"(d[o + 3]), "+f"(d[o + 4]), "+f"(d[o + 5]), "+f"(d[o + 6]), "+f"(d[o + 7])
#define R32A "%0, %1, %2, %3, %4, %5, %6, %7, %8, %9, %10, %11, %12, %13, %14, %15, %16, %17, %18, %19, %20, %21, %22, %23, %24, %25, %26, %27, %28, %29, %30, %31"
#define R32B "%32, %33, %34, %35, %36, %37, %38, %39, %40, %41, %42, %43, %44, %45, %46, %47, %48, %49, %50, %51, %52, %53, %54, %55, %56, %57, %58, %59, %60, %61, %62, %63"

template <int TB>
__device__ __forceinline__ void mma_n128(float (&d)[64], uint32_t a0, uint32_t a1, uint32_t a2, uint32_t a3, uint64_t db, int acc) {
  asm volatile("{\n.reg .pred p;\nsetp.ne.b32 p, %69, 0;\n"
               "wgmma.mma_async.sync.aligned.m64n128k16.f32.bf16.bf16 {" R32A ", " R32B "}, {%64, %65, %66, %67}, %68, p, 1, 1, %70;\n}\n"
               : F8(d, 0), F8(d, 8), F8(d, 16), F8(d, 24), F8(d, 32), F8(d, 40), F8(d, 48), F8(d, 56)
               : "r"(a0), "r"(a1), "r"(a2), "r"(a3), "l"(db), "r"(acc), "n"(TB));
}
template <int TB>
__device__ __forceinline__ void mma_n128_ss(float (&d)[64], uint64_t da, uint64_t db, int acc) {
  asm volatile("{\n.reg .pred p;\nsetp.ne.b32 p, %66, 0;\n"
               "wgmma.mma_async.sync.aligned.m64n128k16.f32.bf16.bf16 {" R32A ", " R32B "}, %64, %65, p, 1, 1, 0, %67;\n}\n"
               : F8(d, 0), F8(d, 8), F8(d, 16), F8(d, 24), F8(d, 32), F8(d, 40), F8(d, 48), F8(d, 56)
               : "l"(da), "l"(db), "r"(acc), "n"(TB));
}
template <int TB>
__device__ __forceinline__ void mma_n64(float (&d)[32], uint32_t a0, uint32_t a1, uint32_t a2, uint32_t a3, uint64_t db, int acc) {
  asm volatile("{\n.reg .pred p;\nsetp.ne.b32 p, %37, 0;\n"
               "wgmma.mma_async.sync.aligned.m64n64k16.f32.bf16.bf16 {" R32A "}, {%32, %33, %34, %35}, %36, p, 1, 1, %38;\n}\n"
               : F8(d, 0), F8(d, 8), F8(d, 16), F8(d, 24)
               : "r"(a0), "r"(a1), "r"(a2), "r"(a3), "l"(db), "r"(acc), "n"(TB));
}
__device__ __forceinline__ void mma_n8(float (&d)[4], uint64_t da, uint64_t db, int acc) {
  asm volatile("{\n.reg .pred p;\nsetp.ne.b32 p, %6, 0;\n"
               "wgmma.mma_async.sync.aligned.m64n8k16.f32.bf16.bf16 {%0, %1, %2, %3}, %4, %5, p, 1, 1, 1, 0;\n}\n"
               : "+f"(d[0]), "+f"(d[1]), "+f"(d[2]), "+f"(d[3])
               : "l"(da), "l"(db), "r"(acc));
}
__device__ __forceinline__ void hmma_k16(float (&d)[4], uint32_t a0, uint32_t a1, uint32_t a2, uint32_t a3, uint32_t b0, uint32_t b1) {
  asm volatile("mma.sync.aligned.m16n8k16.row.col.f32.bf16.bf16.f32 {%0, %1, %2, %3}, {%4, %5, %6, %7}, {%8, %9}, {%0, %1, %2, %3};"
               : "+f"(d[0]), "+f"(d[1]), "+f"(d[2]), "+f"(d[3]) : "r"(a0), "r"(a1), "r"(a2), "r"(a3), "r"(b0), "r"(b1));
}

__device__ __forceinline__ uint32_t pack2(float lo, float hi) {
  uint32_t r;
  asm("cvt.rn.bf16x2.f32 %0, %1, %2;" : "=r"(r) : "f"(hi), "f"(lo));
  return r;
}
__device__ __forceinline__ float bf_lo(uint32_t w) { return __uint_as_float(w << 16); }
__device__ __forceinline__ float bf_hi(uint32_t w) { return __uint_as_float(w & 0xFFFF0000u); }
__device__ __forceinline__ float bfr(float x) { return __uint_as_float(pack2(0.f, x)); }
__device__ __forceinline__ uint32_t sub2(uint32_t a, uint32_t b) {
  uint32_t r;
  asm("sub.rn.bf16x2 %0, %1, %2;" : "=r"(r) : "r"(a), "r"(b));
  return r;
}
__device__ __forceinline__ uint32_t add2(uint32_t a, uint32_t b) {
  uint32_t r;
  asm("add.rn.bf16x2 %0, %1, %2;" : "=r"(r) : "r"(a), "r"(b));
  return r;
}
__device__ __forceinline__ uint32_t mul2(uint32_t a, uint32_t b) {
  uint32_t r;
  asm("mul.rn.bf16x2 %0, %1, %2;" : "=r"(r) : "r"(a), "r"(b));
  return r;
}
__device__ __forceinline__ uint32_t fma2(uint32_t a, uint32_t b, uint32_t c) {
  uint32_t r;
  asm("fma.rn.bf16x2 %0, %1, %2, %3;" : "=r"(r) : "r"(a), "r"(b), "r"(c));
  return r;
}
__device__ __forceinline__ float ex2(float x) {
  float r;
  asm("ex2.approx.ftz.f32 %0, %1;" : "=f"(r) : "f"(x));
  return r;
}
__device__ __forceinline__ float rcp(float x) {
  float r;
  asm("rcp.approx.ftz.f32 %0, %1;" : "=f"(r) : "f"(x));
  return r;
}
__device__ __forceinline__ float silu_f(float t) { return t * rcp(1.0f + ex2(-1.4426950408889634f * t)); }
__device__ __forceinline__ void lds128(uint32_t a, uint32_t& x, uint32_t& y, uint32_t& z, uint32_t& w) {
  asm volatile("ld.shared.v4.u32 {%0, %1, %2, %3}, [%4];" : "=r"(x), "=r"(y), "=r"(z), "=r"(w) : "r"(a) : "memory");
}
__device__ __forceinline__ void ldsm4(uint32_t a, uint32_t& x, uint32_t& y, uint32_t& z, uint32_t& w) {
  asm volatile("ldmatrix.sync.aligned.m8n8.x4.shared.b16 {%0, %1, %2, %3}, [%4];" : "=r"(x), "=r"(y), "=r"(z), "=r"(w) : "r"(a) : "memory");
}
constexpr uint32_t TAG_BIT = 0x10000;
__device__ __forceinline__ void st_gran(uint4* p, uint32_t x, uint32_t y, uint32_t z, uint32_t w) {
  asm volatile("st.relaxed.gpu.global.v4.b32 [%0], {%1, %2, %3, %4};" ::"l"(p), "r"(x), "r"(y), "r"(z), "r"(w) : "memory");
}
__device__ __forceinline__ void ld_gran(const uint4* p, uint32_t& x, uint32_t& y, uint32_t& z, uint32_t& w) {
  asm volatile("ld.relaxed.gpu.global.v4.b32 {%0, %1, %2, %3}, [%4];" : "=r"(x), "=r"(y), "=r"(z), "=r"(w) : "l"(p) : "memory");
}
__device__ __forceinline__ void ldsm4t(uint32_t a, uint32_t& x, uint32_t& y, uint32_t& z, uint32_t& w) {
  asm volatile("ldmatrix.sync.aligned.m8n8.x4.trans.shared.b16 {%0, %1, %2, %3}, [%4];" : "=r"(x), "=r"(y), "=r"(z), "=r"(w) : "r"(a) : "memory");
}
__device__ __forceinline__ void stsm4t(uint32_t a, uint32_t x, uint32_t y, uint32_t z, uint32_t w) {
  asm volatile("stmatrix.sync.aligned.m8n8.x4.trans.shared.b16 [%0], {%1, %2, %3, %4};" ::"r"(a), "r"(x), "r"(y), "r"(z), "r"(w) : "memory");
}
__device__ __forceinline__ void stsm4(uint32_t a, uint32_t x, uint32_t y, uint32_t z, uint32_t w) {
  asm volatile("stmatrix.sync.aligned.m8n8.x4.shared.b16 [%0], {%1, %2, %3, %4};" ::"r"(a), "r"(x), "r"(y), "r"(z), "r"(w) : "memory");
}
template <class T>
__device__ __forceinline__ T* at(const void* base, uint32_t off) {
  uint64_t r;
  asm("{\n.reg .u32 lo, hi;\nmov.b64 {lo, hi}, %1;\nadd.cc.u32 lo, lo, %2;\naddc.u32 hi, hi, 0;\nmov.b64 %0, {lo, hi};\n}"
      : "=l"(r) : "l"(base), "r"(off));
  return (T*)__cvta_global_to_generic(r);
}
__device__ __forceinline__ void add_granules(float (&red)[32], const uint32_t (&g)[16]) {
#pragma unroll
  for (int i = 0; i < 16; i++) { red[2 * i] += bf_lo(g[i]); red[2 * i + 1] += bf_hi((i & 3) ? g[i] : g[i] & ~TAG_BIT); }
}
__device__ __forceinline__ bool granules_ok(const uint32_t (&g)[16], uint32_t tag) {
  uint32_t u, v;
  asm("lop3.b32 %0, %1, %2, %3, 0x7E;" : "=r"(u) : "r"(g[0]), "r"(g[4]), "r"(tag));
  asm("lop3.b32 %0, %1, %2, %3, 0x7E;" : "=r"(v) : "r"(g[8]), "r"(g[12]), "r"(tag));
  return __all_sync(0xffffffffu, ((u | v) & TAG_BIT) == 0);
}
__device__ __forceinline__ unsigned ld_acquire(const unsigned* p) {
  unsigned v;
  asm volatile("ld.acquire.gpu.global.u32 %0, [%1];" : "=r"(v) : "l"(p) : "memory");
  return v;
}
__device__ __forceinline__ void red_release(unsigned* p) {
  asm volatile("red.release.gpu.global.add.u32 [%0], 1;" ::"l"(p) : "memory");
}
__device__ __forceinline__ void st_release(unsigned* p, unsigned v) {
  asm volatile("st.release.gpu.global.u32 [%0], %1;" ::"l"(p), "r"(v) : "memory");
}

template <int K0, int K1>
__device__ __forceinline__ void ln_fetch(uint32_t (&xa)[144], uint32_t boxes, uint32_t lo) {
#pragma unroll
  for (int k = K0; k < K1; k++) ldsm4(((boxes + lo) ^ ((k & 3) << 5)) + (k >> 2) * 8192, xa[4 * k], xa[4 * k + 1], xa[4 * k + 2], xa[4 * k + 3]);
}
template <int K0, int K1>
__device__ __forceinline__ void ln_sums(const uint32_t (&xa)[144], float (&sm)[4][4]) {
#pragma unroll
  for (int k = K0; k < K1; k++) hmma_k16(sm[k & 3], xa[4 * k], xa[4 * k + 1], xa[4 * k + 2], xa[4 * k + 3], 0x3F803F80u, 0x3F803F80u);
}
__device__ __forceinline__ uint32_t sq8(const uint32_t* a) {
  uint32_t t, u;
  asm("mul.rn.bf16x2 %0, %1, %1;" : "=r"(t) : "r"(a[0]));
  asm("mul.rn.bf16x2 %0, %1, %1;" : "=r"(u) : "r"(a[2]));
#pragma unroll
  for (int i = 4; i < 16; i += 4) {
    asm("fma.rn.bf16x2 %0, %1, %1, %0;" : "+r"(t) : "r"(a[i]));
    asm("fma.rn.bf16x2 %0, %1, %1, %0;" : "+r"(u) : "r"(a[i + 2]));
  }
  return add2(t, u);
}
__device__ __forceinline__ void ln_centre(uint32_t (&xa)[144], int j0, int j1, uint32_t mm0, uint32_t mm1, float& sq0, float& sq1) {
#pragma unroll
  for (int j = 0; j < 72; j += 8)
    if (j >= j0 && j < j1) {
#pragma unroll
      for (int k = j; k < j + 8; k++) {
        xa[2 * k] = sub2(xa[2 * k], mm0);
        xa[2 * k + 1] = sub2(xa[2 * k + 1], mm1);
      }
      const uint32_t t0 = sq8(xa + 2 * j), t1 = sq8(xa + 2 * j + 1);
      sq0 += bf_lo(t0) + bf_hi(t0);
      sq1 += bf_lo(t1) + bf_hi(t1);
    }
}
__device__ __forceinline__ float ln_rstd(float var) {
  float sd;
  asm("sqrt.approx.ftz.f32 %0, %1;" : "=f"(sd) : "f"(bfr(bfr(fmaxf(var, 0.0f)) + 1e-5f)));
  return rcp(bfr(sd));
}
__device__ __forceinline__ uint32_t silu2(uint32_t t) { return pack2(silu_f(bf_lo(t)), silu_f(bf_hi(t))); }
__device__ __forceinline__ float sum8(float v) {
#pragma unroll
  for (int d = 4; d; d >>= 1) v += __shfl_xor_sync(0xffffffffu, v, d);
  return v;
}
__device__ __forceinline__ void await_count(const unsigned* p, unsigned target, unsigned sleep_ns) {
#pragma unroll 1
  for (int n = 0; n < (1 << 18) && __any_sync(0xffffffffu, (int)(ld_acquire(p) - target) < 0); n++) __nanosleep(sleep_ns);
}
__device__ __forceinline__ void bulk_load(uint32_t dst, const void* src, uint32_t bytes, uint32_t bar) {
  asm volatile("cp.async.bulk.shared::cluster.global.mbarrier::complete_tx::bytes [%0], [%1], %2, [%3];"
               ::"r"(dst), "l"(src), "r"(bytes), "r"(bar) : "memory");
}
__device__ __forceinline__ void proxy_fence() { asm volatile("fence.proxy.async;" ::: "memory"); }

template <int V> struct IC { static constexpr int value = V; };

struct Ctx {
  uint32_t sb;
  uint8_t* sp;
  uint32_t rank;
  Scratch* gs;
};

__device__ __forceinline__ void dly(const Ctx&, int) {}
__device__ __forceinline__ void load_box(uint32_t dst, const CUtensorMap* tm, int c0, int c1, uint32_t bar, uint64_t pol) {
  asm volatile("{\n.reg .pred p;\nelect.sync _|p, 0xffffffff;\n"
               "@p cp.async.bulk.tensor.2d.shared::cluster.global.mbarrier::complete_tx::bytes.multicast::cluster.L2::cache_hint"
               " [%0], [%1, {%2, %3}], [%4], %5, %6;\n}"
               ::"r"(dst), "l"(tm), "r"(c0), "r"(c1), "r"(bar), "h"((uint16_t)3), "l"(pol) : "memory");
}
template <int BOXES>
__device__ __forceinline__ void load_stage(uint32_t dst, const CUtensorMap* tm, int c0, int c1, uint32_t bar, uint32_t bytes, uint64_t pol) {
  asm volatile("{\n.reg .pred p;\nelect.sync _|p, 0xffffffff;\n"
               "@p mbarrier.arrive.expect_tx.shared::cta.b64 _, [%4], %7;\n"
               "@p cp.async.bulk.tensor.2d.shared::cluster.global.mbarrier::complete_tx::bytes.multicast::cluster.L2::cache_hint"
               " [%0], [%1, {%2, %3}], [%4], %5, %6;\n}"
               ::"r"(dst), "l"(tm), "r"(c0), "r"(c1), "r"(bar), "h"((uint16_t)3), "l"(pol), "r"(bytes) : "memory");
  if (BOXES == 2) load_box(dst + 8192, tm, c0, c1 + 64, bar, pol);
}
__device__ __forceinline__ void attn_producer(const Ctx& cx, int qb, int hs, const CUtensorMap* tmX, const CUtensorMap* tmK,
                                              const CUtensorMap* tmV, const CUtensorMap* tmWq, const CUtensorMap* tmWo) {
  const uint32_t full = cx.sb + SM_FULL, empty = cx.sb + SM_EMPTY, ring = cx.sb + SM_RING + cx.rank * 16384;
  const uint64_t keep = policy_evict_normal(), last_use = policy_evict_first();
  auto acquire = [&](int st) {
    mbar_wait(empty + 8 * (st & 3), ((st >> 2) ^ ((st & 3) >> 1) ^ 1) & 1);
    if (st > 3) dly(cx, st);
  };
  if (elect_one()) {
#pragma unroll
    for (int j = 0; j < 3; j++) {
      mbar_expect_tx(cx.sb + SM_XFULL + 96 + 8 * j, 24576);
      tma3d(cx.sb + SM_X + 73728 + j * 24576, tmX, qb * 128 + 64, j * 3, cx.sb + SM_XFULL + 96 + 8 * j);
    }
  }
  __syncwarp();
  const int c0 = cx.rank * 64;
#pragma unroll 1
  for (int st = 0; st < NST_Q - 1; st++) {
    const bool half = st >= 10 && st < 13;
    const int i = st - (st < 5 ? 0 : st < 10 ? 5 : half ? 10 : 13), sl = st & 3;
    const int n0 = (hs * 4 + (st < 5 ? 0 : st < 10 ? 2 : half ? 3 : 1)) * DH + (half ? 0 : c0);
    const int k0 = half ? (i < 2 ? 256 * i + 2 * c0 : 448 + c0) : (i < 3 ? 128 * i : 128 * i - 64);
    if (st == 1) mbar_wait(cx.sb + SM_XFULL + 16, 0);
    acquire(st);
    load_stage<1>(ring + sl * STAGE, tmWq, n0, k0, full + 8 * sl, i == 2 ? 16384 : (half && i) ? 24576 : 32768, last_use);
    if (i != 2 && !(half && i && c0)) load_box(ring + sl * STAGE + 8192, tmWq, n0, k0 + 64, full + 8 * sl, last_use);
    if ((st == 3 || st == 4 || st == 8) && elect_one()) {
      if (st != 4) tma2d_prefetch(tmWq, (hs * 4 + 2 - (st >> 3)) * DH + (qb & 1) * 64, (qb >> 1) * 64);
      else if (qb < 9) tma2d_prefetch(tmWq, (hs * 4 + 3) * DH, qb * 64);
    }
    __syncwarp();
  }
  int vrow = 0;
  uint64_t vpol = keep;
#pragma unroll 1
  for (int j = 0; j < 32; j++) {
    const int st = NST_Q - 1 + 4 * j, row = (hs * 2 + (j >> 4)) * SEQ + (j & 7) * 256;
    const uint64_t pol = (j & 8) ? last_use : keep;
    if (j < 7 && qb < 8 && elect_one()) tma2d_prefetch((qb & 4) ? tmV : tmK, (qb & 1) * 64, row + 256 + (qb & 2) * 64);
    __syncwarp();
    if (j == 24) mbar_wait(cx.sb + SM_BAR_Q3, 0);
    acquire(st);
    load_stage<1>(ring + SL_KE * STAGE, tmK, c0, row, full + 8 * SL_KE, 32768, pol);
    acquire(st + 1);
    if (j) load_stage<1>(ring + SL_VE * STAGE, tmV, c0, vrow, full + 8 * SL_VE, 32768, vpol);
    else load_stage<2>(ring + SL_VE * STAGE, tmWq, (hs * 4 + 1) * DH + c0, 448, full + 8 * SL_VE, 32768, last_use);
    vrow = row + 128;
    vpol = pol;
    acquire(st + 2);
    load_stage<1>(ring + SL_KO * STAGE, tmK, c0, vrow, full + 8 * SL_KO, 32768, pol);
    acquire(st + 3);
    load_stage<1>(ring + SL_VO * STAGE, tmV, c0, row, full + 8 * SL_VO, 32768, pol);
  }
  acquire(NST_Q + NST_KV - 1);
  load_stage<1>(ring + SL_KE * STAGE, tmV, c0, vrow, full + 8 * SL_KE, 32768, last_use);
#pragma unroll 1
  for (int u = 0; u < NST_O; u++) {
    const int st = NST_Q + NST_KV + u, sl = st & 3;
    const int blk = u < 4 && cx.rank ? 8 : ((hs + max(u >> 1, 1)) & 7);
    const int head = u < 4 ? u ^ (u >> 1) : ((u & 1) * 2 + cx.rank + 3) & 3;
    acquire(st);
    load_stage<1>(ring + sl * STAGE, tmWo, blk * 64, hs * 512 + head * 128, full + 8 * sl, 32768, last_use);
  }
}

__device__ __forceinline__ uint32_t xn_offset(uint32_t row, int lane) {
  return (row >> 6) * (9 * 8192) + (row & 63) * 128 + ((((lane >> 2) ^ row) & 7) << 4) + (lane & 3) * 4;
}

__device__ __forceinline__ void attn_rows(const Ctx& cx, int qb, int hs, int hw, int lane, const CUtensorMap* tmX16,
                                          const __nv_bfloat16* w_r) {
  extern __shared__ __align__(1024) uint8_t smem_rows[];
  auto box = [&](int blk) { return blk < 8 ? SM_SLOT + 2 * STAGE + 8192 + (blk >> 2) * 16384 + (blk & 3) * 2048 : SM_BOX8; };
  const uint32_t sb = smem_u32(smem_rows);
  if (hw == 0) {
    bar_sync(BAR_HELPER, 160);
    if (elect_one()) {
      mbar_expect_tx(sb + SM_BAR_ROWS, 9 * 2048);
#pragma unroll 1
      for (int i = 0; i < 9; i++) tma2d(sb + box(i), tmX16, i * 64, qb * 128 + hs * 16, sb + SM_BAR_ROWS);
    }
    __syncwarp();
  }
  uint32_t g = (lane >> 3) * 128 + (((lane ^ (lane >> 3)) & 7) << 4);
  auto next = [&]() {
    g = ((g + 512) & 2047) ^ 64;
    asm volatile("" : "+r"(g));
  };
  float* const part = (float*)(smem_rows + SM_ROWS);
  mbar_wait(sb + SM_BAR_ROWS, 0);
  if (hw == 0) dly(cx, 190);
#pragma unroll 1
  for (int i = 0; i < 4; i++) {
    float a = 0.f, b = 0.f;
#pragma unroll
    for (int j = 0; j < 3; j++) {
      const uint4 v = *(const uint4*)(smem_rows + box(hw * 3 + j) + g);
      const uint32_t w[4] = {v.x, v.y, v.z, v.w};
#pragma unroll
      for (int k = 0; k < 4; k++) {
        a += bf_lo(w[k]) + bf_hi(w[k]);
        b = fmaf(bf_lo(w[k]), bf_lo(w[k]), fmaf(bf_hi(w[k]), bf_hi(w[k]), b));
      }
    }
    a = sum8(a);
    b = sum8(b);
    float* p = part + hw * 16 + (g >> 7);
    p[0] = a;
    p[48] = b;
    next();
  }
  bar_sync(BAR_ROWS, 96);
  if (hw == 0) dly(cx, 191);
  {
    const float* p = part + (lane & 15);
    const float mean = (p[0] + p[16] + p[32]) * (1.0f / DM), rstd = ln_rstd((p[48] + p[64] + p[80]) * (1.0f / DM) - mean * mean);
    const uint32_t mm = pack2(mean, mean), rr = pack2(rstd - bfr(rstd), rstd);
#pragma unroll 1
    for (int u = hw * 12; u < hw * 12 + 12; u++) {
      const int blk = u >> 2;
      uint4* q = (uint4*)(smem_rows + box(blk) + g);
      uint4 v = *q;
      const uint32_t m = __shfl_sync(0xffffffffu, mm, g >> 7), r = __shfl_sync(0xffffffffu, rr, g >> 7);
      const uint32_t hi = __byte_perm(r, 0, 0x3232), lo = __byte_perm(r, 0, 0x1010);
      auto norm = [&](uint32_t w) {
        const uint32_t xc = sub2(w, m);
        return fma2(xc, hi, mul2(xc, lo));
      };
      v = make_uint4(norm(v.x), norm(v.y), norm(v.z), norm(v.w));
      *q = v;
      *at<uint4>(cx.gs->xn + ((qb * 2 + (hs >> 2)) * 9 + blk) * 512 + (hs & 3) * 128, g) = v;
      next();
    }
  }
  bar_sync(BAR_ROWS, 96);
  if (hw == 0) {
    dly(cx, 192);
    if (lane == 0) red_release(&cx.gs->rows[qb * 32]);
    dly(cx, 193);
  }
#pragma unroll 1
  for (int u = hw ? 13 * hw - 3 : 0; u < 13 * hw + 10; u++) {
    const int blk = u >> 2;
    const uint32_t o = (g + (u & 3) * 512) ^ ((u & 1) << 6);
    const uint4 v = *(const uint4*)(smem_rows + box(blk) + o);
    *at<uint4>(cx.gs->gate + (blk < 8 ? (qb * 8 + blk) * 144 + hs * 16 : (qb * 8 + hs) * 144 + 128) * 8, o) =
        make_uint4(silu2(v.x), silu2(v.y), silu2(v.z), silu2(v.w));
  }
  if (hw) dly(cx, 194 + hw);
  if (X_DS) __nanosleep(X_DS);
#pragma unroll 1
  for (int blk = hw * 3; blk < hw * 3 + 3; blk++) {
    const uint4 c = __ldg(at<const uint4>(w_r, blk * 128 + ((g ^ (g >> 3)) & 0x70)));
#pragma unroll 1
    for (int i = 0; i < 4; i++) {
      const uint4 v = *(const uint4*)(smem_rows + box(blk) + g);
      part[blk * 16 + (g >> 7)] =
          sum8(fmaf(bf_lo(v.x), bf_lo(c.x), fmaf(bf_hi(v.x), bf_hi(c.x), fmaf(bf_lo(v.y), bf_lo(c.y), bf_hi(v.y) * bf_hi(c.y)))) +
               fmaf(bf_lo(v.z), bf_lo(c.z), fmaf(bf_hi(v.z), bf_hi(c.z), fmaf(bf_lo(v.w), bf_lo(c.w), bf_hi(v.w) * bf_hi(c.w)))));
      next();
      if (X_DR) __nanosleep(X_DR);
    }
  }
  bar_sync(BAR_ROWS, 96);
  if (hw == 0) {
    dly(cx, 194);
    float d = 0.f;
#pragma unroll
    for (int j = 0; j < 9; j++) d += part[j * 16 + (lane & 15)];
    const uint32_t row = qb * 128 + hs * 16 + (lane & 15), b = pack2(0.f, d);
    *at<uint32_t>(cx.gs->key, row * 4) = (b ^ ((int)b < 0 ? 0xFFFF0000u : 0x80000000u)) + 0xFFFF - row;
    __syncwarp();
    if (lane == 0) red_release(&cx.gs->rows[qb * 32 + 1]);
  }
}

constexpr uint32_t SM_XO = SM_SLOT, SM_GO = SM_SLOT + STAGE, SM_P8 = SM_SLOT + 2 * STAGE;
__device__ __forceinline__ void attn_helper(const Ctx& cx, int qb, int hs, int lane, const __nv_bfloat16* wo, const CUtensorMap* tmX16) {
  unsigned e = 0;
  if (lane == 0) {
    e = cx.gs->launch[blockIdx.x];
    cx.gs->launch[blockIdx.x] = e + 1;
  }
  e = __shfl_sync(0xffffffffu, e, 0);
  if (lane == 0) {
    *(uint32_t*)(cx.sp + SM_TAG) = (~e & 1) * TAG_BIT;
    mbar_arrive(cx.sb + SM_BAR_MISC);
  }
  bar_sync(BAR_HELPER, 64);
  await_count(&cx.gs->rows[qb * 32 + 1], 8 * (e + 1), 1000);
  await_count(&cx.gs->q3_flag[qb * 8 + hs], e + 1, 1000);
  proxy_fence();
  if (elect_one()) {
    mbar_expect_tx(cx.sb + SM_BAR_Q3, 16384);
#pragma unroll
    for (int i = 0; i < 2; i++) bulk_load(cx.sb + SM_SLOT + 2 * STAGE + i * 16384 + 8192, cx.gs->q3 + (qb * 16 + hs * 2 + i) * 512, 8192, cx.sb + SM_BAR_Q3);
  }
  __syncwarp();
  bar_sync(BAR_HELPER, 64);
  prefetch_l2(at<const void>(wo, (hs * 512 + qb * 32 + lane) * (DM * 2)), DM * 2);
  await_count(&cx.gs->ycnt, 4 * (e + 1), 500);
  const uint32_t mykey = __ldcg(at<const uint32_t>(cx.gs->top, (lane >> 1) * 4)), myrow = 0xFFFF - (mykey & 0xFFFF);
#pragma unroll 1
  for (uint32_t todo = __ballot_sync(0xffffffffu, lane < 16 && ((lane & 1) ? myrow >> 4 == qb * 8 + hs : myrow >> 7 == qb)); todo; todo &= todo - 1) {
    const int i = __ffs(todo) - 1, blk = (i & 1) ? 8 : hs;
    const uint32_t key = __shfl_sync(0xffffffffu, mykey, i), row = 0xFFFF - (key & 0xFFFF), o = xn_offset(row, lane);
    const uint32_t t = __ldcg(at<const uint32_t>(cx.gs->xn, o + blk * 8192));
    const float2* p = at<const float2>(cx.gs->ypart, ((i >> 1) * DM + blk * 64 + 2 * lane) * 4);
    const float2 y0 = __ldcg(p), y1 = __ldcg(p + TOPC * DM / 2), y2 = __ldcg(p + TOPC * DM), y3 = __ldcg(p + 3 * TOPC * DM / 2);
    const float rs = bfr(rcp(1.0f + ex2(-1.4426950408889634f * bf_hi(key ^ ((int)key < 0 ? 0x80000000u : 0xFFFF0000u)))));
    const uint32_t y = pack2((y0.x + y1.x) + (y2.x + y3.x), (y0.y + y1.y) + (y2.y + y3.y));
    const uint32_t u = pack2(bf_lo(y) * rs, bf_hi(y) * rs);
    *at<uint32_t>(cx.gs->gate, ((qb * 8 + hs) * 144 + ((i & 1) ? 128 + (row & 15) : row & 127)) * 128 + (o & 127)) = silu2(add2(t, u));
  }
  proxy_fence();
  bar_sync(BAR_OA, 352);
  if (elect_one()) {
    const uint32_t bar = cx.sb + SM_BAR_XG;
    mbar_expect_tx(bar, 2 * 144 * 128);
    bulk_load(cx.sb + SM_GO, cx.gs->gate + (qb * 8 + hs) * (144 * 8), 144 * 128, bar);
#pragma unroll 1
    for (int i = 0; i < 9; i++) tma2d_stream(cx.sb + SM_XO + i * 2048, tmX16, i < 8 ? hs * 64 : 512, qb * 128 + (i < 8 ? i : hs) * 16, bar);
  }
  __syncwarp();
  const uint4* src = cx.gs->part + (qb * 64 + 56 + hs) * 1024;
#pragma unroll 1
  for (int n = 0; n < (1 << 16); n++) {
    __nanosleep(n ? 400 : 700);
    uint32_t a, b, d, t;
    ld_gran(at<const uint4>(src, (lane & 7) * 2048 + 2032), a, b, d, t);
    if (__all_sync(0xffffffffu, ((a >> 16) ^ e) & 1)) break;
  }
  if (elect_one()) {
    mbar_expect_tx(cx.sb + SM_BAR_P8, 16384);
    bulk_load(cx.sb + SM_P8, src, 16384, cx.sb + SM_BAR_P8);
  }
  __syncwarp();
}
__device__ __forceinline__ void attn_finish8(const Ctx& cx, int qb, int hs, int hw, int lane, __nv_bfloat16* out) {
  const uint32_t tag = *(const uint32_t*)(cx.sp + SM_TAG);
  mbar_wait(cx.sb + SM_BAR_P8, 0);
  mbar_wait(cx.sb + SM_BAR_XG, 0);
#pragma unroll 1
  for (int g = 2 - hw; g < 4; g += 3) {
    float acc[8] = {0.f, 0.f, 0.f, 0.f, 0.f, 0.f, 0.f, 0.f};
    uint32_t a[4];
#pragma unroll 1
    for (uint32_t o = g * 512 + lane * 16; o < 16384; o += 2048) {
      lds128(cx.sb + SM_P8 + o, a[0], a[1], a[2], a[3]);
#pragma unroll 1
      for (int n = 0; n < (1 << 16) && __any_sync(0xffffffffu, (a[0] & TAG_BIT) != tag); n++)
        ld_gran(at<const uint4>(cx.gs->part, (qb * 64 + 56 + hs) * 16384 + o), a[0], a[1], a[2], a[3]);
      a[0] &= ~TAG_BIT;
#pragma unroll
      for (int j = 0; j < 4; j++) { acc[2 * j] += bf_lo(a[j]); acc[2 * j + 1] += bf_hi(a[j]); }
    }
    asm volatile("" : "+r"(lane));
    const uint32_t tile = cx.sb + SM_XO + (128 + (lane & 15)) * 128 + (((lane >> 4) ^ (lane & 7)) << 4);
    uint32_t b[4];
    ldsm4((tile ^ (g << 5)) + STAGE, a[0], a[1], a[2], a[3]);
    ldsm4(tile ^ (g << 5), b[0], b[1], b[2], b[3]);
    stsm4(tile ^ (g << 5), fma2(pack2(acc[0], acc[1]), a[0], b[0]), fma2(pack2(acc[2], acc[3]), a[1], b[1]),
          fma2(pack2(acc[4], acc[5]), a[2], b[2]), fma2(pack2(acc[6], acc[7]), a[3], b[3]));
  }
  bar_sync(BAR_ROWS, 96);
#pragma unroll 1
  for (int ch = threadIdx.x - 32; ch < 128; ch += 96)
    *at<uint4>(out, ((qb * 128 + hs * 16 + (ch >> 3)) * DM + 512 + (ch & 7) * 8) * 2) =
        *(const uint4*)(cx.sp + SM_XO + (128 + (ch >> 3)) * 128 + (((ch ^ (ch >> 3)) & 7) << 4));
}

constexpr float S_BIAS = X_SC, S_SCALE = (float)(1ull << (int)X_SC);
constexpr float SUM_HI = 7.2057594e16f, SUM_LO = 9.0949470e-13f;

__device__ __forceinline__ float offset_for(const float* o) {
  const float m = fmaxf(fmaxf(fmaxf(fabsf(o[0]), fabsf(o[9])), fmaxf(fabsf(o[16]), fabsf(o[25]))),
                        fmaxf(fmaxf(fabsf(o[32]), fabsf(o[41])), fmaxf(fabsf(o[48]), fabsf(o[57]))));
  return __uint_as_float(__float_as_uint(m) & 0x7F800000u) * (X_OK * S_SCALE);
}
template <int LO, int HI>
__device__ __forceinline__ void softmax_exp(float (&s)[64]) {
#pragma unroll
  for (int i = LO; i < HI; i++) s[i] = ex2(s[i]);
}
__device__ __forceinline__ void row_sums(const uint32_t (&pf)[32], float& l0, float& l1) {
  uint32_t t[16];
#pragma unroll
  for (int i = 0; i < 16; i++) t[i] = add2(pf[(i >> 1) * 4 + (i & 1)], pf[(i >> 1) * 4 + 2 + (i & 1)]);
#pragma unroll
  for (int i = 0; i < 8; i++) t[i] = add2(t[(i >> 1) * 4 + (i & 1)], t[(i >> 1) * 4 + 2 + (i & 1)]);
#pragma unroll
  for (int i = 0; i < 4; i++) t[i] = add2(t[(i >> 1) * 4 + (i & 1)], t[(i >> 1) * 4 + 2 + (i & 1)]);
  if (X_T4) {
    t[0] = add2(t[0], t[2]);
    t[1] = add2(t[1], t[3]);
    l0 = (l0 + bf_lo(t[0])) + bf_hi(t[0]);
    l1 = (l1 + bf_lo(t[1])) + bf_hi(t[1]);
  } else {
    l0 += (bf_lo(t[0]) + bf_lo(t[2])) + (bf_hi(t[0]) + bf_hi(t[2]));
    l1 += (bf_lo(t[1]) + bf_lo(t[3])) + (bf_hi(t[1]) + bf_hi(t[3]));
  }
}
__device__ __forceinline__ void softmax_redo(uint32_t (&pf)[32], const uint32_t (&q)[32], const __nv_bfloat16* kblk, int lane, float& n0,
                                             float& n1, float& l0, float& l1, float& sc0, float& sc1, float bias) {
  float x0 = -3.0e38f, x1 = -3.0e38f;
#pragma unroll 1
  for (int u = 0; u < 16; u++) {
    const uint32_t* kp = (const uint32_t*)(kblk + ((u & 7) * 16 + (lane >> 2)) * DH) + (lane & 3);
    float d[2][4] = {};
#pragma unroll
    for (int k = 0; k < 16; k++)
      hmma_k16(d[k & 1], q[2 * (k & 14)], q[2 * (k & 14) + 1], q[2 * (k & 14) + 2], q[2 * (k & 14) + 3],
               kp[(k & 1) * 4 * DH + (k >> 1) * 8], kp[(k & 1) * 4 * DH + (k >> 1) * 8 + 4]);
    if (u < 8) {
      x0 = fmaxf(fmaxf(x0, fmaxf(d[0][0], d[0][1])), fmaxf(d[1][0], d[1][1]));
      x1 = fmaxf(fmaxf(x1, fmaxf(d[0][2], d[0][3])), fmaxf(d[1][2], d[1][3]));
      if (u == 7) {
#pragma unroll
        for (int m = 1; m < 4; m <<= 1) {
          x0 = fmaxf(x0, __shfl_xor_sync(0xffffffffu, x0, m));
          x1 = fmaxf(x1, __shfl_xor_sync(0xffffffffu, x1, m));
        }
        x0 = fminf(bias - x0, n0);
        x1 = fminf(bias - x1, n1);
        sc0 = ex2(x0 - n0);
        sc1 = ex2(x1 - n1);
        n0 = x0;
        n1 = x1;
        l0 *= sc0;
        l1 *= sc1;
      }
    } else {
#pragma unroll
      for (int i = 0; i < 28; i++) pf[i] = pf[i + 4];
#pragma unroll
      for (int i = 0; i < 4; i++) {
        const float n = (i & 1) ? n1 : n0;
        pf[28 + i] = pack2(ex2(d[i >> 1][(i & 1) * 2] + n), ex2(d[i >> 1][(i & 1) * 2 + 1] + n));
        ((i & 1) ? l1 : l0) += bf_lo(pf[28 + i]) + bf_hi(pf[28 + i]);
      }
    }
  }
}

#define TH(i)
__device__ __forceinline__ void attn_consumer(const Ctx& cx, int qb, int hs, int wg, int cw, int lane, const __nv_bfloat16* x,
                                              const __nv_bfloat16* kc, __nv_bfloat16* out) {
  const uint32_t full = cx.sb + SM_FULL;
  const uint32_t ring = cx.sb + SM_RING;
  uint32_t lo = ((cw & 3) * 16 + (lane & 15)) * 128 + (((lane >> 4) ^ (lane & 7)) << 4);
  const uint32_t slot = cx.sb + SM_SLOT + wg * 16384;
  auto frag = [&](int sl, int k) { return ((slot + sl * STAGE + lo) ^ ((k & 3) << 5)) + (k >> 2) * 8192; };
  auto park = [&](const float (&a)[64], int sl, int k0, int k1, float f0, float f1, float g0 = -0.f, float g1 = -0.f) {
#pragma unroll
    for (int k = 0; k < 8; k++)
      if (k >= k0 && k < k1)
        stsm4(frag(sl, k), pack2(fmaf(a[8 * k], f0, g0), fmaf(a[8 * k + 1], f0, g0)), pack2(fmaf(a[8 * k + 2], f1, g1), fmaf(a[8 * k + 3], f1, g1)),
              pack2(fmaf(a[8 * k + 4], f0, g0), fmaf(a[8 * k + 5], f0, g0)), pack2(fmaf(a[8 * k + 6], f1, g1), fmaf(a[8 * k + 7], f1, g1)));
  };
  const bool signaller = lane == 0 && (cw & 3) < 2;
  int my_turn = 1 + wg, other_turn = 2 - wg;

  uint32_t pf[32], q[32], empty_c;
#pragma nv_diag_suppress 549
  float o[64], l0, l1, c0 = 0.f, c1 = 0.f;
  {
    uint32_t xa[144];
    float rstd0, rstd1;
    {
      const uint32_t xb = cx.sb + SM_X + wg * 73728, xf = cx.sb + SM_XFULL + wg * 96;
      float sm[4][4] = {};
      prof(wg, 0);
      empty_c = mapa(cx.sb + SM_EMPTY, cw & 1);
      mbar_wait(xf, 0);
      TH(0)
      ln_fetch<0, 12>(xa, xb, lo);
      mbar_wait(xf + 8, 0);
      TH(1)
      ln_fetch<12, 24>(xa, xb, lo);
      ln_sums<0, 12>(xa, sm);
      mbar_wait(xf + 16, 0);
      TH(2)
      ln_fetch<24, 36>(xa, xb, lo);
      ln_sums<12, 36>(xa, sm);
      block_fence(36);
      if (wg) bar_arrive(other_turn, 256);
      block_fence(35);
      TH(3)
      rstd0 = ((sm[0][0] + sm[1][0]) + (sm[2][0] + sm[3][0])) * (1.0f / DM);
      rstd1 = ((sm[0][2] + sm[1][2]) + (sm[2][2] + sm[3][2])) * (1.0f / DM);
    }
    const uint32_t mm0 = pack2(rstd0, rstd0), mm1 = pack2(rstd1, rstd1);
    rstd0 -= bf_lo(mm0);
    rstd1 -= bf_lo(mm1);
    rstd0 *= rstd0 * (-0.25f * DM);
    rstd1 *= rstd1 * (-0.25f * DM);
    auto ln_finish = [&]() {
      rstd0 += __shfl_xor_sync(0xffffffffu, rstd0, 1); rstd1 += __shfl_xor_sync(0xffffffffu, rstd1, 1);
      rstd0 += __shfl_xor_sync(0xffffffffu, rstd0, 2); rstd1 += __shfl_xor_sync(0xffffffffu, rstd1, 2);
      rstd0 = ln_rstd(rstd0 * (1.0f / DM)) * SM_SCALE_LOG2;
      rstd1 = ln_rstd(rstd1 * (1.0f / DM)) * SM_SCALE_LOG2;
    };
    ln_centre(xa, 0, X_C0, mm0, mm1, rstd0, rstd1);
    if (wg == 0) {
      bar_sync(4, 128);
      if (signaller) {
        asm volatile("mbarrier.arrive.shared::cluster.b64 _, [%0], 2;" ::"r"(empty_c + 16) : "memory");
        asm volatile("mbarrier.arrive.shared::cluster.b64 _, [%0], 2;" ::"r"(empty_c + 24) : "memory");
      }
      block_fence(37);
      pin(xa);
      ln_centre(xa, X_C0, X_C1, mm0, mm1, rstd0, rstd1);
    }
    pin(xa);

    extern __shared__ __align__(1024) uint8_t smem_q[];
    const uint32_t ring = smem_u32(smem_q) + SM_RING;
    auto release = [&](int st) { if (signaller) mbar_arrive_cluster(empty_c + 8 * (st & 3)); };
    auto q_stage = [&](float (&acc)[64], int st, int i, int last) {
      mbar_wait(full + 8 * (st & 3), (st >> 2) & 1);
      if (i != (wg ? last : 1)) bar_sync(my_turn, 256);
      wg_fence();
      const uint64_t db = mkdesc(ring + (st & 3) * STAGE, 16384);
#pragma unroll
      for (int k = 0; k < 8; k++) {
        const int kb = (i < 3 ? 8 * i : 8 * i - 4) + k;
        if (i != 2 || k < 4) mma_n128<1>(acc, xa[4 * kb], xa[4 * kb + 1], xa[4 * kb + 2], xa[4 * kb + 3], db + k * 128, kb > 0);
      }
      wg_commit();
      if (i != (wg ? last - 1 : 0)) bar_arrive(other_turn, 256);
    };
    auto q_release = [&](int st, int i, int last) {
      if (i == 1 || i == last) {
        wg_wait<1>();
        if (i == last || !wg) release(st - 1);
      }
      if (i != last - 1 && (i || wg)) {
        wg_wait<0>();
        release(st);
      }
    };
    {
      float (&acc)[64] = o;
#pragma unroll 1
      for (int p = 0; p < 2; p++) {
#pragma unroll
        for (int i = 0; i < 5; i++) {
          q_stage(acc, 5 * p + i, i, 4);
          if (p == 0 && i != 3) {
            if (i == 0 && wg) bar_arrive(BAR_HELPER, 160);
            if ((wg || i) && i < 3) ln_centre(xa, i == 0 ? X_C0 : i == 1 ? X_C1 : X_C2, i == 0 ? X_C1 : i == 1 ? X_C2 : 72, mm0, mm1, rstd0, rstd1);
            if (i == 4) ln_finish();
            pin(xa);
          }
          q_release(5 * p + i, i, 4);
        }
        pin(acc);
#pragma unroll
        for (int k = 0; k < 8; k += 2) {
          park(acc, p, k, k + 2, rstd0, rstd1);
          if (k < 6) block_fence(40 + k);
        }
      }
    }
    {
      float (&h)[32] = *(float (*)[32])&o[0];
#pragma unroll
      for (int i = 0; i < 3; i++) {
        const uint32_t sl = (10 + i) & 3;
        mbar_wait(full + 8 * sl, ((10 + i) >> 2) & 1);
        if (i != (wg ? 2 : 1)) bar_sync(my_turn, 256);
        wg_fence();
#pragma unroll
        for (int k = 0; k < 16 - 4 * i; k++) {
          const int kb = (i == 2 ? 28 : 16 * i) + k;
          const uint64_t db = mkdesc(ring + sl * STAGE, 16) + (i == 2 && k >= 4 ? k + 4 : k) * 128;
          mma_n64<1>(h, xa[4 * kb], xa[4 * kb + 1], xa[4 * kb + 2], xa[4 * kb + 3], db, kb > 0);
        }
        wg_commit();
        if (i != (wg ? 1 : 0)) bar_arrive(other_turn, 256);
        q_release(10 + i, i, 2);
      }
      pin(h);
      park(o, 2, 0, 2, rstd0, rstd1);
      block_fence(49);
      park(o, 2, 2, 4, rstd0, rstd1);
    }
#pragma unroll
    for (int i = 0; i < 4; i++) {
      q_stage(o, 13 + i, i, 3);
      q_release(13 + i, i, 3);
    }
    prof(wg, 6);
#pragma unroll
    for (int i = 0; i < 32; i++) pf[i] = xa[112 + i];
    l0 = 0.25f * rcp(rstd0);
    l1 = 0.25f * rcp(rstd1);
  }

  uint32_t oa[96];
  const uint32_t zero = __shfl_sync(0xffffffffu, blockIdx.y, lane);
  my_turn = __shfl_sync(0xffffffffu, my_turn, lane);
  other_turn = __shfl_sync(0xffffffffu, other_turn, lane);
  lo = __shfl_sync(0xffffffffu, lo, lane);
  {
    float s[64], n0 = 0.f, n1 = 0.f;
    float lp0, lp1;
    float i0 = 0.f, i1 = 0.f;
    float hi = 0.f;
    bool redo;
    auto turn = [&](int it, auto kc_) -> bool {
      constexpr int KIND = decltype(kc_)::value;
      constexpr uint32_t slk = KIND == 1 ? SL_KO : SL_KE, slv = KIND == 1 ? SL_VO : SL_VE, slkn = KIND == 1 ? SL_KE : SL_KO;
      constexpr int SPLIT = KIND == 3 ? X_SPLIT3 : X_SPLIT, PARK1 = X_PARK;
      const uint32_t par = ((it + NST_Q / 2) >> 1) & 1;
      const int hsl = max((it >> 4) - 1, 0);
      const bool second = KIND == 1 && (it & 15) == 1;
      const uint64_t dk = mkdesc(ring + slk * STAGE, 16), dv = mkdesc(ring + slv * STAGE, 16384);
      auto qk = [&](int k, int acc) {
        if (KIND == 3) mma_n128_ss<0>(s, mkdesc(slot + hsl * STAGE, 16) + (k >> 2) * 512 + (k & 3) * 2, dk + (k >> 2) * 1024 + (k & 3) * 2, acc);
        else mma_n128<0>(s, q[4 * k], q[4 * k + 1], q[4 * k + 2], q[4 * k + 3], dk + (k >> 2) * 1024 + (k & 3) * 2, acc);
      };
      auto pv = [&]() {
#pragma unroll
        for (int k = 0; k < 8; k++)
          mma_n128<1>(o, pf[4 * k], pf[4 * k + 1], pf[4 * k + 2], pf[4 * k + 3], dv + k * 128, k > 0 || !second);
        wg_commit();
      };
      if (KIND == 2 && (it & 15) == 2) {
        n0 += S_BIAS;
        n1 += S_BIAS;
        l0 *= S_SCALE;
        l1 *= S_SCALE;
        hi = SUM_HI * S_SCALE;
        asm volatile("" : "+f"(n0), "+f"(n1), "+f"(l0), "+f"(l1), "+f"(hi)::"memory");
      }
      auto rebias = [&](int k0, int k1) {
#pragma unroll
        for (int i = 0; i < 64; i++)
          if (i >= k0 && i < k1) o[i] = fmaf(o[i], S_SCALE, (i & 2) ? c1 : c0);
        pin(o);
      };
      lp0 = l0; lp1 = l1;
#define TS(i)
      {
        TS(0)
        if (KIND == 3) {
          asm volatile("fence.proxy.async.shared::cta;" ::: "memory");
          const float t0 = lp0 + __shfl_xor_sync(0xffffffffu, lp0, 1), t1 = lp1 + __shfl_xor_sync(0xffffffffu, lp1, 1);
          i0 = rcp(t0 + __shfl_xor_sync(0xffffffffu, t0, 2));
          i1 = rcp(t1 + __shfl_xor_sync(0xffffffffu, t1, 2));
          asm volatile("" : "+f"(i0), "+f"(i1)::"memory");
          block_fence(31, zero);
#pragma unroll
          for (int k = 0; k < X_N1; k++) ldsm4(frag(hsl, k), q[4 * k], q[4 * k + 1], q[4 * k + 2], q[4 * k + 3]);
        }
        if (KIND != 3) pin(q);
        pin(pf); pin(o);
        if (X_SB && KIND != 3 && !second) {
#pragma unroll
          for (int i = 0; i < 64; i++) s[i] = ((i & 2) ? n1 : n0) + (i + 1) * 1e-30f;
        }
        if (X_SB && KIND != 3) pin(s);
        if (X_OS && KIND == 1 && (it & 15) == 3) rebias(0, X_OS);
        bar_sync(my_turn, 256);
        wg_fence();
#pragma unroll
        for (int k = 0; k < 8; k++) qk(k, k > 0 || (X_SB && KIND != 3 && !second));
        wg_commit();
        TS(2)
        mbar_wait(full + 8 * slv, par);
        if (KIND == 2 && (it & 15) == 2) {
          c0 = offset_for(o);
          c1 = offset_for(o + 2);
          asm volatile("" : "+f"(c0), "+f"(c1)::"memory");
          wg_fence();
        }
        if (KIND == 1 && (it & 13) == 1) {
          if (second) {
            park(o, hsl, PARK1, 8, i0, i1, c0, c1);
          } else {
            rebias(X_OS, 64);
          }
          wg_fence();
        }
        if (KIND == 3) {
#pragma unroll
          for (int k = X_N1; k < 8; k++) ldsm4(frag(hsl, k), q[4 * k], q[4 * k + 1], q[4 * k + 2], q[4 * k + 3]);
          block_fence(32, zero);
        }
        TS(3)
        pv();
        bar_arrive(other_turn, 256);
        TS(4)
        wg_wait<1>();
      }
      pin(s);
      mbar_arrive_cluster_now<10 * KIND + 3>(empty_c + 8 * slk, signaller, zero);
      TS(5)
      if (KIND == 3) {
        n0 = n1 = l0 = l1 = 0.f;
        hi = SUM_HI;
        c0 *= -i0;
        c1 *= -i1;
      }
      softmax_exp<0, SPLIT>(s);
      pin(s);
      block_fence(10 * KIND + 4, zero);
      TS(6)
      wg_wait<0>();
      pin(o); pin(pf);
      mbar_arrive_cluster_now<10 * KIND + 5>(empty_c + 8 * slv, signaller, zero);
      TS(7)
      const bool kready = mbar_test(full + 8 * slkn, par);
      softmax_exp<SPLIT, 64>(s);
#pragma unroll
      for (int i = 0; i < 32; i++) pf[i] = pack2(s[2 * i], s[2 * i + 1]);
      row_sums(pf, l0, l1);
      if (KIND == 3) {
        park(o, hsl, 0, PARK1, i0, i1, c0, c1);
        if (it) prof(wg, 6 + (it >> 4));
        if (it >= 32 && cw == 0) bar_arrive(BAR_HELPER, 64);
      }
      redo = !(l0 + l1 <= hi) || (KIND == 3 && fminf(l0, l1) < SUM_LO);
      const bool leave = __any_sync(0xffffffffu, redo || !kready);
      return leave;
    };
    int it = -1;
#pragma unroll 1
    while (true) {
      mbar_wait(full + 8 * ((it & 1) ? SL_KE : SL_KO), ((it + NST_Q / 2) >> 1) & 1);
      it++;
#pragma unroll 1
      while (true) {
        if (it & 1) {
          if (turn(it, IC<1>()) || it == 63) break;
          it++;
        }
        if (it & 15) {
          if (turn(it, IC<2>())) break;
        } else {
          if (turn(it, IC<3>())) break;
        }
        it++;
      }
      if (__any_sync(0xffffffffu, redo)) {
        const int j = it & 15;
        float sc0 = 1.f, sc1 = 1.f;
        if (j == 0) n0 = n1 = 3.0e38f;
        l0 = j ? lp0 : 0.f;
        l1 = j ? lp1 : 0.f;
        softmax_redo(pf, q, kc + (size_t)((hs * 2 + (it >> 5)) * SEQ + j * 128) * DH, lane, n0, n1, l0, l1, sc0, sc1, j > 1 ? S_BIAS : 0.f);
        if (j == 0) {
          sc0 = sc1 = 1.f;
          hi = -1.f;
        }
        c0 *= sc0;
        c1 *= sc1;
#pragma unroll
        for (int i = 0; i < 16; i++) { o[4 * i] *= sc0; o[4 * i + 1] *= sc0; o[4 * i + 2] *= sc1; o[4 * i + 3] *= sc1; }
      }
      if (it == 63) break;
    }
  }

#define TE(i) {}
  {
    constexpr int ST0 = NST_Q + NST_KV;
    float acc[32], red[32], first[32];
    uint32_t tag;
    uint4* xch;
    auto await = [&](int st) { mbar_wait(full + 8 * (st & 3), (st >> 2) & 1); };
    auto release = [&](int st) { if (signaller) mbar_arrive_cluster(empty_c + 8 * (st & 3)); };
    auto unpark = [&](int h, int k0, int k1) {
#pragma unroll
      for (int k = 0; k < 8; k++)
        if (k >= k0 && k < k1) ldsm4(frag(h, k), oa[32 * h + 4 * k], oa[32 * h + 4 * k + 1], oa[32 * h + 4 * k + 2], oa[32 * h + 4 * k + 3]);
    };
    {
      float ar[64];
      asm volatile("fence.proxy.async.shared::cta;" ::: "memory");
      await(ST0 - 1);
      unpark(1, 0, 4);
      bar_sync(my_turn, 256);
      pin(pf); pin(o);
      wg_fence();
#pragma unroll
      for (int k = 0; k < 8; k++)
        mma_n128<1>(o, pf[4 * k], pf[4 * k + 1], pf[4 * k + 2], pf[4 * k + 3], mkdesc(ring + SL_KE * STAGE, 16384) + k * 128, 1);
      wg_commit();
      block_fence(66, zero);
      l0 += __shfl_xor_sync(0xffffffffu, l0, 1); l1 += __shfl_xor_sync(0xffffffffu, l1, 1);
      l0 += __shfl_xor_sync(0xffffffffu, l0, 2); l1 += __shfl_xor_sync(0xffffffffu, l1, 2);
      float f0 = rcp(l0), f1 = rcp(l1);
      asm volatile("" : "+f"(f0), "+f"(f1)::"memory");
      await(ST0);
      unpark(1, 4, 8);
      block_fence(61, zero);
#pragma unroll
      for (int k = 0; k < 8; k++) mma_n128_ss<1>(ar, mkdesc(slot, 16) + (k >> 2) * 512 + (k & 3) * 2, mkdesc(ring + (ST0 & 3) * STAGE, 16384) + k * 128, k > 0);
      wg_commit();
      bar_arrive(other_turn, 256);
      wg_wait<1>();
      pin(o); pin(pf);
      mbar_arrive_cluster_now<62>(empty_c + 8 * SL_KE, signaller, zero);
      c0 *= -f0;
      c1 *= -f1;
#pragma unroll
      for (int i = 0; i < 16; i++) {
        pf[2 * i] = pack2(fmaf(o[4 * i], f0, c0), fmaf(o[4 * i + 1], f0, c0));
        pf[2 * i + 1] = pack2(fmaf(o[4 * i + 2], f1, c1), fmaf(o[4 * i + 3], f1, c1));
      }
      pin(pf);
      prof(wg, 10);
#pragma unroll
      for (int u = 1; u < 4; u++) {
        await(ST0 + u);
        wg_wait<0>();
        release(ST0 + u - 1);
        bar_sync(my_turn, 256);
        wg_fence();
#pragma unroll
        for (int k = 0; k < 8; k++) {
          const uint32_t* a = (u == 1 ? oa + 32 : u == 2 ? pf : oa + 64) + 4 * k;
          mma_n128<1>(ar, a[0], a[1], a[2], a[3], mkdesc(ring + ((ST0 + u) & 3) * STAGE, 16384) + k * 128, 1);
        }
        wg_commit();
        bar_arrive(other_turn, 256);
        if (u < 3) {
          block_fence(62 + u, zero);
          unpark(u == 1 ? 2 : 0, 0, 8);
        }
      }
      mbar_wait(cx.sb + SM_BAR_MISC, 0);
      tag = *(const volatile uint32_t*)(cx.sp + SM_TAG);
      xch = at<uint4>(cx.gs->part, (qb << 20) + lane * 16 + zero);
      tag = __shfl_sync(0xffffffffu, tag, lane);
      await(ST0 + 4);
      wg_wait<0>();
      release(ST0 + 3);
      pin(ar);
#pragma unroll
      for (int i = 0; i < 32; i++) { first[i] = ar[i]; red[i] = ar[32 + i]; }
    }
    auto send = [&](const float (&v)[32], int dst, int idx) {
      uint4* p = at<uint4>(xch, (dst * 8 + idx) * 2048);
#pragma unroll
      for (int i = 0; i < 4; i++)
        st_gran(p + i * 32, (pack2(v[8 * i], v[8 * i + 1]) & ~TAG_BIT) | tag, pack2(v[8 * i + 2], v[8 * i + 3]),
                pack2(v[8 * i + 4], v[8 * i + 5]), pack2(v[8 * i + 6], v[8 * i + 7]));
    };
    send(first, ((hs + 1) & 7) * 7, cw);
    int nrx = 1;
    auto half_step = [&](int s, auto hc, bool arrive) {
      constexpr int h = decltype(hc)::value;
      const int st = ST0 + 2 * s + h;
      const uint64_t db = mkdesc(ring + (st & 3) * STAGE, 16);
      bar_sync(my_turn, 256);
      if (h == 0) pin(pf);
#pragma unroll
      for (int i = 32 * h; i < 32 + 64 * h; i++) asm volatile("" : "+r"(oa[i])::"memory");
      wg_fence();
#pragma unroll
      for (int k = 0; k < 16; k++) {
        const int kb = h * 16 + k - 8;
        if (kb >= 0) mma_n64<1>(acc, oa[4 * kb], oa[4 * kb + 1], oa[4 * kb + 2], oa[4 * kb + 3], db + k * 128, 1);
        else mma_n64<1>(acc, pf[4 * k], pf[4 * k + 1], pf[4 * k + 2], pf[4 * k + 3], db + k * 128, k > 0);
      }
      wg_commit();
      if (arrive) bar_arrive(other_turn, 256);
    };
    auto source = [&](int n) { return at<const uint4>(xch, ((hs * 7 + n - 1) * 8 + cw) * 2048); };
    auto fetch = [&](uint32_t (&g)[16], const uint4* p) {
#pragma unroll
      for (int i = 0; i < 4; i++) ld_gran(p + i * 32, g[4 * i], g[4 * i + 1], g[4 * i + 2], g[4 * i + 3]);
    };
    uint32_t g[16];
#pragma unroll 1
    for (int s = 2; s < 8; s++) {
      const int st = ST0 + 2 * s;
      half_step(s, IC<0>(), true);
      if (s == 2) {
        bar_arrive(BAR_OA, 352);
        send(red, 56 + cw, hs);
#pragma unroll
        for (int i = 0; i < 32; i++) red[i] = 0.f;
      }
      await(st + 1);
      if (s > 3 && granules_ok(g, tag)) { add_granules(red, g); nrx++; }
      wg_wait<0>();
      if (s < 7) release(st);
      if (s > 2) fetch(g, source(nrx));
      half_step(s, IC<1>(), true);
      await(st + 2);
      wg_wait<0>();
      if (s < 7) release(st + 1);
      pin(acc);
      if (s == 7) prof(wg, 19);
      send(acc, ((hs + s) & 7) * 7 + s - 1, cw);
    }
    TE(1)
    uint32_t xv[16], gt[16];
    {
      const int s = 8;
      uint32_t g2[16];
      half_step(s, IC<0>(), true);
      TE(2)
      await(NST_Q + NST_KV + NST_O - 1);
      cluster_arrive();
      mbar_wait(cx.sb + SM_BAR_XG, 0);
      const uint32_t tile = cx.sb + SM_XO + wg * 8192 + lo;
      if (granules_ok(g, tag)) { add_granules(red, g); nrx++; }
      fetch(g, source(nrx));
      block_fence(58, zero);
      wg_wait<0>();
      TE(3)
#pragma unroll
      for (int k = 0; k < 4; k++) ldsm4((tile ^ (k << 5)) + STAGE, gt[4 * k], gt[4 * k + 1], gt[4 * k + 2], gt[4 * k + 3]);
      half_step(s, IC<1>(), wg == 0);
      TE(4)
      block_fence(56, zero);
      const bool ok = granules_ok(g, tag);
      block_fence(57, zero + ok * 1000);
      const uint4* src = source(7);
      fetch(g2, src);
#pragma unroll
      for (int k = 0; k < 4; k++) ldsm4(tile ^ (k << 5), xv[4 * k], xv[4 * k + 1], xv[4 * k + 2], xv[4 * k + 3]);
      if (ok) { add_granules(red, g); nrx++; }
      TE(5)
      block_fence(59, zero);
      wg_wait<0>();
      pin(acc);
      TE(6)
#pragma unroll
      for (int i = 0; i < 32; i++) red[i] += acc[i];
      pin(red);
      TE(7)
      int n = 7;
#pragma unroll 1
      for (int spins = 0; spins < (1 << 16); spins++) {
        if (granules_ok(g2, tag)) {
          add_granules(red, g2);
          if (--n < nrx) {
            break;
          }
          src -= 1024;
        }
        fetch(g2, src);
      }
      TE(8)
    }
    prof(wg, 20);
    TE(9)
    const uint32_t ot = ring + ((ST0 + NST_O) & 3) * STAGE + cw * (16 * 144);
    uint32_t ow[16];
#pragma unroll
    for (int i = 0; i < 16; i++) ow[i] = fma2(pack2(red[2 * i], red[2 * i + 1]), gt[i], xv[i]);
#pragma unroll
    for (int i = 0; i < 4; i++)
      stsm4(ot + (lane & 15) * 144 + (2 * i + (lane >> 4)) * 16, ow[4 * i], ow[4 * i + 1], ow[4 * i + 2], ow[4 * i + 3]);
    __syncwarp();
#pragma unroll
    for (int i = 0; i < 4; i++) {
      uint4 v;
      lds128(ot + (i * 4 + (lane >> 3)) * 144 + (lane & 7) * 16, v.x, v.y, v.z, v.w);
      at<uint4>(out, ((qb * 128 + cw * 16 + (lane >> 3)) * DM + hs * 64 + (lane & 7) * 8) * 2)[i * (4 * DM / 8)] = v;
    }
    TE(10)
    prof(wg, 22);
  }
}

constexpr int AST_X = 6, AST_F = AST_X + 96;
__device__ __forceinline__ void aux_producer(const Ctx& cx, int f, const CUtensorMap* tmWq, const CUtensorMap* tmG) {
  const uint32_t full = cx.sb + SM_FULL, empty = cx.sb + SM_EMPTY;
  __nanosleep(3000);
  if (elect_one()) {
#pragma unroll 1
    for (int st = 0; st < AST_X; st++) {
      mbar_expect_tx(full + 8 * st, FSTAGE);
#pragma unroll
      for (int i = 0; i < 3; i++)
        tma2d_stream(cx.sb + st * FSTAGE + i * 8192, tmWq, (2 * f + (st & 1)) * 512 + 448, (st >> 1) * 192 + i * 64, full + 8 * st);
    }
  }
  __syncwarp();
  mbar_wait(cx.sb + SM_BAR_MISC, 0);
  proxy_fence();
  int st = AST_X;
#pragma unroll 1
  for (; st < AST_F; st++) {
    const uint32_t sl = st & 7;
    mbar_wait(empty + 8 * sl, ((st >> 3) & 1) ^ 1);
    if (elect_one()) {
      mbar_expect_tx(full + 8 * sl, FSTAGE);
      bulk_load(cx.sb + sl * FSTAGE, cx.gs->xn + (st - AST_X) * (FSTAGE / 16), FSTAGE, full + 8 * sl);
    }
    __syncwarp();
  }
#pragma unroll 1
  for (int pair = 0; pair < 14; pair++) {
#pragma unroll 1
    for (int u = 0; u < 12; u++, st++) {
      const uint32_t sl = st & 7;
      const int unit = pair * 2 + (u & 1), k = u >> 1;
      if (unit == 27) continue;
      const bool gu = pair < 9;
      mbar_wait(empty + 8 * sl, ((st >> 3) & 1) ^ 1);
      if (elect_one()) {
        mbar_expect_tx(full + 8 * sl, FSTAGE);
        tma2d_stream(cx.sb + sl * FSTAGE, tmG + (gu ? k >= 3 : 2), gu ? f * 1152 + unit * 64 : (unit - 18) * 64,
                     gu ? (k >= 3 ? k - 3 : k) * 192 : f * 1152 + k * 192, full + 8 * sl);
      }
      __syncwarp();
    }
  }
}

constexpr int BAR_FREE = 4, BAR_TILE = 6;
__device__ __forceinline__ void aux_helper(const Ctx& cx, int f, int warp, int lane) {
  unsigned epoch = 0;
  if (lane == 0) epoch = cx.gs->launch[blockIdx.x] + 1;
  epoch = __shfl_sync(0xffffffffu, epoch, 0);
  bar_sync(BAR_OA, 96);
  if (warp == 3) {
    if (lane == 0) cx.gs->launch[blockIdx.x] = epoch;
    await_count(at<const unsigned>(cx.gs->rows, (lane & 15) * 128), 8 * epoch, 200);
    if (lane == 0) mbar_arrive(cx.sb + SM_BAR_MISC);
    prof(0, 1, 31);
    await_count(at<const unsigned>(cx.gs->rows, (lane & 15) * 128 + 4), 8 * epoch, 500);
    uint32_t bound = 0xFFFFFFFFu, m0 = 0, m1 = 0;
#pragma unroll 1
    for (int k = 0; k < TOPC; k++) {
      if (__any_sync(0xffffffffu, m0 == 0)) {
        m0 = m1 = 0;
#pragma unroll 2
        for (int i = 0; i < 16; i++) {
          const uint4 v = __ldcg(at<const uint4>(cx.gs->key, lane * 16 + i * 512));
          const uint32_t w[4] = {v.x, v.y, v.z, v.w};
#pragma unroll
          for (int j = 0; j < 4; j++) {
            const uint32_t t = w[j] <= bound ? w[j] : 0;
            m1 = max(m1, min(m0, t));
            m0 = max(m0, t);
          }
        }
      }
      uint32_t m = m0;
      m = __reduce_max_sync(0xffffffffu, m);
      bound = m - 1;
      if (m0 == m) { m0 = m1; m1 = 0; }
      if (f == 0 && lane == 0) *at<uint32_t>(cx.gs->top, k * 4) = m;
#pragma unroll
      for (int j = 0; j < 3; j++) {
        const uint32_t row = 0xFFFF - (m & 0xFFFF), i = min(j * 4 + (lane >> 3), 8);
        *(uint4*)(cx.sp + SM_XSEL + i * 1024 + k * 128 + (((lane ^ k) & 7) << 4)) =
            __ldcg(at<const uint4>(cx.gs->xn, xn_offset(row, (lane & 7) * 4) + i * 8192));
      }
    }
    asm volatile("fence.proxy.async.shared::cta;" ::: "memory");
    prof(0, 2, 31);
  } else {
    const int wg = warp - 1;
#pragma unroll 1
    for (int u = 0; u < 32; u++) {
      bar_arrive(BAR_FREE + wg, 160);
      bar_sync(BAR_TILE + wg, 160);
      if (elect_one()) {
        const int n = (u >> 1) * 8 + 2 * f + wg;
        asm volatile("cp.async.bulk.global.shared::cta.bulk_group [%0], [%1], 8192;\ncp.async.bulk.commit_group;\ncp.async.bulk.wait_group 0;"
                     ::"l"(cx.gs->q3 + (n * 2 + (u & 1)) * 512), "r"(cx.sb + SM_H + wg * 8192) : "memory");
        if (u & 1) st_release(&cx.gs->q3_flag[n], epoch);
      }
      __syncwarp();
    }
  }
  bar_arrive(3, 352);
}

__device__ __forceinline__ void aux_consumer(const Ctx& cx, int f, int wg, int cw, int lane) {
  const int r = lane >> 2, c = lane & 3, tid = cw * 32 + lane;
  const uint32_t full = cx.sb + SM_FULL, empty = cx.sb + SM_EMPTY;
  const bool signaller = (tid & 127) == 0;
  auto await = [&](int st) { mbar_wait(full + 8 * (st & 7), (st >> 3) & 1); };
  auto release = [&](int st, int cnt) {
    asm volatile("{\n.reg .pred p;\nsetp.ne.u32 p, %2, 0;\n@p mbarrier.arrive.shared::cta.b64 _, [%0], %1;\n}"
                 ::"r"(empty + 8 * (st & 7)), "r"(cnt), "r"((uint32_t)signaller) : "memory");
  };
  prof(wg, 0);
  {
    const uint32_t lt = ((lane & 7) + (lane >> 4) * 8) * 128 + ((((cw & 3) * 2 + ((lane >> 3) & 1)) ^ (lane & 7)) << 4);
    uint32_t wa[144];
#pragma unroll
    for (int i = 0; i < 3; i++) {
      await(2 * i + wg);
#pragma unroll
      for (int k = 0; k < 12; k++) {
        const int kb = 12 * i + k;
        ldsm4t(cx.sb + (2 * i + wg) * FSTAGE + k * 2048 + lt, wa[4 * kb], wa[4 * kb + 1], wa[4 * kb + 2], wa[4 * kb + 3]);
      }
    }
    bar_sync(1, 256);
#pragma unroll
    for (int i = 0; i < 3; i++) release(2 * i + wg, 2);
    if (wg) bar_arrive(1, 256);
#pragma unroll 1
    for (int st = AST_X; st < AST_F; st += 3) {
      float acc[32];
      await(st);
      await(st + 1);
      await(st + 2);
      bar_sync(1 + wg, 256);
      wg_fence();
#pragma unroll
      for (int kb = 0; kb < 36; kb++) {
        const int i = kb / 12, k = kb % 12;
        mma_n64<0>(acc, wa[4 * kb], wa[4 * kb + 1], wa[4 * kb + 2], wa[4 * kb + 3],
                   mkdesc(cx.sb + ((st + i) & 7) * FSTAGE, 16) + (k >> 2) * 512 + (k & 3) * 2, kb > 0);
        if (k == 11) wg_commit();
      }
      if (st < AST_F - 3 || !wg) bar_arrive(2 - wg, 256);
      wg_wait<1>();
      release(st, 1);
      release(st + 1, 1);
      bar_sync(BAR_FREE + wg, 160);
      wg_wait<0>();
      pin(acc);
      release(st + 2, 1);
#pragma unroll
      for (int k = 0; k < 4; k++)
        stsm4t(cx.sb + SM_H + wg * 8192 + k * 2048 + lt, pack2(acc[8 * k] * SM_SCALE_LOG2, acc[8 * k + 1] * SM_SCALE_LOG2),
               pack2(acc[8 * k + 2] * SM_SCALE_LOG2, acc[8 * k + 3] * SM_SCALE_LOG2),
               pack2(acc[8 * k + 4] * SM_SCALE_LOG2, acc[8 * k + 5] * SM_SCALE_LOG2),
               pack2(acc[8 * k + 6] * SM_SCALE_LOG2, acc[8 * k + 7] * SM_SCALE_LOG2));
      asm volatile("fence.proxy.async.shared::cta;" ::: "memory");
      bar_arrive(BAR_TILE + wg, 160);
    }
    bar_sync(3, 352);
  }
  prof(wg, 3);
#pragma unroll 1
  for (int unit = wg; unit < 27; unit += 2) {
    if (unit >> 1 == 9) {
      asm volatile("fence.proxy.async.shared::cta;" ::: "memory");
      bar_sync(3, 256);
      prof(wg, 4);
    }
    const bool gu = unit < 18;
    float a0[4], a1[4];
#pragma unroll 1
    for (int m = 0; m < 2; m++) {
      float p0[4], p1[4];
      int st = AST_F + (unit >> 1) * 12 + m * 6 + wg;
      uint32_t b = cx.sb + (gu ? SM_XSEL : SM_H + m * 9216);
#pragma unroll 1
      for (int u = 0; u < 3; u++, st += 2, b += 3072) {
        await(st);
        wg_fence();
        const uint64_t da = mkdesc(cx.sb + (st & 7) * FSTAGE, 16), db = mkdesc(b, 16);
#pragma unroll
        for (int k = 0; k < 12; k++) mma_n8((k & 1) ? p1 : p0, da + k * 128, db + (k >> 2) * 64 + (k & 3) * 2, u > 0 || k > 1);
        wg_commit();
        wg_wait<0>();
        release(st, 2);
      }
      pin(p0); pin(p1);
#pragma unroll
      for (int i = 0; i < 4; i++) { a0[i] = a1[i]; a1[i] = p0[i] + p1[i]; }
    }
#pragma unroll
    for (int i = 0; i < 4; i++) {
      const int fl = (cw & 3) * 16 + r + (i >> 1) * 8, tok = 2 * c + (i & 1);
      if (gu) {
        const float h = bfr(silu_f(bfr(a0[i]))) * bfr(a1[i]);
        *(__nv_bfloat16*)(cx.sp + SM_H + unit * 1024 + tok * 128 + (((fl >> 3) ^ tok) << 4) + (fl & 7) * 2) = __float2bfloat16_rn(h);
      } else {
        *at<float>(cx.gs->ypart, ((f * TOPC + tok) * DM + (unit - 18) * 64 + fl) * 4) = a0[i] + a1[i];
      }
    }
  }
  prof(wg, 5);
  bar_sync(3, 256);
  if (tid == 0) red_release(&cx.gs->ycnt);
  prof(wg, 6);
}

struct Maps { CUtensorMap m[9]; };
__global__ void __cluster_dims__(2, 1, 1) __launch_bounds__(THREADS, 1)
fused_kernel(const __nv_bfloat16* __restrict__ x, const __nv_bfloat16* __restrict__ w_r, const __nv_bfloat16* __restrict__ kc,
             const __nv_bfloat16* __restrict__ wo, __nv_bfloat16* __restrict__ out, Scratch* gs,
             const __grid_constant__ Maps maps) {
  const CUtensorMap &tmX = maps.m[0], &tmWq = maps.m[1], &tmK = maps.m[2], &tmV = maps.m[3], &tmWo = maps.m[4];
  extern __shared__ __align__(1024) uint8_t smem_raw[];
  prof(0, 23, 511);
  if (threadIdx.x < 72 && blockIdx.x < N_ATT_CTA)
    asm volatile("prefetch.global.L2 [%0];" ::"l"(at<const void>(x, ((blockIdx.x >> 3) * 128 + (blockIdx.x & 7) * 8) * (DM * 2) + threadIdx.x * 128)));
  Ctx cx;
  cx.sb = smem_u32(smem_raw);
  cx.sp = smem_raw;
  cx.gs = gs;
  cx.rank = blockIdx.x & 1;
  const int warp = __shfl_sync(0xffffffffu, threadIdx.x >> 5, 0);
  const int cluster = blockIdx.x >> 1;
  const bool is_aux = blockIdx.x >= N_ATT_CTA;
  const int c7 = ((cluster - 36) * 37) >> 8;
  const int hs = cluster < 4 ? 4 + cluster : cluster < 36 ? (cluster - 4) >> 3 : 4 + c7;
  const int qb = (cluster < 4 ? 0 : cluster < 36 ? (cluster - 4) & 7 : cluster - 35 - 7 * c7) * 2 + cx.rank;

  extern __shared__ __align__(1024) uint8_t smem_alias[];
  const uint32_t xf = smem_u32(smem_alias) + SM_MISC + warp * 24;
  if (warp == 4 && elect_one()) prefetch_tmap(&tmX);
  if (elect_one()) {
    const uint32_t cnt = (warp > 4 && warp < 8) ? (is_aux ? 2 : 4) : 1;
#pragma unroll
    for (int i = 0; i < 3; i++) mbar_init(xf + 8 * i, cnt);
    asm volatile("fence.proxy.async.shared::cta;" ::: "memory");
    asm volatile("fence.mbarrier_init.release.cluster;" ::: "memory");
  }
  __syncwarp();
  cluster_arrive();
  if (warp == 4 && !is_aux) {
    if (elect_one()) {
#pragma unroll
      for (int i = 0; i < 3; i++) {
        mbar_expect_tx(xf + 8 * i, 24576);
        tma3d(xf - SM_XFULL + SM_X + i * 24576, &tmX, qb * 128, i * 3, xf + 8 * i);
      }
    }
  } else if (warp > 7 && elect_one()) {
    prefetch_tmap(&tmX + (is_aux ? warp - 4 : warp == 8 ? 8 : warp - 8));
  }
  __syncwarp();

  if (warp < 4) {
    asm volatile("setmaxnreg.dec.sync.aligned.u32 24;");
    cluster_wait();
    prof(0, 24, 511);
    if (warp == 0) {
      if (!is_aux) attn_producer(cx, qb, hs, &tmX, &tmK, &tmV, &tmWq, &tmWo);
      else aux_producer(cx, blockIdx.x - N_ATT_CTA, &tmWq, &maps.m[5]);
      prof(0, 25, 511);
    } else if (!is_aux) {
      attn_rows(cx, qb, hs, 3 - warp, read_lane(), &maps.m[8], w_r);
      if (warp == 1) attn_helper(cx, qb, hs, read_lane(), wo, &maps.m[8]);
      else bar_sync(BAR_OA, 352);
      attn_finish8(cx, qb, hs, warp - 1, read_lane(), out);
    } else {
      aux_helper(cx, blockIdx.x - N_ATT_CTA, warp, read_lane());
    }
    __syncwarp();
    cluster_arrive();
    cluster_wait();
    if (threadIdx.x == 32) { dly(cx, 201); dly(cx, 251); }
  } else {
    asm volatile("setmaxnreg.inc.sync.aligned.u32 240;");
    cluster_wait();
    const int cw = warp - 4, wg = cw >> 2;
    if (is_aux) aux_consumer(cx, blockIdx.x - N_ATT_CTA, wg, cw, read_lane());
    else attn_consumer(cx, qb, hs, wg, cw, read_lane(), x, kc, out);
  }
}

typedef CUresult (*EncodeFn)(CUtensorMap*, CUtensorMapDataType, cuuint32_t, void*, const cuuint64_t*, const cuuint64_t*,
                             const cuuint32_t*, const cuuint32_t*, CUtensorMapInterleave, CUtensorMapSwizzle,
                             CUtensorMapL2promotion, CUtensorMapFloatOOBfill);

void encode(EncodeFn fn, CUtensorMap* m, const void* p, int rank, const cuuint64_t* dims, const cuuint64_t* strides,
            const cuuint32_t* box) {
  const cuuint32_t es[5] = {1, 1, 1, 1, 1};
  fn(m, CU_TENSOR_MAP_DATA_TYPE_BFLOAT16, rank, const_cast<void*>(p), dims, strides, box, es, CU_TENSOR_MAP_INTERLEAVE_NONE,
     CU_TENSOR_MAP_SWIZZLE_128B, CU_TENSOR_MAP_L2_PROMOTION_L2_128B, CU_TENSOR_MAP_FLOAT_OOB_FILL_NONE);
}
void encode2d(EncodeFn fn, CUtensorMap* m, const void* p, uint64_t rows, uint64_t cols, uint32_t box_rows) {
  const cuuint64_t dims[2] = {cols, rows}, strides[1] = {cols * 2};
  const cuuint32_t box[2] = {64, box_rows};
  encode(fn, m, p, 2, dims, strides, box);
}

}

extern "C" void kernel_launch(void* const* d_in, const int* in_sizes, int n_in, void* d_out, int out_size) {
  (void)in_sizes; (void)n_in; (void)out_size;
  void* fnp = nullptr;
  cudaDriverEntryPointQueryResult qr;
  cudaGetDriverEntryPoint("cuTensorMapEncodeTiled", &fnp, cudaEnableDefault, &qr);
  EncodeFn fn = (EncodeFn)fnp;
  void* gs = nullptr;
  cudaGetSymbolAddress(&gs, g_scratch);
  Maps maps;
  CUtensorMap &tmX = maps.m[0], &tmWq = maps.m[1], &tmK = maps.m[2], &tmV = maps.m[3], &tmWo = maps.m[4], &tmG = maps.m[5],
              &tmU = maps.m[6], &tmD = maps.m[7];
  encode2d(fn, &tmK, d_in[1], 16 * SEQ, DH, 128);
  encode2d(fn, &tmV, d_in[2], 16 * SEQ, DH, 128);
  encode2d(fn, &tmWq, d_in[3], DM, 4096, 64);
  {
    const cuuint64_t dims[3] = {64, SEQ, 9}, strides[2] = {DM * 2, 128};
    const cuuint32_t box[3] = {64, 64, 3};
    encode(fn, &tmX, d_in[0], 3, dims, strides, box);
  }
  encode2d(fn, &maps.m[8], d_in[0], SEQ, DM, 16);
  encode2d(fn, &tmWo, d_in[4], 4096, DM, 128);
  encode2d(fn, &tmG, d_in[7], DM, FF, 192);
  encode2d(fn, &tmU, d_in[8], DM, FF, 192);
  encode2d(fn, &tmD, d_in[9], FF, DM, 192);
  cudaFuncSetAttribute(fused_kernel, cudaFuncAttributeMaxDynamicSharedMemorySize, SM_TOTAL);
  fused_kernel<<<N_CTA, THREADS, SM_TOTAL>>>((const __nv_bfloat16*)d_in[0], (const __nv_bfloat16*)d_in[6], (const __nv_bfloat16*)d_in[1],
                                            (const __nv_bfloat16*)d_in[4], (__nv_bfloat16*)d_out, (Scratch*)gs, maps);
}
```

```cpp
#include <cuda_runtime.h>
#include <cuda_bf16.h>
#include <cuda.h>
#include <stdint.h>

namespace {

constexpr int SEQ = 2048, DM = 576, DH = 128, FF = 4608, TOPC = 8;
constexpr int N_ATT_CTA = 128, N_CTA = 132;
constexpr int THREADS = 384;

constexpr uint32_t SM_RING = 0;
constexpr uint32_t STAGE = 32768;
constexpr uint32_t SM_SLOT = 131072;
constexpr uint32_t FSTAGE = 24576;
constexpr uint32_t SM_XSEL = 196608;
constexpr uint32_t SM_H = 205824;
constexpr uint32_t SM_MISC = 229376;
constexpr uint32_t SM_FULL = SM_MISC, SM_BAR_MISC = SM_MISC + 64, SM_BAR_XG = SM_MISC + 72, SM_BAR_P8 = SM_MISC + 80, SM_BAR_Q3 = SM_MISC + 88, SM_XFULL = SM_MISC + 96,
                   SM_EMPTY = SM_MISC + 120, SM_BAR_ROWS = SM_MISC + 216, SM_TAG = SM_MISC + 288,
                   SM_ROWS = SM_MISC + 304, SM_BOX8 = SM_MISC + 1024;
constexpr uint32_t SM_TOTAL = SM_MISC + 3072;
constexpr uint32_t SM_X = SM_MISC - 147456;

constexpr int BAR_ROWS = 6, BAR_HELPER = 7, BAR_OA = 8;
constexpr int NST_Q = 18, NST_KV = 128, NST_O = 18;
constexpr uint32_t SL_KE = (NST_Q - 1) & 3, SL_VE = NST_Q & 3, SL_KO = (NST_Q + 1) & 3, SL_VO = (NST_Q + 2) & 3;
#define X_N1 6
#define X_SPLIT 44
#define X_SPLIT3 36
#define X_PARK 5
#define X_C0 24
#define X_C1 32
#define X_C2 56
constexpr float SM_SCALE_LOG2 = 0.08838834764831845f * 1.4426950408889634f;

struct Scratch {
  uint4 part[16 * 64 * 2 * 4 * 128];
  uint4 gate[N_ATT_CTA * 144 * 8];
  uint4 q3[N_ATT_CTA * 1024];
  uint4 xn[SEQ * DM / 8];
  uint32_t key[SEQ];
  float ypart[4 * TOPC * DM];
  uint32_t top[32];
  unsigned launch[160];
  unsigned rows[16 * 32];
  unsigned q3_flag[N_ATT_CTA];
  unsigned ycnt;
};
__device__ __align__(1024) Scratch g_scratch;

__device__ __forceinline__ void prof(int, int, int = 0) {}

__device__ __forceinline__ uint32_t smem_u32(const void* p) { return (uint32_t)__cvta_generic_to_shared(p); }
__device__ __forceinline__ void mbar_init(uint32_t bar, uint32_t cnt) {
  asm volatile("mbarrier.init.shared::cta.b64 [%0], %1;" ::"r"(bar), "r"(cnt) : "memory");
}
__device__ __forceinline__ void mbar_expect_tx(uint32_t bar, uint32_t bytes) {
  asm volatile("mbarrier.arrive.expect_tx.shared::cta.b64 _, [%0], %1;" ::"r"(bar), "r"(bytes) : "memory");
}
__device__ __forceinline__ void mbar_arrive(uint32_t bar) {
  asm volatile("mbarrier.arrive.shared::cta.b64 _, [%0];" ::"r"(bar) : "memory");
}
__device__ __forceinline__ void mbar_arrive_cluster(uint32_t bar_cluster_addr) {
  asm volatile("mbarrier.arrive.shared::cluster.b64 _, [%0];" ::"r"(bar_cluster_addr) : "memory");
}
template <int ID>
__device__ __forceinline__ void mbar_arrive_cluster_now(uint32_t bar_cluster_addr, bool pred, uint32_t zero) {
  asm volatile("{\n.reg .pred p, q;\nsetp.ne.u32 p, %1, 0;\nsetp.eq.u32 q, %2, %3;\n"
               "ARR_LOOP:\n@p mbarrier.arrive.shared::cluster.b64 _, [%0];\n@q bra.uni ARR_LOOP;\n}"
               ::"r"(bar_cluster_addr), "r"((uint32_t)pred), "r"(zero), "n"(ID) : "memory");
}
__device__ __forceinline__ void block_fence(int id, uint32_t zero = blockIdx.y) {
  asm volatile("{\n.reg .pred q;\nsetp.eq.u32 q, %0, %1;\nBF_LOOP:\n@q st.volatile.shared.u32 [%0], %0;\n@q bra.uni BF_LOOP;\n}"
               ::"r"(zero), "r"(id) : "memory");
}
__device__ __forceinline__ bool mbar_test(uint32_t bar, uint32_t parity) {
  uint32_t ok;
  asm volatile("{\n.reg .pred p;\nmbarrier.test_wait.parity.shared::cta.b64 p, [%1], %2;\nselp.u32 %0, 1, 0, p;\n}"
               : "=r"(ok) : "r"(bar), "r"(parity) : "memory");
  return ok;
}
__device__ __forceinline__ void mbar_wait(uint32_t bar, uint32_t parity) {
  asm volatile("{\n.reg .pred p, q;\n.reg .u32 n;\nmov.u32 n, 0;\n"
               "WAIT_LOOP:\nmbarrier.try_wait.parity.shared::cta.b64 p, [%0], %1;\n"
               "add.u32 n, n, 1;\nsetp.lt.u32 q, n, 4194304;\nand.pred q, q, !p;\n@q bra WAIT_LOOP;\n}"
               ::"r"(bar), "r"(parity) : "memory");
}
__device__ __forceinline__ uint32_t mapa(uint32_t addr, uint32_t rank) {
  uint32_t r;
  asm volatile("mapa.shared::cluster.u32 %0, %1, %2;" : "=r"(r) : "r"(addr), "r"(rank));
  return r;
}
__device__ __forceinline__ void cluster_arrive() { asm volatile("barrier.cluster.arrive.relaxed.aligned;" ::: "memory"); }
__device__ __forceinline__ bool elect_one() {
  uint32_t p;
  asm volatile("{\n.reg .pred p;\nelect.sync _|p, 0xffffffff;\nselp.u32 %0, 1, 0, p;\n}" : "=r"(p));
  return p;
}
__device__ __forceinline__ int read_lane() { return threadIdx.x & 31; }
__device__ __forceinline__ void cluster_wait() { asm volatile("barrier.cluster.wait.acquire.aligned;" ::: "memory"); }
__device__ __forceinline__ void bar_sync(int id, int n) { asm volatile("barrier.cta.sync %0, %1;" ::"r"(id), "r"(n) : "memory"); }
__device__ __forceinline__ void bar_arrive(int id, int n) { asm volatile("barrier.cta.arrive %0, %1;" ::"r"(id), "r"(n) : "memory"); }

__device__ __forceinline__ uint64_t policy_evict_first() {
  uint64_t p;
  asm("createpolicy.fractional.L2::evict_first.b64 %0, 1.0;" : "=l"(p));
  return p;
}
__device__ __forceinline__ uint64_t policy_evict_normal() {
  uint64_t p;
  asm("createpolicy.fractional.L2::evict_normal.b64 %0, 1.0;" : "=l"(p));
  return p;
}
__device__ __forceinline__ void tma3d(uint32_t dst, const CUtensorMap* tm, int c1, int c2, uint32_t bar) {
  asm volatile("cp.async.bulk.tensor.3d.shared::cluster.global.mbarrier::complete_tx::bytes [%0], [%1, {%2, %3, %4}], [%5];"
               ::"r"(dst), "l"(tm), "r"(0), "r"(c1), "r"(c2), "r"(bar) : "memory");
}
__device__ __forceinline__ void tma2d(uint32_t dst, const CUtensorMap* tm, int c0, int c1, uint32_t bar) {
  asm volatile("cp.async.bulk.tensor.2d.shared::cluster.global.mbarrier::complete_tx::bytes [%0], [%1, {%2, %3}], [%4];"
               ::"r"(dst), "l"(tm), "r"(c0), "r"(c1), "r"(bar) : "memory");
}
__device__ __forceinline__ void tma2d_stream(uint32_t dst, const CUtensorMap* tm, int c0, int c1, uint32_t bar) {
  asm volatile("{\n.reg .b64 pol;\ncreatepolicy.fractional.L2::evict_first.b64 pol, 1.0;\n"
               "cp.async.bulk.tensor.2d.shared::cluster.global.mbarrier::complete_tx::bytes.L2::cache_hint [%0], [%1, {%2, %3}], [%4], pol;\n}"
               ::"r"(dst), "l"(tm), "r"(c0), "r"(c1), "r"(bar) : "memory");
}
__device__ __forceinline__ void tma2d_prefetch(const CUtensorMap* tm, int c0, int c1) {
  asm volatile("cp.async.bulk.prefetch.tensor.2d.L2.global [%0, {%1, %2}];" ::"l"(tm), "r"(c0), "r"(c1) : "memory");
}
__device__ __forceinline__ void prefetch_l2(const void* p, uint32_t bytes) {
  asm volatile("cp.async.bulk.prefetch.L2.global [%0], %1;" ::"l"(p), "r"(bytes) : "memory");
}
__device__ __forceinline__ void prefetch_tmap(const CUtensorMap* tm) {
  asm volatile("prefetch.tensormap [%0];" ::"l"(tm) : "memory");
}

__device__ __forceinline__ void wg_fence() { asm volatile("wgmma.fence.sync.aligned;" ::: "memory"); }
__device__ __forceinline__ void wg_commit() { asm volatile("wgmma.commit_group.sync.aligned;" ::: "memory"); }
template <int N> __device__ __forceinline__ void wg_wait() { asm volatile("wgmma.wait_group.sync.aligned %0;" ::"n"(N) : "memory"); }

__device__ __forceinline__ uint64_t mkdesc(uint32_t addr, uint32_t lbo_bytes) {
  return (uint64_t)(((addr & 0x3FFFF) >> 4) | ((lbo_bytes >> 4) << 16)) | ((uint64_t)0x40000040u << 32);
}
template <int N> __device__ __forceinline__ void pin(float (&a)[N]) {
#pragma unroll
  for (int i = 0; i < N; i++) asm volatile("" : "+f"(a[i])::"memory");
}
template <int N> __device__ __forceinline__ void pin(uint32_t (&a)[N]) {
#pragma unroll
  for (int i = 0; i < N; i++) asm volatile("" : "+r"(a[i])::"memory");
}

#define F8(d, o) "+f"(d[o]), "+f"(d[o + 1]), "+f"(d[o + 2]), "+f"(d[o + 3]), "+f"(d[o + 4]), "+f"(d[o + 5]), "+f"(d[o + 6]), "+f"(d[o + 7])
#define R32A "%0, %1, %2, %3, %4, %5, %6, %7, %8, %9, %10, %11, %12, %13, %14, %15, %16, %17, %18, %19, %20, %21, %22, %23, %24, %25, %26, %27, %28, %29, %30, %31"
#define R32B "%32, %33, %34, %35, %36, %37, %38, %39, %40, %41, %42, %43, %44, %45, %46, %47, %48, %49, %50, %51, %52, %53, %54, %55, %56, %57, %58, %59, %60, %61, %62, %63"

template <int TB>
__device__ __forceinline__ void mma_n128(float (&d)[64], uint32_t a0, uint32_t a1, uint32_t a2, uint32_t a3, uint64_t db, int acc) {
  asm volatile("{\n.reg .pred p;\nsetp.ne.b32 p, %69, 0;\n"
               "wgmma.mma_async.sync.aligned.m64n128k16.f32.bf16.bf16 {" R32A ", " R32B "}, {%64, %65, %66, %67}, %68, p, 1, 1, %70;\n}\n"
               : F8(d, 0), F8(d, 8), F8(d, 16), F8(d, 24), F8(d, 32), F8(d, 40), F8(d, 48), F8(d, 56)
               : "r"(a0), "r"(a1), "r"(a2), "r"(a3), "l"(db), "r"(acc), "n"(TB));
}
template <int TB>
__device__ __forceinline__ void mma_n128_ss(float (&d)[64], uint64_t da, uint64_t db, int acc) {
  asm volatile("{\n.reg .pred p;\nsetp.ne.b32 p, %66, 0;\n"
               "wgmma.mma_async.sync.aligned.m64n128k16.f32.bf16.bf16 {" R32A ", " R32B "}, %64, %65, p, 1, 1, 0, %67;\n}\n"
               : F8(d, 0), F8(d, 8), F8(d, 16), F8(d, 24), F8(d, 32), F8(d, 40), F8(d, 48), F8(d, 56)
               : "l"(da), "l"(db), "r"(acc), "n"(TB));
}
template <int TB>
__device__ __forceinline__ void mma_n64(float (&d)[32], uint32_t a0, uint32_t a1, uint32_t a2, uint32_t a3, uint64_t db, int acc) {
  asm volatile("{\n.reg .pred p;\nsetp.ne.b32 p, %37, 0;\n"
               "wgmma.mma_async.sync.aligned.m64n64k16.f32.bf16.bf16 {" R32A "}, {%32, %33, %34, %35}, %36, p, 1, 1, %38;\n}\n"
               : F8(d, 0), F8(d, 8), F8(d, 16), F8(d, 24)
               : "r"(a0), "r"(a1), "r"(a2), "r"(a3), "l"(db), "r"(acc), "n"(TB));
}
__device__ __forceinline__ void mma_n8(float (&d)[4], uint64_t da, uint64_t db, int acc) {
  asm volatile("{\n.reg .pred p;\nsetp.ne.b32 p, %6, 0;\n"
               "wgmma.mma_async.sync.aligned.m64n8k16.f32.bf16.bf16 {%0, %1, %2, %3}, %4, %5, p, 1, 1, 1, 0;\n}\n"
               : "+f"(d[0]), "+f"(d[1]), "+f"(d[2]), "+f"(d[3])
               : "l"(da), "l"(db), "r"(acc));
}
__device__ __forceinline__ void hmma_k16(float (&d)[4], uint32_t a0, uint32_t a1, uint32_t a2, uint32_t a3, uint32_t b0, uint32_t b1) {
  asm volatile("mma.sync.aligned.m16n8k16.row.col.f32.bf16.bf16.f32 {%0, %1, %2, %3}, {%4, %5, %6, %7}, {%8, %9}, {%0, %1, %2, %3};"
               : "+f"(d[0]), "+f"(d[1]), "+f"(d[2]), "+f"(d[3]) : "r"(a0), "r"(a1), "r"(a2), "r"(a3), "r"(b0), "r"(b1));
}

__device__ __forceinline__ uint32_t pack2(float lo, float hi) {
  uint32_t r;
  asm("cvt.rn.bf16x2.f32 %0, %1, %2;" : "=r"(r) : "f"(hi), "f"(lo));
  return r;
}
__device__ __forceinline__ float bf_lo(uint32_t w) { return __uint_as_float(w << 16); }
__device__ __forceinline__ float bf_hi(uint32_t w) { return __uint_as_float(w & 0xFFFF0000u); }
__device__ __forceinline__ float bfr(float x) { return __uint_as_float(pack2(0.f, x)); }
__device__ __forceinline__ uint32_t sub2(uint32_t a, uint32_t b) {
  uint32_t r;
  asm("sub.rn.bf16x2 %0, %1, %2;" : "=r"(r) : "r"(a), "r"(b));
  return r;
}
__device__ __forceinline__ uint32_t add2(uint32_t a, uint32_t b) {
  uint32_t r;
  asm("add.rn.bf16x2 %0, %1, %2;" : "=r"(r) : "r"(a), "r"(b));
  return r;
}
__device__ __forceinline__ uint32_t mul2(uint32_t a, uint32_t b) {
  uint32_t r;
  asm("mul.rn.bf16x2 %0, %1, %2;" : "=r"(r) : "r"(a), "r"(b));
  return r;
}
__device__ __forceinline__ uint32_t fma2(uint32_t a, uint32_t b, uint32_t c) {
  uint32_t r;
  asm("fma.rn.bf16x2 %0, %1, %2, %3;" : "=r"(r) : "r"(a), "r"(b), "r"(c));
  return r;
}
__device__ __forceinline__ float ex2(float x) {
  float r;
  asm("ex2.approx.ftz.f32 %0, %1;" : "=f"(r) : "f"(x));
  return r;
}
__device__ __forceinline__ float rcp(float x) {
  float r;
  asm("rcp.approx.ftz.f32 %0, %1;" : "=f"(r) : "f"(x));
  return r;
}
__device__ __forceinline__ float silu_f(float t) { return t * rcp(1.0f + ex2(-1.4426950408889634f * t)); }
__device__ __forceinline__ void lds128(uint32_t a, uint32_t& x, uint32_t& y, uint32_t& z, uint32_t& w) {
  asm volatile("ld.shared.v4.u32 {%0, %1, %2, %3}, [%4];" : "=r"(x), "=r"(y), "=r"(z), "=r"(w) : "r"(a) : "memory");
}
__device__ __forceinline__ void ldsm4(uint32_t a, uint32_t& x, uint32_t& y, uint32_t& z, uint32_t& w) {
  asm volatile("ldmatrix.sync.aligned.m8n8.x4.shared.b16 {%0, %1, %2, %3}, [%4];" : "=r"(x), "=r"(y), "=r"(z), "=r"(w) : "r"(a) : "memory");
}
constexpr uint32_t TAG_BIT = 0x10000;
__device__ __forceinline__ void st_gran(uint4* p, uint32_t x, uint32_t y, uint32_t z, uint32_t w) {
  asm volatile("st.relaxed.gpu.global.v4.b32 [%0], {%1, %2, %3, %4};" ::"l"(p), "r"(x), "r"(y), "r"(z), "r"(w) : "memory");
}
__device__ __forceinline__ void ld_gran(const uint4* p, uint32_t& x, uint32_t& y, uint32_t& z, uint32_t& w) {
  asm volatile("ld.relaxed.gpu.global.v4.b32 {%0, %1, %2, %3}, [%4];" : "=r"(x), "=r"(y), "=r"(z), "=r"(w) : "l"(p) : "memory");
}
__device__ __forceinline__ void ldsm4t(uint32_t a, uint32_t& x, uint32_t& y, uint32_t& z, uint32_t& w) {
  asm volatile("ldmatrix.sync.aligned.m8n8.x4.trans.shared.b16 {%0, %1, %2, %3}, [%4];" : "=r"(x), "=r"(y), "=r"(z), "=r"(w) : "r"(a) : "memory");
}
__device__ __forceinline__ void stsm4t(uint32_t a, uint32_t x, uint32_t y, uint32_t z, uint32_t w) {
  asm volatile("stmatrix.sync.aligned.m8n8.x4.trans.shared.b16 [%0], {%1, %2, %3, %4};" ::"r"(a), "r"(x), "r"(y), "r"(z), "r"(w) : "memory");
}
__device__ __forceinline__ void stsm4(uint32_t a, uint32_t x, uint32_t y, uint32_t z, uint32_t w) {
  asm volatile("stmatrix.sync.aligned.m8n8.x4.shared.b16 [%0], {%1, %2, %3, %4};" ::"r"(a), "r"(x), "r"(y), "r"(z), "r"(w) : "memory");
}
template <class T>
__device__ __forceinline__ T* at(const void* base, uint32_t off) {
  uint64_t r;
  asm("{\n.reg .u32 lo, hi;\nmov.b64 {lo, hi}, %1;\nadd.cc.u32 lo, lo, %2;\naddc.u32 hi, hi, 0;\nmov.b64 %0, {lo, hi};\n}"
      : "=l"(r) : "l"(base), "r"(off));
  return (T*)__cvta_global_to_generic(r);
}
__device__ __forceinline__ void add_granules(float (&red)[32], const uint32_t (&g)[16]) {
#pragma unroll
  for (int i = 0; i < 16; i++) { red[2 * i] += bf_lo(g[i]); red[2 * i + 1] += bf_hi((i & 3) ? g[i] : g[i] & ~TAG_BIT); }
}
__device__ __forceinline__ bool granules_ok(const uint32_t (&g)[16], uint32_t tag) {
  uint32_t u, v;
  asm("lop3.b32 %0, %1, %2, %3, 0x7E;" : "=r"(u) : "r"(g[0]), "r"(g[4]), "r"(tag));
  asm("lop3.b32 %0, %1, %2, %3, 0x7E;" : "=r"(v) : "r"(g[8]), "r"(g[12]), "r"(tag));
  return __all_sync(0xffffffffu, ((u | v) & TAG_BIT) == 0);
}
__device__ __forceinline__ unsigned ld_acquire(const unsigned* p) {
  unsigned v;
  asm volatile("ld.acquire.gpu.global.u32 %0, [%1];" : "=r"(v) : "l"(p) : "memory");
  return v;
}
__device__ __forceinline__ void red_release(unsigned* p) {
  asm volatile("red.release.gpu.global.add.u32 [%0], 1;" ::"l"(p) : "memory");
}
__device__ __forceinline__ void st_release(unsigned* p, unsigned v) {
  asm volatile("st.release.gpu.global.u32 [%0], %1;" ::"l"(p), "r"(v) : "memory");
}

template <int K0, int K1>
__device__ __forceinline__ void ln_fetch(uint32_t (&xa)[144], uint32_t boxes, uint32_t lo) {
#pragma unroll
  for (int k = K0; k < K1; k++) ldsm4(((boxes + lo) ^ ((k & 3) << 5)) + (k >> 2) * 8192, xa[4 * k], xa[4 * k + 1], xa[4 * k + 2], xa[4 * k + 3]);
}
template <int K0, int K1>
__device__ __forceinline__ void ln_sums(const uint32_t (&xa)[144], float (&sm)[4][4]) {
#pragma unroll
  for (int k = K0; k < K1; k++) hmma_k16(sm[k & 3], xa[4 * k], xa[4 * k + 1], xa[4 * k + 2], xa[4 * k + 3], 0x3F803F80u, 0x3F803F80u);
}
__device__ __forceinline__ uint32_t sq8(const uint32_t* a) {
  uint32_t t, u;
  asm("mul.rn.bf16x2 %0, %1, %1;" : "=r"(t) : "r"(a[0]));
  asm("mul.rn.bf16x2 %0, %1, %1;" : "=r"(u) : "r"(a[2]));
#pragma unroll
  for (int i = 4; i < 16; i += 4) {
    asm("fma.rn.bf16x2 %0, %1, %1, %0;" : "+r"(t) : "r"(a[i]));
    asm("fma.rn.bf16x2 %0, %1, %1, %0;" : "+r"(u) : "r"(a[i + 2]));
  }
  return add2(t, u);
}
__device__ __forceinline__ void ln_centre(uint32_t (&xa)[144], int j0, int j1, uint32_t mm0, uint32_t mm1, float& sq0, float& sq1) {
#pragma unroll
  for (int j = 0; j < 72; j += 8)
    if (j >= j0 && j < j1) {
#pragma unroll
      for (int k = j; k < j + 8; k++) {
        xa[2 * k] = sub2(xa[2 * k], mm0);
        xa[2 * k + 1] = sub2(xa[2 * k + 1], mm1);
      }
      const uint32_t t0 = sq8(xa + 2 * j), t1 = sq8(xa + 2 * j + 1);
      sq0 += bf_lo(t0) + bf_hi(t0);
      sq1 += bf_lo(t1) + bf_hi(t1);
    }
}
__device__ __forceinline__ float ln_rstd(float var) {
  float sd;
  asm("sqrt.approx.ftz.f32 %0, %1;" : "=f"(sd) : "f"(bfr(bfr(fmaxf(var, 0.0f)) + 1e-5f)));
  return rcp(bfr(sd));
}
__device__ __forceinline__ uint32_t silu2(uint32_t t) { return pack2(silu_f(bf_lo(t)), silu_f(bf_hi(t))); }
__device__ __forceinline__ float sum8(float v) {
#pragma unroll
  for (int d = 4; d; d >>= 1) v += __shfl_xor_sync(0xffffffffu, v, d);
  return v;
}
__device__ __forceinline__ void await_count(const unsigned* p, unsigned target, unsigned sleep_ns) {
#pragma unroll 1
  for (int n = 0; n < (1 << 18) && __any_sync(0xffffffffu, (int)(ld_acquire(p) - target) < 0); n++) __nanosleep(sleep_ns);
}
__device__ __forceinline__ void bulk_load(uint32_t dst, const void* src, uint32_t bytes, uint32_t bar) {
  asm volatile("cp.async.bulk.shared::cluster.global.mbarrier::complete_tx::bytes [%0], [%1], %2, [%3];"
               ::"r"(dst), "l"(src), "r"(bytes), "r"(bar) : "memory");
}
__device__ __forceinline__ void proxy_fence() { asm volatile("fence.proxy.async;" ::: "memory"); }

template <int V> struct IC { static constexpr int value = V; };

struct Ctx {
  uint32_t sb;
  uint8_t* sp;
  uint32_t rank;
  Scratch* gs;
};

__device__ __forceinline__ void dly(const Ctx&, int) {}
__device__ __forceinline__ void load_box(uint32_t dst, const CUtensorMap* tm, int c0, int c1, uint32_t bar, uint64_t pol) {
  asm volatile("{\n.reg .pred p;\nelect.sync _|p, 0xffffffff;\n"
               "@p cp.async.bulk.tensor.2d.shared::cluster.global.mbarrier::complete_tx::bytes.multicast::cluster.L2::cache_hint"
               " [%0], [%1, {%2, %3}], [%4], %5, %6;\n}"
               ::"r"(dst), "l"(tm), "r"(c0), "r"(c1), "r"(bar), "h"((uint16_t)3), "l"(pol) : "memory");
}
template <int BOXES>
__device__ __forceinline__ void load_stage(uint32_t dst, const CUtensorMap* tm, int c0, int c1, uint32_t bar, uint32_t bytes, uint64_t pol) {
  asm volatile("{\n.reg .pred p;\nelect.sync _|p, 0xffffffff;\n"
               "@p mbarrier.arrive.expect_tx.shared::cta.b64 _, [%4], %7;\n"
               "@p cp.async.bulk.tensor.2d.shared::cluster.global.mbarrier::complete_tx::bytes.multicast::cluster.L2::cache_hint"
               " [%0], [%1, {%2, %3}], [%4], %5, %6;\n}"
               ::"r"(dst), "l"(tm), "r"(c0), "r"(c1), "r"(bar), "h"((uint16_t)3), "l"(pol), "r"(bytes) : "memory");
  if (BOXES == 2) load_box(dst + 8192, tm, c0, c1 + 64, bar, pol);
}
__device__ __forceinline__ void attn_producer(const Ctx& cx, int qb, int hs, const CUtensorMap* tmX, const CUtensorMap* tmK,
                                              const CUtensorMap* tmV, const CUtensorMap* tmWq, const CUtensorMap* tmWo) {
  const uint32_t full = cx.sb + SM_FULL, empty = cx.sb + SM_EMPTY, ring = cx.sb + SM_RING + cx.rank * 16384;
  const uint64_t keep = policy_evict_normal(), last_use = policy_evict_first();
  auto acquire = [&](int st) {
    mbar_wait(empty + 8 * (st & 3), ((st >> 2) ^ ((st & 3) >> 1) ^ 1) & 1);
    if (st > 3) dly(cx, st);
  };
  if (elect_one()) {
#pragma unroll
    for (int j = 0; j < 3; j++) {
      mbar_expect_tx(cx.sb + SM_XFULL + 96 + 8 * j, 24576);
      tma3d(cx.sb + SM_X + 73728 + j * 24576, tmX, qb * 128 + 64, j * 3, cx.sb + SM_XFULL + 96 + 8 * j);
    }
  }
  __syncwarp();
  const int c0 = cx.rank * 64;
#pragma unroll 1
  for (int st = 0; st < NST_Q - 1; st++) {
    const bool half = st >= 10 && st < 13;
    const int i = st - (st < 5 ? 0 : st < 10 ? 5 : half ? 10 : 13), sl = st & 3;
    const int n0 = (hs * 4 + (st < 5 ? 0 : st < 10 ? 2 : half ? 3 : 1)) * DH + (half ? 0 : c0);
    const int k0 = half ? (i < 2 ? 256 * i + 2 * c0 : 448 + c0) : (i < 3 ? 128 * i : 128 * i - 64);
    if (st == 1) mbar_wait(cx.sb + SM_XFULL + 16, 0);
    acquire(st);
    load_stage<1>(ring + sl * STAGE, tmWq, n0, k0, full + 8 * sl, i == 2 ? 16384 : (half && i) ? 24576 : 32768, last_use);
    if (i != 2 && !(half && i && c0)) load_box(ring + sl * STAGE + 8192, tmWq, n0, k0 + 64, full + 8 * sl, last_use);
    if ((st == 3 || st == 4 || st == 8) && elect_one()) {
      if (st != 4) tma2d_prefetch(tmWq, (hs * 4 + 2 - (st >> 3)) * DH + (qb & 1) * 64, (qb >> 1) * 64);
      else if (qb < 9) tma2d_prefetch(tmWq, (hs * 4 + 3) * DH, qb * 64);
    }
    __syncwarp();
  }
  int vrow = 0;
  uint64_t vpol = keep;
#pragma unroll 1
  for (int j = 0; j < 32; j++) {
    const int st = NST_Q - 1 + 4 * j, row = (hs * 2 + (j >> 4)) * SEQ + (j & 7) * 256;
    const uint64_t pol = (j & 8) ? last_use : keep;
    if (j < 7 && qb < 8 && elect_one()) tma2d_prefetch((qb & 4) ? tmV : tmK, (qb & 1) * 64, row + 256 + (qb & 2) * 64);
    __syncwarp();
    if (j == 24) mbar_wait(cx.sb + SM_BAR_Q3, 0);
    acquire(st);
    load_stage<1>(ring + SL_KE * STAGE, tmK, c0, row, full + 8 * SL_KE, 32768, pol);
    acquire(st + 1);
    if (j) load_stage<1>(ring + SL_VE * STAGE, tmV, c0, vrow, full + 8 * SL_VE, 32768, vpol);
    else load_stage<2>(ring + SL_VE * STAGE, tmWq, (hs * 4 + 1) * DH + c0, 448, full + 8 * SL_VE, 32768, last_use);
    vrow = row + 128;
    vpol = pol;
    acquire(st + 2);
    load_stage<1>(ring + SL_KO * STAGE, tmK, c0, vrow, full + 8 * SL_KO, 32768, pol);
    acquire(st + 3);
    load_stage<1>(ring + SL_VO * STAGE, tmV, c0, row, full + 8 * SL_VO, 32768, pol);
  }
  acquire(NST_Q + NST_KV - 1);
  load_stage<1>(ring + SL_KE * STAGE, tmV, c0, vrow, full + 8 * SL_KE, 32768, last_use);
#pragma unroll 1
  for (int u = 0; u < NST_O; u++) {
    const int st = NST_Q + NST_KV + u, sl = st & 3;
    const int blk = u < 4 && cx.rank ? 8 : ((hs + max(u >> 1, 1)) & 7);
    const int head = u < 4 ? u ^ (u >> 1) : ((u & 1) * 2 + cx.rank + 3) & 3;
    acquire(st);
    load_stage<1>(ring + sl * STAGE, tmWo, blk * 64, hs * 512 + head * 128, full + 8 * sl, 32768, last_use);
  }
}

__device__ __forceinline__ uint32_t xn_offset(uint32_t row, int lane) {
  return (row >> 6) * (9 * 8192) + (row & 63) * 128 + ((((lane >> 2) ^ row) & 7) << 4) + (lane & 3) * 4;
}

__device__ __forceinline__ void attn_rows(const Ctx& cx, int qb, int hs, int hw, int lane, const CUtensorMap* tmX16,
                                          const __nv_bfloat16* w_r) {
  extern __shared__ __align__(1024) uint8_t smem_rows[];
  auto box = [&](int blk) { return blk < 8 ? SM_SLOT + 2 * STAGE + 8192 + (blk >> 2) * 16384 + (blk & 3) * 2048 : SM_BOX8; };
  const uint32_t sb = smem_u32(smem_rows);
  if (hw == 0) {
    bar_sync(BAR_HELPER, 160);
    if (elect_one()) {
      mbar_expect_tx(sb + SM_BAR_ROWS, 9 * 2048);
#pragma unroll
      for (int i = 0; i < 9; i++) tma2d(sb + box(i), tmX16, i * 64, qb * 128 + hs * 16, sb + SM_BAR_ROWS);
    }
    __syncwarp();
  }
  uint32_t g = (lane >> 3) * 128 + (((lane ^ (lane >> 3)) & 7) << 4);
  auto next = [&]() {
    g = ((g + 512) & 2047) ^ 64;
    asm volatile("" : "+r"(g));
  };
  float* const part = (float*)(smem_rows + SM_ROWS);
  mbar_wait(sb + SM_BAR_ROWS, 0);
  if (hw == 0) dly(cx, 190);
#pragma unroll 1
  for (int i = 0; i < 4; i++) {
    float a = 0.f, b = 0.f;
#pragma unroll
    for (int j = 0; j < 3; j++) {
      const uint4 v = *(const uint4*)(smem_rows + box(hw * 3 + j) + g);
      const uint32_t w[4] = {v.x, v.y, v.z, v.w};
#pragma unroll
      for (int k = 0; k < 4; k++) {
        a += bf_lo(w[k]) + bf_hi(w[k]);
        b = fmaf(bf_lo(w[k]), bf_lo(w[k]), fmaf(bf_hi(w[k]), bf_hi(w[k]), b));
      }
    }
    a = sum8(a);
    b = sum8(b);
    float* p = part + hw * 16 + (g >> 7);
    p[0] = a;
    p[48] = b;
    next();
  }
  bar_sync(BAR_ROWS, 96);
  if (hw == 0) dly(cx, 191);
  {
    const float* p = part + (lane & 15);
    const float mean = (p[0] + p[16] + p[32]) * (1.0f / DM), rstd = ln_rstd((p[48] + p[64] + p[80]) * (1.0f / DM) - mean * mean);
    const uint32_t mm = pack2(mean, mean), rr = pack2(rstd - bfr(rstd), rstd);
#pragma unroll 1
    for (int u = hw * 12; u < hw * 12 + 12; u++) {
      const int blk = u >> 2;
      uint4* q = (uint4*)(smem_rows + box(blk) + g);
      uint4 v = *q;
      const uint32_t m = __shfl_sync(0xffffffffu, mm, g >> 7), r = __shfl_sync(0xffffffffu, rr, g >> 7);
      const uint32_t hi = __byte_perm(r, 0, 0x3232), lo = __byte_perm(r, 0, 0x1010);
      auto norm = [&](uint32_t w) {
        const uint32_t xc = sub2(w, m);
        return fma2(xc, hi, mul2(xc, lo));
      };
      v = make_uint4(norm(v.x), norm(v.y), norm(v.z), norm(v.w));
      *q = v;
      *at<uint4>(cx.gs->xn + ((qb * 2 + (hs >> 2)) * 9 + blk) * 512 + (hs & 3) * 128, g) = v;
      next();
    }
  }
  bar_sync(BAR_ROWS, 96);
  if (hw == 0) {
    dly(cx, 192);
    if (lane == 0) red_release(&cx.gs->rows[qb * 32]);
    dly(cx, 193);
  }
#pragma unroll 1
  for (int u = hw ? 13 * hw - 3 : 0; u < 13 * hw + 10; u++) {
    const int blk = u >> 2;
    const uint32_t o = (g + (u & 3) * 512) ^ ((u & 1) << 6);
    const uint4 v = *(const uint4*)(smem_rows + box(blk) + o);
    *at<uint4>(cx.gs->gate + (blk < 8 ? (qb * 8 + blk) * 144 + hs * 16 : (qb * 8 + hs) * 144 + 128) * 8, o) =
        make_uint4(silu2(v.x), silu2(v.y), silu2(v.z), silu2(v.w));
  }
  if (hw) dly(cx, 194 + hw);
  __nanosleep(8000);
#pragma unroll 1
  for (int blk = hw * 3; blk < hw * 3 + 3; blk++) {
    const uint4 c = __ldg(at<const uint4>(w_r, blk * 128 + ((g ^ (g >> 3)) & 0x70)));
#pragma unroll 1
    for (int i = 0; i < 4; i++) {
      const uint4 v = *(const uint4*)(smem_rows + box(blk) + g);
      part[blk * 16 + (g >> 7)] =
          sum8(fmaf(bf_lo(v.x), bf_lo(c.x), fmaf(bf_hi(v.x), bf_hi(c.x), fmaf(bf_lo(v.y), bf_lo(c.y), bf_hi(v.y) * bf_hi(c.y)))) +
               fmaf(bf_lo(v.z), bf_lo(c.z), fmaf(bf_hi(v.z), bf_hi(c.z), fmaf(bf_lo(v.w), bf_lo(c.w), bf_hi(v.w) * bf_hi(c.w)))));
      next();
      __nanosleep(700);
    }
  }
  bar_sync(BAR_ROWS, 96);
  if (hw == 0) {
    dly(cx, 194);
    float d = 0.f;
#pragma unroll
    for (int j = 0; j < 9; j++) d += part[j * 16 + (lane & 15)];
    const uint32_t row = qb * 128 + hs * 16 + (lane & 15), b = pack2(0.f, d);
    *at<uint32_t>(cx.gs->key, row * 4) = (b ^ ((int)b < 0 ? 0xFFFF0000u : 0x80000000u)) + 0xFFFF - row;
    __syncwarp();
    if (lane == 0) red_release(&cx.gs->rows[qb * 32 + 1]);
  }
}

constexpr uint32_t SM_XO = SM_SLOT, SM_GO = SM_SLOT + STAGE, SM_P8 = SM_SLOT + 2 * STAGE;
__device__ __forceinline__ void attn_helper(const Ctx& cx, int qb, int hs, int lane, const __nv_bfloat16* wo, const CUtensorMap* tmX16) {
  unsigned e = 0;
  if (lane == 0) {
    e = cx.gs->launch[blockIdx.x];
    cx.gs->launch[blockIdx.x] = e + 1;
  }
  e = __shfl_sync(0xffffffffu, e, 0);
  if (lane == 0) {
    *(uint32_t*)(cx.sp + SM_TAG) = (~e & 1) * TAG_BIT;
    mbar_arrive(cx.sb + SM_BAR_MISC);
  }
  bar_sync(BAR_HELPER, 64);
  await_count(&cx.gs->rows[qb * 32 + 1], 8 * (e + 1), 1000);
  await_count(&cx.gs->q3_flag[qb * 8 + hs], e + 1, 1000);
  proxy_fence();
  if (elect_one()) {
    mbar_expect_tx(cx.sb + SM_BAR_Q3, 16384);
#pragma unroll
    for (int i = 0; i < 2; i++) bulk_load(cx.sb + SM_SLOT + 2 * STAGE + i * 16384 + 8192, cx.gs->q3 + (qb * 16 + hs * 2 + i) * 512, 8192, cx.sb + SM_BAR_Q3);
  }
  __syncwarp();
  bar_sync(BAR_HELPER, 64);
  prefetch_l2(at<const void>(wo, (hs * 512 + qb * 32 + lane) * (DM * 2)), DM * 2);
  await_count(&cx.gs->ycnt, 4 * (e + 1), 500);
  const uint32_t mykey = __ldcg(at<const uint32_t>(cx.gs->top, (lane >> 1) * 4)), myrow = 0xFFFF - (mykey & 0xFFFF);
#pragma unroll 1
  for (uint32_t todo = __ballot_sync(0xffffffffu, lane < 16 && ((lane & 1) ? myrow >> 4 == qb * 8 + hs : myrow >> 7 == qb)); todo; todo &= todo - 1) {
    const int i = __ffs(todo) - 1, blk = (i & 1) ? 8 : hs;
    const uint32_t key = __shfl_sync(0xffffffffu, mykey, i), row = 0xFFFF - (key & 0xFFFF), o = xn_offset(row, lane);
    const uint32_t t = __ldcg(at<const uint32_t>(cx.gs->xn, o + blk * 8192));
    const float2* p = at<const float2>(cx.gs->ypart, ((i >> 1) * DM + blk * 64 + 2 * lane) * 4);
    const float2 y0 = __ldcg(p), y1 = __ldcg(p + TOPC * DM / 2), y2 = __ldcg(p + TOPC * DM), y3 = __ldcg(p + 3 * TOPC * DM / 2);
    const float rs = bfr(rcp(1.0f + ex2(-1.4426950408889634f * bf_hi(key ^ ((int)key < 0 ? 0x80000000u : 0xFFFF0000u)))));
    const uint32_t y = pack2((y0.x + y1.x) + (y2.x + y3.x), (y0.y + y1.y) + (y2.y + y3.y));
    const uint32_t u = pack2(bf_lo(y) * rs, bf_hi(y) * rs);
    *at<uint32_t>(cx.gs->gate, ((qb * 8 + hs) * 144 + ((i & 1) ? 128 + (row & 15) : row & 127)) * 128 + (o & 127)) = silu2(add2(t, u));
  }
  proxy_fence();
  bar_sync(BAR_OA, 352);
  if (elect_one()) {
    const uint32_t bar = cx.sb + SM_BAR_XG;
    mbar_expect_tx(bar, 2 * 144 * 128);
    bulk_load(cx.sb + SM_GO, cx.gs->gate + (qb * 8 + hs) * (144 * 8), 144 * 128, bar);
#pragma unroll 1
    for (int i = 0; i < 9; i++) tma2d_stream(cx.sb + SM_XO + i * 2048, tmX16, i < 8 ? hs * 64 : 512, qb * 128 + (i < 8 ? i : hs) * 16, bar);
  }
  __syncwarp();
  const uint4* src = cx.gs->part + (qb * 64 + 56 + hs) * 1024;
#pragma unroll 1
  for (int n = 0; n < (1 << 16); n++) {
    __nanosleep(n ? 400 : 700);
    uint32_t a, b, d, t;
    ld_gran(at<const uint4>(src, (lane & 7) * 2048 + 2032), a, b, d, t);
    if (__all_sync(0xffffffffu, ((a >> 16) ^ e) & 1)) break;
  }
  if (elect_one()) {
    mbar_expect_tx(cx.sb + SM_BAR_P8, 16384);
    bulk_load(cx.sb + SM_P8, src, 16384, cx.sb + SM_BAR_P8);
  }
  __syncwarp();
}
__device__ __forceinline__ void attn_finish8(const Ctx& cx, int qb, int hs, int hw, int lane, __nv_bfloat16* out) {
  const uint32_t tag = *(const uint32_t*)(cx.sp + SM_TAG);
  mbar_wait(cx.sb + SM_BAR_P8, 0);
  mbar_wait(cx.sb + SM_BAR_XG, 0);
#pragma unroll 1
  for (int g = 2 - hw; g < 4; g += 3) {
    float acc[8] = {0.f, 0.f, 0.f, 0.f, 0.f, 0.f, 0.f, 0.f};
    uint32_t a[4];
#pragma unroll 1
    for (uint32_t o = g * 512 + lane * 16; o < 16384; o += 2048) {
      lds128(cx.sb + SM_P8 + o, a[0], a[1], a[2], a[3]);
#pragma unroll 1
      for (int n = 0; n < (1 << 16) && __any_sync(0xffffffffu, (a[0] & TAG_BIT) != tag); n++)
        ld_gran(at<const uint4>(cx.gs->part, (qb * 64 + 56 + hs) * 16384 + o), a[0], a[1], a[2], a[3]);
      a[0] &= ~TAG_BIT;
#pragma unroll
      for (int j = 0; j < 4; j++) { acc[2 * j] += bf_lo(a[j]); acc[2 * j + 1] += bf_hi(a[j]); }
    }
    asm volatile("" : "+r"(lane));
    const uint32_t tile = cx.sb + SM_XO + (128 + (lane & 15)) * 128 + (((lane >> 4) ^ (lane & 7)) << 4);
    uint32_t b[4];
    ldsm4((tile ^ (g << 5)) + STAGE, a[0], a[1], a[2], a[3]);
    ldsm4(tile ^ (g << 5), b[0], b[1], b[2], b[3]);
    stsm4(tile ^ (g << 5), fma2(pack2(acc[0], acc[1]), a[0], b[0]), fma2(pack2(acc[2], acc[3]), a[1], b[1]),
          fma2(pack2(acc[4], acc[5]), a[2], b[2]), fma2(pack2(acc[6], acc[7]), a[3], b[3]));
  }
  bar_sync(BAR_ROWS, 96);
#pragma unroll 1
  for (int ch = threadIdx.x - 32; ch < 128; ch += 96)
    *at<uint4>(out, ((qb * 128 + hs * 16 + (ch >> 3)) * DM + 512 + (ch & 7) * 8) * 2) =
        *(const uint4*)(cx.sp + SM_XO + (128 + (ch >> 3)) * 128 + (((ch ^ (ch >> 3)) & 7) << 4));
}

constexpr float S_BIAS = 24.f, S_SCALE = 16777216.f;
constexpr float SUM_HI = 7.2057594e16f, SUM_LO = 9.0949470e-13f;

__device__ __forceinline__ float offset_for(const float* o) {
  const float m = fmaxf(fmaxf(fmaxf(fabsf(o[0]), fabsf(o[9])), fmaxf(fabsf(o[16]), fabsf(o[25]))),
                        fmaxf(fmaxf(fabsf(o[32]), fabsf(o[41])), fmaxf(fabsf(o[48]), fabsf(o[57]))));
  return __uint_as_float(__float_as_uint(m) & 0x7F800000u) * (48.f * S_SCALE);
}
template <int LO, int HI>
__device__ __forceinline__ void softmax_exp(float (&s)[64]) {
#pragma unroll
  for (int i = LO; i < HI; i++) s[i] = ex2(s[i]);
}
__device__ __forceinline__ void row_sums(const uint32_t (&pf)[32], float& l0, float& l1) {
  uint32_t t[16];
#pragma unroll
  for (int i = 0; i < 16; i++) t[i] = add2(pf[(i >> 1) * 4 + (i & 1)], pf[(i >> 1) * 4 + 2 + (i & 1)]);
#pragma unroll
  for (int i = 0; i < 8; i++) t[i] = add2(t[(i >> 1) * 4 + (i & 1)], t[(i >> 1) * 4 + 2 + (i & 1)]);
#pragma unroll
  for (int i = 0; i < 4; i++) t[i] = add2(t[(i >> 1) * 4 + (i & 1)], t[(i >> 1) * 4 + 2 + (i & 1)]);
  t[0] = add2(t[0], t[2]);
  t[1] = add2(t[1], t[3]);
  l0 = (l0 + bf_lo(t[0])) + bf_hi(t[0]);
  l1 = (l1 + bf_lo(t[1])) + bf_hi(t[1]);
}
__device__ __forceinline__ void softmax_redo(uint32_t (&pf)[32], const uint32_t (&q)[32], const __nv_bfloat16* kblk, int lane, float& n0,
                                             float& n1, float& l0, float& l1, float& sc0, float& sc1, float bias) {
  float x0 = -3.0e38f, x1 = -3.0e38f;
#pragma unroll 1
  for (int u = 0; u < 16; u++) {
    const uint32_t* kp = (const uint32_t*)(kblk + ((u & 7) * 16 + (lane >> 2)) * DH) + (lane & 3);
    float d[2][4] = {};
#pragma unroll
    for (int k = 0; k < 16; k++)
      hmma_k16(d[k & 1], q[2 * (k & 14)], q[2 * (k & 14) + 1], q[2 * (k & 14) + 2], q[2 * (k & 14) + 3],
               kp[(k & 1) * 4 * DH + (k >> 1) * 8], kp[(k & 1) * 4 * DH + (k >> 1) * 8 + 4]);
    if (u < 8) {
      x0 = fmaxf(fmaxf(x0, fmaxf(d[0][0], d[0][1])), fmaxf(d[1][0], d[1][1]));
      x1 = fmaxf(fmaxf(x1, fmaxf(d[0][2], d[0][3])), fmaxf(d[1][2], d[1][3]));
      if (u == 7) {
#pragma unroll
        for (int m = 1; m < 4; m <<= 1) {
          x0 = fmaxf(x0, __shfl_xor_sync(0xffffffffu, x0, m));
          x1 = fmaxf(x1, __shfl_xor_sync(0xffffffffu, x1, m));
        }
        x0 = fminf(bias - x0, n0);
        x1 = fminf(bias - x1, n1);
        sc0 = ex2(x0 - n0);
        sc1 = ex2(x1 - n1);
        n0 = x0;
        n1 = x1;
        l0 *= sc0;
        l1 *= sc1;
      }
    } else {
#pragma unroll
      for (int i = 0; i < 28; i++) pf[i] = pf[i + 4];
#pragma unroll
      for (int i = 0; i < 4; i++) {
        const float n = (i & 1) ? n1 : n0;
        pf[28 + i] = pack2(ex2(d[i >> 1][(i & 1) * 2] + n), ex2(d[i >> 1][(i & 1) * 2 + 1] + n));
        ((i & 1) ? l1 : l0) += bf_lo(pf[28 + i]) + bf_hi(pf[28 + i]);
      }
    }
  }
}

#define TH(i)
__device__ __forceinline__ void attn_consumer(const Ctx& cx, int qb, int hs, int wg, int cw, int lane, const __nv_bfloat16* x,
                                              const __nv_bfloat16* kc, __nv_bfloat16* out) {
  const uint32_t full = cx.sb + SM_FULL;
  const uint32_t ring = cx.sb + SM_RING;
  uint32_t lo = ((cw & 3) * 16 + (lane & 15)) * 128 + (((lane >> 4) ^ (lane & 7)) << 4);
  const uint32_t slot = cx.sb + SM_SLOT + wg * 16384;
  auto frag = [&](int sl, int k) { return ((slot + sl * STAGE + lo) ^ ((k & 3) << 5)) + (k >> 2) * 8192; };
  auto park = [&](const float (&a)[64], int sl, int k0, int k1, float f0, float f1, float g0 = -0.f, float g1 = -0.f) {
#pragma unroll
    for (int k = 0; k < 8; k++)
      if (k >= k0 && k < k1)
        stsm4(frag(sl, k), pack2(fmaf(a[8 * k], f0, g0), fmaf(a[8 * k + 1], f0, g0)), pack2(fmaf(a[8 * k + 2], f1, g1), fmaf(a[8 * k + 3], f1, g1)),
              pack2(fmaf(a[8 * k + 4], f0, g0), fmaf(a[8 * k + 5], f0, g0)), pack2(fmaf(a[8 * k + 6], f1, g1), fmaf(a[8 * k + 7], f1, g1)));
  };
  const bool signaller = lane == 0 && (cw & 3) < 2;
  int my_turn = 1 + wg, other_turn = 2 - wg;

  uint32_t pf[32], q[32], empty_c;
#pragma nv_diag_suppress 549
  float o[64], l0, l1, c0 = 0.f, c1 = 0.f;
  {
    uint32_t xa[144];
    float rstd0, rstd1;
    {
      const uint32_t xb = cx.sb + SM_X + wg * 73728, xf = cx.sb + SM_XFULL + wg * 96;
      float sm[4][4] = {};
      prof(wg, 0);
      empty_c = mapa(cx.sb + SM_EMPTY, cw & 1);
      mbar_wait(xf, 0);
      TH(0)
      ln_fetch<0, 12>(xa, xb, lo);
      mbar_wait(xf + 8, 0);
      TH(1)
      ln_fetch<12, 24>(xa, xb, lo);
      ln_sums<0, 12>(xa, sm);
      mbar_wait(xf + 16, 0);
      TH(2)
      ln_fetch<24, 36>(xa, xb, lo);
      ln_sums<12, 36>(xa, sm);
      block_fence(36);
      if (wg) bar_arrive(other_turn, 256);
      block_fence(35);
      TH(3)
      rstd0 = ((sm[0][0] + sm[1][0]) + (sm[2][0] + sm[3][0])) * (1.0f / DM);
      rstd1 = ((sm[0][2] + sm[1][2]) + (sm[2][2] + sm[3][2])) * (1.0f / DM);
    }
    const uint32_t mm0 = pack2(rstd0, rstd0), mm1 = pack2(rstd1, rstd1);
    rstd0 -= bf_lo(mm0);
    rstd1 -= bf_lo(mm1);
    rstd0 *= rstd0 * (-0.25f * DM);
    rstd1 *= rstd1 * (-0.25f * DM);
    auto ln_finish = [&]() {
      rstd0 += __shfl_xor_sync(0xffffffffu, rstd0, 1); rstd1 += __shfl_xor_sync(0xffffffffu, rstd1, 1);
      rstd0 += __shfl_xor_sync(0xffffffffu, rstd0, 2); rstd1 += __shfl_xor_sync(0xffffffffu, rstd1, 2);
      rstd0 = ln_rstd(rstd0 * (1.0f / DM)) * SM_SCALE_LOG2;
      rstd1 = ln_rstd(rstd1 * (1.0f / DM)) * SM_SCALE_LOG2;
    };
    ln_centre(xa, 0, X_C0, mm0, mm1, rstd0, rstd1);
    if (wg == 0) {
      bar_sync(4, 128);
      if (signaller) {
        asm volatile("mbarrier.arrive.shared::cluster.b64 _, [%0], 2;" ::"r"(empty_c + 16) : "memory");
        asm volatile("mbarrier.arrive.shared::cluster.b64 _, [%0], 2;" ::"r"(empty_c + 24) : "memory");
      }
      block_fence(37);
      pin(xa);
      ln_centre(xa, X_C0, X_C1, mm0, mm1, rstd0, rstd1);
    }
    pin(xa);

    extern __shared__ __align__(1024) uint8_t smem_q[];
    const uint32_t ring = smem_u32(smem_q) + SM_RING;
    auto release = [&](int st) { if (signaller) mbar_arrive_cluster(empty_c + 8 * (st & 3)); };
    auto q_stage = [&](float (&acc)[64], int st, int i, int last) {
      mbar_wait(full + 8 * (st & 3), (st >> 2) & 1);
      if (i != (wg ? last : 1)) bar_sync(my_turn, 256);
      wg_fence();
      const uint64_t db = mkdesc(ring + (st & 3) * STAGE, 16384);
#pragma unroll
      for (int k = 0; k < 8; k++) {
        const int kb = (i < 3 ? 8 * i : 8 * i - 4) + k;
        if (i != 2 || k < 4) mma_n128<1>(acc, xa[4 * kb], xa[4 * kb + 1], xa[4 * kb + 2], xa[4 * kb + 3], db + k * 128, kb > 0);
      }
      wg_commit();
      if (i != (wg ? last - 1 : 0)) bar_arrive(other_turn, 256);
    };
    auto q_release = [&](int st, int i, int last) {
      if (i == 1 || i == last) {
        wg_wait<1>();
        if (i == last || !wg) release(st - 1);
      }
      if (i != last - 1 && (i || wg)) {
        wg_wait<0>();
        release(st);
      }
    };
    {
      float (&acc)[64] = o;
#pragma unroll 1
      for (int p = 0; p < 2; p++) {
#pragma unroll
        for (int i = 0; i < 5; i++) {
          q_stage(acc, 5 * p + i, i, 4);
          if (p == 0 && i != 3) {
            if (i == 0 && wg) bar_arrive(BAR_HELPER, 160);
            if ((wg || i) && i < 3) ln_centre(xa, i == 0 ? X_C0 : i == 1 ? X_C1 : X_C2, i == 0 ? X_C1 : i == 1 ? X_C2 : 72, mm0, mm1, rstd0, rstd1);
            if (i == 4) ln_finish();
            pin(xa);
          }
          q_release(5 * p + i, i, 4);
        }
        pin(acc);
#pragma unroll
        for (int k = 0; k < 8; k += 2) {
          park(acc, p, k, k + 2, rstd0, rstd1);
          if (k < 6) block_fence(40 + k);
        }
      }
    }
    {
      float (&h)[32] = *(float (*)[32])&o[0];
#pragma unroll
      for (int i = 0; i < 3; i++) {
        const uint32_t sl = (10 + i) & 3;
        mbar_wait(full + 8 * sl, ((10 + i) >> 2) & 1);
        if (i != (wg ? 2 : 1)) bar_sync(my_turn, 256);
        wg_fence();
#pragma unroll
        for (int k = 0; k < 16 - 4 * i; k++) {
          const int kb = (i == 2 ? 28 : 16 * i) + k;
          const uint64_t db = mkdesc(ring + sl * STAGE, 16) + (i == 2 && k >= 4 ? k + 4 : k) * 128;
          mma_n64<1>(h, xa[4 * kb], xa[4 * kb + 1], xa[4 * kb + 2], xa[4 * kb + 3], db, kb > 0);
        }
        wg_commit();
        if (i != (wg ? 1 : 0)) bar_arrive(other_turn, 256);
        q_release(10 + i, i, 2);
      }
      pin(h);
      park(o, 2, 0, 2, rstd0, rstd1);
      block_fence(49);
      park(o, 2, 2, 4, rstd0, rstd1);
    }
#pragma unroll
    for (int i = 0; i < 4; i++) {
      q_stage(o, 13 + i, i, 3);
      q_release(13 + i, i, 3);
    }
    prof(wg, 6);
#pragma unroll
    for (int i = 0; i < 32; i++) pf[i] = xa[112 + i];
    l0 = 0.25f * rcp(rstd0);
    l1 = 0.25f * rcp(rstd1);
  }

  uint32_t oa[96];
  const uint32_t zero = __shfl_sync(0xffffffffu, blockIdx.y, lane);
  my_turn = __shfl_sync(0xffffffffu, my_turn, lane);
  other_turn = __shfl_sync(0xffffffffu, other_turn, lane);
  lo = __shfl_sync(0xffffffffu, lo, lane);
  {
    float s[64], n0 = 0.f, n1 = 0.f;
    float lp0, lp1;
    float i0 = 0.f, i1 = 0.f;
    float hi = 0.f;
    bool redo;
    auto turn = [&](int it, auto kc_) -> bool {
      constexpr int KIND = decltype(kc_)::value;
      constexpr uint32_t slk = KIND == 1 ? SL_KO : SL_KE, slv = KIND == 1 ? SL_VO : SL_VE, slkn = KIND == 1 ? SL_KE : SL_KO;
      constexpr int SPLIT = KIND == 3 ? X_SPLIT3 : X_SPLIT, PARK1 = X_PARK;
      const uint32_t par = ((it + NST_Q / 2) >> 1) & 1;
      const int hsl = max((it >> 4) - 1, 0);
      const bool second = KIND == 1 && (it & 15) == 1;
      const uint64_t dk = mkdesc(ring + slk * STAGE, 16), dv = mkdesc(ring + slv * STAGE, 16384);
      auto qk = [&](int k, int acc) {
        if (KIND == 3) mma_n128_ss<0>(s, mkdesc(slot + hsl * STAGE, 16) + (k >> 2) * 512 + (k & 3) * 2, dk + (k >> 2) * 1024 + (k & 3) * 2, acc);
        else mma_n128<0>(s, q[4 * k], q[4 * k + 1], q[4 * k + 2], q[4 * k + 3], dk + (k >> 2) * 1024 + (k & 3) * 2, acc);
      };
      auto pv = [&]() {
#pragma unroll
        for (int k = 0; k < 8; k++)
          mma_n128<1>(o, pf[4 * k], pf[4 * k + 1], pf[4 * k + 2], pf[4 * k + 3], dv + k * 128, k > 0 || !second);
        wg_commit();
      };
      if (KIND == 2 && (it & 15) == 2) {
        n0 += S_BIAS;
        n1 += S_BIAS;
        l0 *= S_SCALE;
        l1 *= S_SCALE;
        hi = SUM_HI * S_SCALE;
        asm volatile("" : "+f"(n0), "+f"(n1), "+f"(l0), "+f"(l1), "+f"(hi)::"memory");
      }
      lp0 = l0; lp1 = l1;
#define TS(i)
      {
        TS(0)
        if (KIND == 3) {
          asm volatile("fence.proxy.async.shared::cta;" ::: "memory");
          const float t0 = lp0 + __shfl_xor_sync(0xffffffffu, lp0, 1), t1 = lp1 + __shfl_xor_sync(0xffffffffu, lp1, 1);
          i0 = rcp(t0 + __shfl_xor_sync(0xffffffffu, t0, 2));
          i1 = rcp(t1 + __shfl_xor_sync(0xffffffffu, t1, 2));
          asm volatile("" : "+f"(i0), "+f"(i1)::"memory");
          block_fence(31, zero);
#pragma unroll
          for (int k = 0; k < X_N1; k++) ldsm4(frag(hsl, k), q[4 * k], q[4 * k + 1], q[4 * k + 2], q[4 * k + 3]);
        }
        if (KIND != 3) pin(q);
        pin(pf); pin(o);
        if (KIND != 3 && !second) {
#pragma unroll
          for (int i = 0; i < 64; i++) s[i] = ((i & 2) ? n1 : n0) + (i + 1) * 1e-30f;
        }
        if (KIND != 3) pin(s);
        bar_sync(my_turn, 256);
        wg_fence();
#pragma unroll
        for (int k = 0; k < 8; k++) qk(k, k > 0 || (KIND != 3 && !second));
        wg_commit();
        TS(2)
        mbar_wait(full + 8 * slv, par);
        if (KIND == 2 && (it & 15) == 2) {
          c0 = offset_for(o);
          c1 = offset_for(o + 2);
          asm volatile("" : "+f"(c0), "+f"(c1)::"memory");
          wg_fence();
        }
        if (KIND == 1 && (it & 13) == 1) {
          if (second) {
            park(o, hsl, PARK1, 8, i0, i1, c0, c1);
          } else {
#pragma unroll
            for (int i = 0; i < 64; i++) o[i] = fmaf(o[i], S_SCALE, (i & 2) ? c1 : c0);
            pin(o);
          }
          wg_fence();
        }
        if (KIND == 3) {
#pragma unroll
          for (int k = X_N1; k < 8; k++) ldsm4(frag(hsl, k), q[4 * k], q[4 * k + 1], q[4 * k + 2], q[4 * k + 3]);
          block_fence(32, zero);
        }
        TS(3)
        pv();
        bar_arrive(other_turn, 256);
        TS(4)
        wg_wait<1>();
      }
      pin(s);
      mbar_arrive_cluster_now<10 * KIND + 3>(empty_c + 8 * slk, signaller, zero);
      TS(5)
      if (KIND == 3) {
        n0 = n1 = l0 = l1 = 0.f;
        hi = SUM_HI;
        c0 *= -i0;
        c1 *= -i1;
      }
      softmax_exp<0, SPLIT>(s);
      pin(s);
      block_fence(10 * KIND + 4, zero);
      TS(6)
      wg_wait<0>();
      pin(o); pin(pf);
      mbar_arrive_cluster_now<10 * KIND + 5>(empty_c + 8 * slv, signaller, zero);
      TS(7)
      const bool kready = mbar_test(full + 8 * slkn, par);
      softmax_exp<SPLIT, 64>(s);
#pragma unroll
      for (int i = 0; i < 32; i++) pf[i] = pack2(s[2 * i], s[2 * i + 1]);
      row_sums(pf, l0, l1);
      if (KIND == 3) {
        park(o, hsl, 0, PARK1, i0, i1, c0, c1);
        if (it) prof(wg, 6 + (it >> 4));
        if (it >= 32 && cw == 0) bar_arrive(BAR_HELPER, 64);
      }
      redo = !(l0 + l1 <= hi) || (KIND == 3 && fminf(l0, l1) < SUM_LO);
      const bool leave = __any_sync(0xffffffffu, redo || !kready);
      return leave;
    };
    int it = -1;
#pragma unroll 1
    while (true) {
      mbar_wait(full + 8 * ((it & 1) ? SL_KE : SL_KO), ((it + NST_Q / 2) >> 1) & 1);
      it++;
#pragma unroll 1
      while (true) {
        if (it & 1) {
          if (turn(it, IC<1>()) || it == 63) break;
          it++;
        }
        if (it & 15) {
          if (turn(it, IC<2>())) break;
        } else {
          if (turn(it, IC<3>())) break;
        }
        it++;
      }
      if (__any_sync(0xffffffffu, redo)) {
        const int j = it & 15;
        float sc0 = 1.f, sc1 = 1.f;
        if (j == 0) n0 = n1 = 3.0e38f;
        l0 = j ? lp0 : 0.f;
        l1 = j ? lp1 : 0.f;
        softmax_redo(pf, q, kc + (size_t)((hs * 2 + (it >> 5)) * SEQ + j * 128) * DH, lane, n0, n1, l0, l1, sc0, sc1, j > 1 ? S_BIAS : 0.f);
        if (j == 0) {
          sc0 = sc1 = 1.f;
          hi = -1.f;
        }
        c0 *= sc0;
        c1 *= sc1;
#pragma unroll
        for (int i = 0; i < 16; i++) { o[4 * i] *= sc0; o[4 * i + 1] *= sc0; o[4 * i + 2] *= sc1; o[4 * i + 3] *= sc1; }
      }
      if (it == 63) break;
    }
  }

#define TE(i) {}
  {
    constexpr int ST0 = NST_Q + NST_KV;
    float acc[32], red[32], first[32];
    uint32_t tag;
    uint4* xch;
    auto await = [&](int st) { mbar_wait(full + 8 * (st & 3), (st >> 2) & 1); };
    auto release = [&](int st) { if (signaller) mbar_arrive_cluster(empty_c + 8 * (st & 3)); };
    auto unpark = [&](int h, int k0, int k1) {
#pragma unroll
      for (int k = 0; k < 8; k++)
        if (k >= k0 && k < k1) ldsm4(frag(h, k), oa[32 * h + 4 * k], oa[32 * h + 4 * k + 1], oa[32 * h + 4 * k + 2], oa[32 * h + 4 * k + 3]);
    };
    {
      float ar[64];
      asm volatile("fence.proxy.async.shared::cta;" ::: "memory");
      await(ST0 - 1);
      unpark(1, 0, 4);
      bar_sync(my_turn, 256);
      pin(pf); pin(o);
      wg_fence();
#pragma unroll
      for (int k = 0; k < 8; k++)
        mma_n128<1>(o, pf[4 * k], pf[4 * k + 1], pf[4 * k + 2], pf[4 * k + 3], mkdesc(ring + SL_KE * STAGE, 16384) + k * 128, 1);
      wg_commit();
      block_fence(66, zero);
      l0 += __shfl_xor_sync(0xffffffffu, l0, 1); l1 += __shfl_xor_sync(0xffffffffu, l1, 1);
      l0 += __shfl_xor_sync(0xffffffffu, l0, 2); l1 += __shfl_xor_sync(0xffffffffu, l1, 2);
      float f0 = rcp(l0), f1 = rcp(l1);
      asm volatile("" : "+f"(f0), "+f"(f1)::"memory");
      await(ST0);
      unpark(1, 4, 8);
      block_fence(61, zero);
#pragma unroll
      for (int k = 0; k < 8; k++) mma_n128_ss<1>(ar, mkdesc(slot, 16) + (k >> 2) * 512 + (k & 3) * 2, mkdesc(ring + (ST0 & 3) * STAGE, 16384) + k * 128, k > 0);
      wg_commit();
      bar_arrive(other_turn, 256);
      wg_wait<1>();
      pin(o); pin(pf);
      mbar_arrive_cluster_now<62>(empty_c + 8 * SL_KE, signaller, zero);
      c0 *= -f0;
      c1 *= -f1;
#pragma unroll
      for (int i = 0; i < 16; i++) {
        pf[2 * i] = pack2(fmaf(o[4 * i], f0, c0), fmaf(o[4 * i + 1], f0, c0));
        pf[2 * i + 1] = pack2(fmaf(o[4 * i + 2], f1, c1), fmaf(o[4 * i + 3], f1, c1));
      }
      pin(pf);
      prof(wg, 10);
#pragma unroll
      for (int u = 1; u < 4; u++) {
        await(ST0 + u);
        wg_wait<0>();
        release(ST0 + u - 1);
        bar_sync(my_turn, 256);
        wg_fence();
#pragma unroll
        for (int k = 0; k < 8; k++) {
          const uint32_t* a = (u == 1 ? oa + 32 : u == 2 ? pf : oa + 64) + 4 * k;
          mma_n128<1>(ar, a[0], a[1], a[2], a[3], mkdesc(ring + ((ST0 + u) & 3) * STAGE, 16384) + k * 128, 1);
        }
        wg_commit();
        bar_arrive(other_turn, 256);
        if (u < 3) {
          block_fence(62 + u, zero);
          unpark(u == 1 ? 2 : 0, 0, 8);
        }
      }
      mbar_wait(cx.sb + SM_BAR_MISC, 0);
      tag = *(const volatile uint32_t*)(cx.sp + SM_TAG);
      xch = at<uint4>(cx.gs->part, (qb << 20) + lane * 16 + zero);
      tag = __shfl_sync(0xffffffffu, tag, lane);
      await(ST0 + 4);
      wg_wait<0>();
      release(ST0 + 3);
      pin(ar);
#pragma unroll
      for (int i = 0; i < 32; i++) { first[i] = ar[i]; red[i] = ar[32 + i]; }
    }
    auto send = [&](const float (&v)[32], int dst, int idx) {
      uint4* p = at<uint4>(xch, (dst * 8 + idx) * 2048);
#pragma unroll
      for (int i = 0; i < 4; i++)
        st_gran(p + i * 32, (pack2(v[8 * i], v[8 * i + 1]) & ~TAG_BIT) | tag, pack2(v[8 * i + 2], v[8 * i + 3]),
                pack2(v[8 * i + 4], v[8 * i + 5]), pack2(v[8 * i + 6], v[8 * i + 7]));
    };
    send(first, ((hs + 1) & 7) * 7, cw);
    int nrx = 1;
    auto half_step = [&](int s, auto hc, bool arrive) {
      constexpr int h = decltype(hc)::value;
      const int st = ST0 + 2 * s + h;
      const uint64_t db = mkdesc(ring + (st & 3) * STAGE, 16);
      bar_sync(my_turn, 256);
      if (h == 0) pin(pf);
#pragma unroll
      for (int i = 32 * h; i < 32 + 64 * h; i++) asm volatile("" : "+r"(oa[i])::"memory");
      wg_fence();
#pragma unroll
      for (int k = 0; k < 16; k++) {
        const int kb = h * 16 + k - 8;
        if (kb >= 0) mma_n64<1>(acc, oa[4 * kb], oa[4 * kb + 1], oa[4 * kb + 2], oa[4 * kb + 3], db + k * 128, 1);
        else mma_n64<1>(acc, pf[4 * k], pf[4 * k + 1], pf[4 * k + 2], pf[4 * k + 3], db + k * 128, k > 0);
      }
      wg_commit();
      if (arrive) bar_arrive(other_turn, 256);
    };
    auto source = [&](int n) { return at<const uint4>(xch, ((hs * 7 + n - 1) * 8 + cw) * 2048); };
    auto fetch = [&](uint32_t (&g)[16], const uint4* p) {
#pragma unroll
      for (int i = 0; i < 4; i++) ld_gran(p + i * 32, g[4 * i], g[4 * i + 1], g[4 * i + 2], g[4 * i + 3]);
    };
    uint32_t g[16];
#pragma unroll 1
    for (int s = 2; s < 8; s++) {
      const int st = ST0 + 2 * s;
      half_step(s, IC<0>(), true);
      if (s == 2) {
        bar_arrive(BAR_OA, 352);
        send(red, 56 + cw, hs);
#pragma unroll
        for (int i = 0; i < 32; i++) red[i] = 0.f;
      }
      await(st + 1);
      if (s > 3 && granules_ok(g, tag)) { add_granules(red, g); nrx++; }
      wg_wait<0>();
      if (s < 7) release(st);
      if (s > 2) fetch(g, source(nrx));
      half_step(s, IC<1>(), true);
      await(st + 2);
      wg_wait<0>();
      if (s < 7) release(st + 1);
      pin(acc);
      if (s == 7) prof(wg, 19);
      send(acc, ((hs + s) & 7) * 7 + s - 1, cw);
    }
    TE(1)
    uint32_t xv[16], gt[16];
    {
      const int s = 8;
      uint32_t g2[16];
      half_step(s, IC<0>(), true);
      TE(2)
      await(NST_Q + NST_KV + NST_O - 1);
      cluster_arrive();
      mbar_wait(cx.sb + SM_BAR_XG, 0);
      const uint32_t tile = cx.sb + SM_XO + wg * 8192 + lo;
      if (granules_ok(g, tag)) { add_granules(red, g); nrx++; }
      fetch(g, source(nrx));
      block_fence(58, zero);
      wg_wait<0>();
      TE(3)
#pragma unroll
      for (int k = 0; k < 4; k++) ldsm4((tile ^ (k << 5)) + STAGE, gt[4 * k], gt[4 * k + 1], gt[4 * k + 2], gt[4 * k + 3]);
      half_step(s, IC<1>(), wg == 0);
      TE(4)
      block_fence(56, zero);
      const bool ok = granules_ok(g, tag);
      block_fence(57, zero + ok * 1000);
      const uint4* src = source(7);
      fetch(g2, src);
#pragma unroll
      for (int k = 0; k < 4; k++) ldsm4(tile ^ (k << 5), xv[4 * k], xv[4 * k + 1], xv[4 * k + 2], xv[4 * k + 3]);
      if (ok) { add_granules(red, g); nrx++; }
      TE(5)
      block_fence(59, zero);
      wg_wait<0>();
      pin(acc);
      TE(6)
#pragma unroll
      for (int i = 0; i < 32; i++) red[i] += acc[i];
      pin(red);
      TE(7)
      int n = 7;
#pragma unroll 1
      for (int spins = 0; spins < (1 << 16); spins++) {
        if (granules_ok(g2, tag)) {
          add_granules(red, g2);
          if (--n < nrx) {
            break;
          }
          src -= 1024;
        }
        fetch(g2, src);
      }
      TE(8)
    }
    prof(wg, 20);
    TE(9)
    const uint32_t ot = ring + ((ST0 + NST_O) & 3) * STAGE + cw * (16 * 144);
    uint32_t ow[16];
#pragma unroll
    for (int i = 0; i < 16; i++) ow[i] = fma2(pack2(red[2 * i], red[2 * i + 1]), gt[i], xv[i]);
#pragma unroll
    for (int i = 0; i < 4; i++)
      stsm4(ot + (lane & 15) * 144 + (2 * i + (lane >> 4)) * 16, ow[4 * i], ow[4 * i + 1], ow[4 * i + 2], ow[4 * i + 3]);
    __syncwarp();
#pragma unroll
    for (int i = 0; i < 4; i++) {
      uint4 v;
      lds128(ot + (i * 4 + (lane >> 3)) * 144 + (lane & 7) * 16, v.x, v.y, v.z, v.w);
      at<uint4>(out, ((qb * 128 + cw * 16 + (lane >> 3)) * DM + hs * 64 + (lane & 7) * 8) * 2)[i * (4 * DM / 8)] = v;
    }
    TE(10)
    prof(wg, 22);
  }
}

constexpr int AST_X = 6, AST_F = AST_X + 96;
__device__ __forceinline__ void aux_producer(const Ctx& cx, int f, const CUtensorMap* tmWq, const CUtensorMap* tmG) {
  const uint32_t full = cx.sb + SM_FULL, empty = cx.sb + SM_EMPTY;
  __nanosleep(3000);
  if (elect_one()) {
#pragma unroll 1
    for (int st = 0; st < AST_X; st++) {
      mbar_expect_tx(full + 8 * st, FSTAGE);
#pragma unroll
      for (int i = 0; i < 3; i++)
        tma2d_stream(cx.sb + st * FSTAGE + i * 8192, tmWq, (2 * f + (st & 1)) * 512 + 448, (st >> 1) * 192 + i * 64, full + 8 * st);
    }
  }
  __syncwarp();
  mbar_wait(cx.sb + SM_BAR_MISC, 0);
  proxy_fence();
  int st = AST_X;
#pragma unroll 1
  for (; st < AST_F; st++) {
    const uint32_t sl = st & 7;
    mbar_wait(empty + 8 * sl, ((st >> 3) & 1) ^ 1);
    if (elect_one()) {
      mbar_expect_tx(full + 8 * sl, FSTAGE);
      bulk_load(cx.sb + sl * FSTAGE, cx.gs->xn + (st - AST_X) * (FSTAGE / 16), FSTAGE, full + 8 * sl);
    }
    __syncwarp();
  }
#pragma unroll 1
  for (int pair = 0; pair < 14; pair++) {
#pragma unroll 1
    for (int u = 0; u < 12; u++, st++) {
      const uint32_t sl = st & 7;
      const int unit = pair * 2 + (u & 1), k = u >> 1;
      if (unit == 27) continue;
      const bool gu = pair < 9;
      mbar_wait(empty + 8 * sl, ((st >> 3) & 1) ^ 1);
      if (elect_one()) {
        mbar_expect_tx(full + 8 * sl, FSTAGE);
        tma2d_stream(cx.sb + sl * FSTAGE, tmG + (gu ? k >= 3 : 2), gu ? f * 1152 + unit * 64 : (unit - 18) * 64,
                     gu ? (k >= 3 ? k - 3 : k) * 192 : f * 1152 + k * 192, full + 8 * sl);
      }
      __syncwarp();
    }
  }
}

constexpr int BAR_FREE = 4, BAR_TILE = 6;
__device__ __forceinline__ void aux_helper(const Ctx& cx, int f, int warp, int lane) {
  unsigned epoch = 0;
  if (lane == 0) epoch = cx.gs->launch[blockIdx.x] + 1;
  epoch = __shfl_sync(0xffffffffu, epoch, 0);
  bar_sync(BAR_OA, 96);
  if (warp == 3) {
    if (lane == 0) cx.gs->launch[blockIdx.x] = epoch;
    await_count(at<const unsigned>(cx.gs->rows, (lane & 15) * 128), 8 * epoch, 200);
    if (lane == 0) mbar_arrive(cx.sb + SM_BAR_MISC);
    prof(0, 1, 31);
    await_count(at<const unsigned>(cx.gs->rows, (lane & 15) * 128 + 4), 8 * epoch, 500);
    proxy_fence();
    if (elect_one()) {
      mbar_expect_tx(cx.sb + SM_BAR_ROWS, SEQ * 4);
      bulk_load(cx.sb + SM_XSEL, cx.gs->key, SEQ * 4, cx.sb + SM_BAR_ROWS);
    }
    __syncwarp();
    mbar_wait(cx.sb + SM_BAR_ROWS, 0);
    uint32_t bound = 0xFFFFFFFFu, mine = 0;
#pragma unroll 1
    for (int k = 0; k < TOPC; k++) {
      uint32_t m = 0;
#pragma unroll 2
      for (int i = 0; i < 16; i++) {
        const uint4 v = *(const uint4*)(cx.sp + SM_XSEL + lane * 16 + i * 512);
        m = max(max(m, v.x <= bound ? v.x : 0), max(v.y <= bound ? v.y : 0, max(v.z <= bound ? v.z : 0, v.w <= bound ? v.w : 0)));
      }
      m = __reduce_max_sync(0xffffffffu, m);
      bound = m - 1;
      if (lane == k) mine = m;
    }
    if (f == 0 && lane < TOPC) *at<uint32_t>(cx.gs->top, lane * 4) = mine;
#pragma unroll 1
    for (int u = 0; u < 6; u++) {
      const int k = (u & 1) * 4 + (lane >> 3);
      const uint32_t row = 0xFFFF - (__shfl_sync(0xffffffffu, mine, k) & 0xFFFF);
#pragma unroll
      for (int j = 0; j < 3; j++)
        *(uint4*)(cx.sp + SM_XSEL + ((u >> 1) * 3 + j) * 1024 + k * 128 + (((lane ^ k) & 7) << 4)) =
            __ldcg(at<const uint4>(cx.gs->xn, xn_offset(row, (lane & 7) * 4) + (u >> 1) * (3 * 8192)) + j * 512);
    }
    asm volatile("fence.proxy.async.shared::cta;" ::: "memory");
    prof(0, 2, 31);
  } else {
    const int wg = warp - 1;
#pragma unroll 1
    for (int u = 0; u < 32; u++) {
      bar_arrive(BAR_FREE + wg, 160);
      bar_sync(BAR_TILE + wg, 160);
      if (elect_one()) {
        const int n = (u >> 1) * 8 + 2 * f + wg;
        asm volatile("cp.async.bulk.global.shared::cta.bulk_group [%0], [%1], 8192;\ncp.async.bulk.commit_group;\ncp.async.bulk.wait_group 0;"
                     ::"l"(cx.gs->q3 + (n * 2 + (u & 1)) * 512), "r"(cx.sb + SM_H + wg * 8192) : "memory");
        if (u & 1) st_release(&cx.gs->q3_flag[n], epoch);
      }
      __syncwarp();
    }
  }
  bar_arrive(3, 352);
}

__device__ __forceinline__ void aux_consumer(const Ctx& cx, int f, int wg, int cw, int lane) {
  const int r = lane >> 2, c = lane & 3, tid = cw * 32 + lane;
  const uint32_t full = cx.sb + SM_FULL, empty = cx.sb + SM_EMPTY;
  const bool signaller = (tid & 127) == 0;
  auto await = [&](int st) { mbar_wait(full + 8 * (st & 7), (st >> 3) & 1); };
  auto release = [&](int st, int cnt) {
    asm volatile("{\n.reg .pred p;\nsetp.ne.u32 p, %2, 0;\n@p mbarrier.arrive.shared::cta.b64 _, [%0], %1;\n}"
                 ::"r"(empty + 8 * (st & 7)), "r"(cnt), "r"((uint32_t)signaller) : "memory");
  };
  prof(wg, 0);
  {
    const uint32_t lt = ((lane & 7) + (lane >> 4) * 8) * 128 + ((((cw & 3) * 2 + ((lane >> 3) & 1)) ^ (lane & 7)) << 4);
    uint32_t wa[144];
#pragma unroll
    for (int i = 0; i < 3; i++) {
      await(2 * i + wg);
#pragma unroll
      for (int k = 0; k < 12; k++) {
        const int kb = 12 * i + k;
        ldsm4t(cx.sb + (2 * i + wg) * FSTAGE + k * 2048 + lt, wa[4 * kb], wa[4 * kb + 1], wa[4 * kb + 2], wa[4 * kb + 3]);
      }
    }
    bar_sync(1, 256);
#pragma unroll
    for (int i = 0; i < 3; i++) release(2 * i + wg, 2);
    if (wg) bar_arrive(1, 256);
#pragma unroll 1
    for (int st = AST_X; st < AST_F; st += 3) {
      float acc[32];
      await(st);
      await(st + 1);
      await(st + 2);
      bar_sync(1 + wg, 256);
      wg_fence();
#pragma unroll
      for (int kb = 0; kb < 36; kb++) {
        const int i = kb / 12, k = kb % 12;
        mma_n64<0>(acc, wa[4 * kb], wa[4 * kb + 1], wa[4 * kb + 2], wa[4 * kb + 3],
                   mkdesc(cx.sb + ((st + i) & 7) * FSTAGE, 16) + (k >> 2) * 512 + (k & 3) * 2, kb > 0);
        if (k == 11) wg_commit();
      }
      if (st < AST_F - 3 || !wg) bar_arrive(2 - wg, 256);
      wg_wait<1>();
      release(st, 1);
      release(st + 1, 1);
      bar_sync(BAR_FREE + wg, 160);
      wg_wait<0>();
      pin(acc);
      release(st + 2, 1);
#pragma unroll
      for (int k = 0; k < 4; k++)
        stsm4t(cx.sb + SM_H + wg * 8192 + k * 2048 + lt, pack2(acc[8 * k] * SM_SCALE_LOG2, acc[8 * k + 1] * SM_SCALE_LOG2),
               pack2(acc[8 * k + 2] * SM_SCALE_LOG2, acc[8 * k + 3] * SM_SCALE_LOG2),
               pack2(acc[8 * k + 4] * SM_SCALE_LOG2, acc[8 * k + 5] * SM_SCALE_LOG2),
               pack2(acc[8 * k + 6] * SM_SCALE_LOG2, acc[8 * k + 7] * SM_SCALE_LOG2));
      asm volatile("fence.proxy.async.shared::cta;" ::: "memory");
      bar_arrive(BAR_TILE + wg, 160);
    }
    bar_sync(3, 352);
  }
  prof(wg, 3);
#pragma unroll 1
  for (int unit = wg; unit < 27; unit += 2) {
    if (unit >> 1 == 9) {
      asm volatile("fence.proxy.async.shared::cta;" ::: "memory");
      bar_sync(3, 256);
      prof(wg, 4);
    }
    const bool gu = unit < 18;
    float a0[4], a1[4];
#pragma unroll 1
    for (int m = 0; m < 2; m++) {
      float p0[4], p1[4];
      int st = AST_F + (unit >> 1) * 12 + m * 6 + wg;
      uint32_t b = cx.sb + (gu ? SM_XSEL : SM_H + m * 9216);
#pragma unroll 1
      for (int u = 0; u < 3; u++, st += 2, b += 3072) {
        await(st);
        wg_fence();
        const uint64_t da = mkdesc(cx.sb + (st & 7) * FSTAGE, 16), db = mkdesc(b, 16);
#pragma unroll
        for (int k = 0; k < 12; k++) mma_n8((k & 1) ? p1 : p0, da + k * 128, db + (k >> 2) * 64 + (k & 3) * 2, u > 0 || k > 1);
        wg_commit();
        wg_wait<0>();
        release(st, 2);
      }
      pin(p0); pin(p1);
#pragma unroll
      for (int i = 0; i < 4; i++) { a0[i] = a1[i]; a1[i] = p0[i] + p1[i]; }
    }
#pragma unroll
    for (int i = 0; i < 4; i++) {
      const int fl = (cw & 3) * 16 + r + (i >> 1) * 8, tok = 2 * c + (i & 1);
      if (gu) {
        const float h = bfr(silu_f(bfr(a0[i]))) * bfr(a1[i]);
        *(__nv_bfloat16*)(cx.sp + SM_H + unit * 1024 + tok * 128 + (((fl >> 3) ^ tok) << 4) + (fl & 7) * 2) = __float2bfloat16_rn(h);
      } else {
        *at<float>(cx.gs->ypart, ((f * TOPC + tok) * DM + (unit - 18) * 64 + fl) * 4) = a0[i] + a1[i];
      }
    }
  }
  prof(wg, 5);
  bar_sync(3, 256);
  if (tid == 0) red_release(&cx.gs->ycnt);
  prof(wg, 6);
}

struct Maps { CUtensorMap m[9]; };
__global__ void __cluster_dims__(2, 1, 1) __launch_bounds__(THREADS, 1)
fused_kernel(const __nv_bfloat16* __restrict__ x, const __nv_bfloat16* __restrict__ w_r, const __nv_bfloat16* __restrict__ kc,
             const __nv_bfloat16* __restrict__ wo, __nv_bfloat16* __restrict__ out, Scratch* gs,
             const __grid_constant__ Maps maps) {
  const CUtensorMap &tmX = maps.m[0], &tmWq = maps.m[1], &tmK = maps.m[2], &tmV = maps.m[3], &tmWo = maps.m[4];
  extern __shared__ __align__(1024) uint8_t smem_raw[];
  prof(0, 23, 511);
  if (threadIdx.x < 72 && blockIdx.x < N_ATT_CTA)
    asm volatile("prefetch.global.L2 [%0];" ::"l"(at<const void>(x, ((blockIdx.x >> 3) * 128 + (blockIdx.x & 7) * 8) * (DM * 2) + threadIdx.x * 128)));
  Ctx cx;
  cx.sb = smem_u32(smem_raw);
  cx.sp = smem_raw;
  cx.gs = gs;
  cx.rank = blockIdx.x & 1;
  const int warp = __shfl_sync(0xffffffffu, threadIdx.x >> 5, 0);
  const int cluster = blockIdx.x >> 1;
  const bool is_aux = blockIdx.x >= N_ATT_CTA;
  const int c7 = ((cluster - 36) * 37) >> 8;
  const int hs = cluster < 4 ? 4 + cluster : cluster < 36 ? (cluster - 4) >> 3 : 4 + c7;
  const int qb = (cluster < 4 ? 0 : cluster < 36 ? (cluster - 4) & 7 : cluster - 35 - 7 * c7) * 2 + cx.rank;

  extern __shared__ __align__(1024) uint8_t smem_alias[];
  const uint32_t xf = smem_u32(smem_alias) + SM_MISC + warp * 24;
  if (warp == 4 && elect_one()) prefetch_tmap(&tmX);
  if (elect_one()) {
    const uint32_t cnt = (warp > 4 && warp < 8) ? (is_aux ? 2 : 4) : 1;
#pragma unroll
    for (int i = 0; i < 3; i++) mbar_init(xf + 8 * i, cnt);
    asm volatile("fence.proxy.async.shared::cta;" ::: "memory");
    asm volatile("fence.mbarrier_init.release.cluster;" ::: "memory");
  }
  __syncwarp();
  cluster_arrive();
  if (warp == 4 && !is_aux) {
    if (elect_one()) {
#pragma unroll
      for (int i = 0; i < 3; i++) {
        mbar_expect_tx(xf + 8 * i, 24576);
        tma3d(xf - SM_XFULL + SM_X + i * 24576, &tmX, qb * 128, i * 3, xf + 8 * i);
      }
    }
  } else if (warp > 7 && elect_one()) {
    prefetch_tmap(&tmX + (is_aux ? warp - 4 : warp == 8 ? 8 : warp - 8));
  }
  __syncwarp();

  if (warp < 4) {
    asm volatile("setmaxnreg.dec.sync.aligned.u32 24;");
    cluster_wait();
    prof(0, 24, 511);
    if (warp == 0) {
      if (!is_aux) attn_producer(cx, qb, hs, &tmX, &tmK, &tmV, &tmWq, &tmWo);
      else aux_producer(cx, blockIdx.x - N_ATT_CTA, &tmWq, &maps.m[5]);
      prof(0, 25, 511);
    } else if (!is_aux) {
      attn_rows(cx, qb, hs, 3 - warp, read_lane(), &maps.m[8], w_r);
      if (warp == 1) attn_helper(cx, qb, hs, read_lane(), wo, &maps.m[8]);
      else bar_sync(BAR_OA, 352);
      attn_finish8(cx, qb, hs, warp - 1, read_lane(), out);
    } else {
      aux_helper(cx, blockIdx.x - N_ATT_CTA, warp, read_lane());
    }
    __syncwarp();
    cluster_arrive();
    cluster_wait();
    if (threadIdx.x == 32) { dly(cx, 201); dly(cx, 251); }
  } else {
    asm volatile("setmaxnreg.inc.sync.aligned.u32 240;");
    cluster_wait();
    const int cw = warp - 4, wg = cw >> 2;
    if (is_aux) aux_consumer(cx, blockIdx.x - N_ATT_CTA, wg, cw, read_lane());
    else attn_consumer(cx, qb, hs, wg, cw, read_lane(), x, kc, out);
  }
}

typedef CUresult (*EncodeFn)(CUtensorMap*, CUtensorMapDataType, cuuint32_t, void*, const cuuint64_t*, const cuuint64_t*,
                             const cuuint32_t*, const cuuint32_t*, CUtensorMapInterleave, CUtensorMapSwizzle,
                             CUtensorMapL2promotion, CUtensorMapFloatOOBfill);

void encode(EncodeFn fn, CUtensorMap* m, const void* p, int rank, const cuuint64_t* dims, const cuuint64_t* strides,
            const cuuint32_t* box) {
  const cuuint32_t es[5] = {1, 1, 1, 1, 1};
  fn(m, CU_TENSOR_MAP_DATA_TYPE_BFLOAT16, rank, const_cast<void*>(p), dims, strides, box, es, CU_TENSOR_MAP_INTERLEAVE_NONE,
     CU_TENSOR_MAP_SWIZZLE_128B, CU_TENSOR_MAP_L2_PROMOTION_L2_128B, CU_TENSOR_MAP_FLOAT_OOB_FILL_NONE);
}
void encode2d(EncodeFn fn, CUtensorMap* m, const void* p, uint64_t rows, uint64_t cols, uint32_t box_rows) {
  const cuuint64_t dims[2] = {cols, rows}, strides[1] = {cols * 2};
  const cuuint32_t box[2] = {64, box_rows};
  encode(fn, m, p, 2, dims, strides, box);
}

}

extern "C" void kernel_launch(void* const* d_in, const int* in_sizes, int n_in, void* d_out, int out_size) {
  (void)in_sizes; (void)n_in; (void)out_size;
  void* fnp = nullptr;
  cudaDriverEntryPointQueryResult qr;
  cudaGetDriverEntryPoint("cuTensorMapEncodeTiled", &fnp, cudaEnableDefault, &qr);
  EncodeFn fn = (EncodeFn)fnp;
  void* gs = nullptr;
  cudaGetSymbolAddress(&gs, g_scratch);
  Maps maps;
  CUtensorMap &tmX = maps.m[0], &tmWq = maps.m[1], &tmK = maps.m[2], &tmV = maps.m[3], &tmWo = maps.m[4], &tmG = maps.m[5],
              &tmU = maps.m[6], &tmD = maps.m[7];
  encode2d(fn, &tmK, d_in[1], 16 * SEQ, DH, 128);
  encode2d(fn, &tmV, d_in[2], 16 * SEQ, DH, 128);
  encode2d(fn, &tmWq, d_in[3], DM, 4096, 64);
  {
    const cuuint64_t dims[3] = {64, SEQ, 9}, strides[2] = {DM * 2, 128};
    const cuuint32_t box[3] = {64, 64, 3};
    encode(fn, &tmX, d_in[0], 3, dims, strides, box);
  }
  encode2d(fn, &maps.m[8], d_in[0], SEQ, DM, 16);
  encode2d(fn, &tmWo, d_in[4], 4096, DM, 128);
  encode2d(fn, &tmG, d_in[7], DM, FF, 192);
  encode2d(fn, &tmU, d_in[8], DM, FF, 192);
  encode2d(fn, &tmD, d_in[9], FF, DM, 192);
  cudaFuncSetAttribute(fused_kernel, cudaFuncAttributeMaxDynamicSharedMemorySize, SM_TOTAL);
  fused_kernel<<<N_CTA, THREADS, SM_TOTAL>>>((const __nv_bfloat16*)d_in[0], (const __nv_bfloat16*)d_in[6], (const __nv_bfloat16*)d_in[1],
                                            (const __nv_bfloat16*)d_in[4], (__nv_bfloat16*)d_out, (Scratch*)gs, maps);
}
```

```cpp
#include <cuda_runtime.h>
#include <cuda_bf16.h>
#include <cuda.h>
#include <stdint.h>

namespace {

constexpr int SEQ = 2048, DM = 576, DH = 128, FF = 4608, TOPC = 8;
constexpr int N_ATT_CTA = 128, N_CTA = 132;
constexpr int THREADS = 384;

constexpr uint32_t SM_RING = 0;
constexpr uint32_t STAGE = 32768;
constexpr uint32_t SM_SLOT = 131072;
constexpr uint32_t FSTAGE = 24576;
constexpr uint32_t SM_XSEL = 196608;
constexpr uint32_t SM_H = 205824;
constexpr uint32_t SM_MISC = 229376;
constexpr uint32_t SM_FULL = SM_MISC, SM_BAR_MISC = SM_MISC + 64, SM_BAR_XG = SM_MISC + 72, SM_BAR_P8 = SM_MISC + 80, SM_BAR_Q3 = SM_MISC + 88, SM_XFULL = SM_MISC + 96,
                   SM_EMPTY = SM_MISC + 120, SM_BAR_ROWS = SM_MISC + 216, SM_TAG = SM_MISC + 288,
                   SM_ROWS = SM_MISC + 304, SM_BOX8 = SM_MISC + 1024;
constexpr uint32_t SM_TOTAL = SM_MISC + 3072;
constexpr uint32_t SM_X = SM_MISC - 147456;

constexpr int BAR_ROWS = 6, BAR_HELPER = 7, BAR_OA = 8;
constexpr int NST_Q = 18, NST_KV = 128, NST_O = 18;
constexpr uint32_t SL_KE = (NST_Q - 1) & 3, SL_VE = NST_Q & 3, SL_KO = (NST_Q + 1) & 3, SL_VO = (NST_Q + 2) & 3;
#define X_N1 6
#define X_SPLIT 44
#define X_SPLIT3 36
#define X_PARK 5
#define X_C0 24
#define X_C1 32
#define X_C2 56
constexpr float SM_SCALE_LOG2 = 0.08838834764831845f * 1.4426950408889634f;

struct Scratch {
  uint4 part[16 * 64 * 2 * 4 * 128];
  uint4 gate[N_ATT_CTA * 144 * 8];
  uint4 q3[N_ATT_CTA * 1024];
  uint4 xn[SEQ * DM / 8];
  uint32_t key[SEQ];
  float ypart[4 * TOPC * DM];
  uint32_t top[32];
  unsigned launch[160];
  unsigned rows[16 * 32];
  unsigned q3_flag[N_ATT_CTA];
  unsigned ycnt;
};
__device__ __align__(1024) Scratch g_scratch;

__device__ __forceinline__ void prof(int, int, int = 0) {}

__device__ __forceinline__ uint32_t smem_u32(const void* p) { return (uint32_t)__cvta_generic_to_shared(p); }
__device__ __forceinline__ void mbar_init(uint32_t bar, uint32_t cnt) {
  asm volatile("mbarrier.init.shared::cta.b64 [%0], %1;" ::"r"(bar), "r"(cnt) : "memory");
}
__device__ __forceinline__ void mbar_expect_tx(uint32_t bar, uint32_t bytes) {
  asm volatile("mbarrier.arrive.expect_tx.shared::cta.b64 _, [%0], %1;" ::"r"(bar), "r"(bytes) : "memory");
}
__device__ __forceinline__ void mbar_arrive(uint32_t bar) {
  asm volatile("mbarrier.arrive.shared::cta.b64 _, [%0];" ::"r"(bar) : "memory");
}
__device__ __forceinline__ void mbar_arrive_cluster(uint32_t bar_cluster_addr) {
  asm volatile("mbarrier.arrive.shared::cluster.b64 _, [%0];" ::"r"(bar_cluster_addr) : "memory");
}
template <int ID>
__device__ __forceinline__ void mbar_arrive_cluster_now(uint32_t bar_cluster_addr, bool pred, uint32_t zero) {
  asm volatile("{\n.reg .pred p, q;\nsetp.ne.u32 p, %1, 0;\nsetp.eq.u32 q, %2, %3;\n"
               "ARR_LOOP:\n@p mbarrier.arrive.shared::cluster.b64 _, [%0];\n@q bra.uni ARR_LOOP;\n}"
               ::"r"(bar_cluster_addr), "r"((uint32_t)pred), "r"(zero), "n"(ID) : "memory");
}
__device__ __forceinline__ void block_fence(int id, uint32_t zero = blockIdx.y) {
  asm volatile("{\n.reg .pred q;\nsetp.eq.u32 q, %0, %1;\nBF_LOOP:\n@q st.volatile.shared.u32 [%0], %0;\n@q bra.uni BF_LOOP;\n}"
               ::"r"(zero), "r"(id) : "memory");
}
__device__ __forceinline__ bool mbar_test(uint32_t bar, uint32_t parity) {
  uint32_t ok;
  asm volatile("{\n.reg .pred p;\nmbarrier.test_wait.parity.shared::cta.b64 p, [%1], %2;\nselp.u32 %0, 1, 0, p;\n}"
               : "=r"(ok) : "r"(bar), "r"(parity) : "memory");
  return ok;
}
__device__ __forceinline__ void mbar_wait(uint32_t bar, uint32_t parity) {
  asm volatile("{\n.reg .pred p, q;\n.reg .u32 n;\nmov.u32 n, 0;\n"
               "WAIT_LOOP:\nmbarrier.try_wait.parity.shared::cta.b64 p, [%0], %1;\n"
               "add.u32 n, n, 1;\nsetp.lt.u32 q, n, 4194304;\nand.pred q, q, !p;\n@q bra WAIT_LOOP;\n}"
               ::"r"(bar), "r"(parity) : "memory");
}
__device__ __forceinline__ uint32_t mapa(uint32_t addr, uint32_t rank) {
  uint32_t r;
  asm volatile("mapa.shared::cluster.u32 %0, %1, %2;" : "=r"(r) : "r"(addr), "r"(rank));
  return r;
}
__device__ __forceinline__ void cluster_arrive() { asm volatile("barrier.cluster.arrive.relaxed.aligned;" ::: "memory"); }
__device__ __forceinline__ bool elect_one() {
  uint32_t p;
  asm volatile("{\n.reg .pred p;\nelect.sync _|p, 0xffffffff;\nselp.u32 %0, 1, 0, p;\n}" : "=r"(p));
  return p;
}
__device__ __forceinline__ int read_lane() { return threadIdx.x & 31; }
__device__ __forceinline__ void cluster_wait() { asm volatile("barrier.cluster.wait.acquire.aligned;" ::: "memory"); }
__device__ __forceinline__ void bar_sync(int id, int n) { asm volatile("barrier.cta.sync %0, %1;" ::"r"(id), "r"(n) : "memory"); }
__device__ __forceinline__ void bar_arrive(int id, int n) { asm volatile("barrier.cta.arrive %0, %1;" ::"r"(id), "r"(n) : "memory"); }

__device__ __forceinline__ uint64_t policy_evict_first() {
  uint64_t p;
  asm("createpolicy.fractional.L2::evict_first.b64 %0, 1.0;" : "=l"(p));
  return p;
}
__device__ __forceinline__ uint64_t policy_evict_normal() {
  uint64_t p;
  asm("createpolicy.fractional.L2::evict_normal.b64 %0, 1.0;" : "=l"(p));
  return p;
}
__device__ __forceinline__ void tma3d(uint32_t dst, const CUtensorMap* tm, int c1, int c2, uint32_t bar) {
  asm volatile("cp.async.bulk.tensor.3d.shared::cluster.global.mbarrier::complete_tx::bytes [%0], [%1, {%2, %3, %4}], [%5];"
               ::"r"(dst), "l"(tm), "r"(0), "r"(c1), "r"(c2), "r"(bar) : "memory");
}
__device__ __forceinline__ void tma2d(uint32_t dst, const CUtensorMap* tm, int c0, int c1, uint32_t bar) {
  asm volatile("cp.async.bulk.tensor.2d.shared::cluster.global.mbarrier::complete_tx::bytes [%0], [%1, {%2, %3}], [%4];"
               ::"r"(dst), "l"(tm), "r"(c0), "r"(c1), "r"(bar) : "memory");
}
__device__ __forceinline__ void tma2d_stream(uint32_t dst, const CUtensorMap* tm, int c0, int c1, uint32_t bar) {
  asm volatile("{\n.reg .b64 pol;\ncreatepolicy.fractional.L2::evict_first.b64 pol, 1.0;\n"
               "cp.async.bulk.tensor.2d.shared::cluster.global.mbarrier::complete_tx::bytes.L2::cache_hint [%0], [%1, {%2, %3}], [%4], pol;\n}"
               ::"r"(dst), "l"(tm), "r"(c0), "r"(c1), "r"(bar) : "memory");
}
__device__ __forceinline__ void tma2d_prefetch(const CUtensorMap* tm, int c0, int c1) {
  asm volatile("cp.async.bulk.prefetch.tensor.2d.L2.global [%0, {%1, %2}];" ::"l"(tm), "r"(c0), "r"(c1) : "memory");
}
__device__ __forceinline__ void prefetch_l2(const void* p, uint32_t bytes) {
  asm volatile("cp.async.bulk.prefetch.L2.global [%0], %1;" ::"l"(p), "r"(bytes) : "memory");
}
__device__ __forceinline__ void prefetch_tmap(const CUtensorMap* tm) {
  asm volatile("prefetch.tensormap [%0];" ::"l"(tm) : "memory");
}

__device__ __forceinline__ void wg_fence() { asm volatile("wgmma.fence.sync.aligned;" ::: "memory"); }
__device__ __forceinline__ void wg_commit() { asm volatile("wgmma.commit_group.sync.aligned;" ::: "memory"); }
template <int N> __device__ __forceinline__ void wg_wait() { asm volatile("wgmma.wait_group.sync.aligned %0;" ::"n"(N) : "memory"); }

__device__ __forceinline__ uint64_t mkdesc(uint32_t addr, uint32_t lbo_bytes) {
  return (uint64_t)(((addr & 0x3FFFF) >> 4) | ((lbo_bytes >> 4) << 16)) | ((uint64_t)0x40000040u << 32);
}
template <int N> __device__ __forceinline__ void pin(float (&a)[N]) {
#pragma unroll
  for (int i = 0; i < N; i++) asm volatile("" : "+f"(a[i])::"memory");
}
template <int N> __device__ __forceinline__ void pin(uint32_t (&a)[N]) {
#pragma unroll
  for (int i = 0; i < N; i++) asm volatile("" : "+r"(a[i])::"memory");
}

#define F8(d, o) "+f"(d[o]), "+f"(d[o + 1]), "+f"(d[o + 2]), "+f"(d[o + 3]), "+f"(d[o + 4]), "+f"(d[o + 5]), "+f"(d[o + 6]), "+f"(d[o + 7])
#define R32A "%0, %1, %2, %3, %4, %5, %6, %7, %8, %9, %10, %11, %12, %13, %14, %15, %16, %17, %18, %19, %20, %21, %22, %23, %24, %25, %26, %27, %28, %29, %30, %31"
#define R32B "%32, %33, %34, %35, %36, %37, %38, %39, %40, %41, %42, %43, %44, %45, %46, %47, %48, %49, %50, %51, %52, %53, %54, %55, %56, %57, %58, %59, %60, %61, %62, %63"

template <int TB>
__device__ __forceinline__ void mma_n128(float (&d)[64], uint32_t a0, uint32_t a1, uint32_t a2, uint32_t a3, uint64_t db, int acc) {
  asm volatile("{\n.reg .pred p;\nsetp.ne.b32 p, %69, 0;\n"
               "wgmma.mma_async.sync.aligned.m64n128k16.f32.bf16.bf16 {" R32A ", " R32B "}, {%64, %65, %66, %67}, %68, p, 1, 1, %70;\n}\n"
               : F8(d, 0), F8(d, 8), F8(d, 16), F8(d, 24), F8(d, 32), F8(d, 40), F8(d, 48), F8(d, 56)
               : "r"(a0), "r"(a1), "r"(a2), "r"(a3), "l"(db), "r"(acc), "n"(TB));
}
template <int TB>
__device__ __forceinline__ void mma_n128_ss(float (&d)[64], uint64_t da, uint64_t db, int acc) {
  asm volatile("{\n.reg .pred p;\nsetp.ne.b32 p, %66, 0;\n"
               "wgmma.mma_async.sync.aligned.m64n128k16.f32.bf16.bf16 {" R32A ", " R32B "}, %64, %65, p, 1, 1, 0, %67;\n}\n"
               : F8(d, 0), F8(d, 8), F8(d, 16), F8(d, 24), F8(d, 32), F8(d, 40), F8(d, 48), F8(d, 56)
               : "l"(da), "l"(db), "r"(acc), "n"(TB));
}
template <int TB>
__device__ __forceinline__ void mma_n64(float (&d)[32], uint32_t a0, uint32_t a1, uint32_t a2, uint32_t a3, uint64_t db, int acc) {
  asm volatile("{\n.reg .pred p;\nsetp.ne.b32 p, %37, 0;\n"
               "wgmma.mma_async.sync.aligned.m64n64k16.f32.bf16.bf16 {" R32A "}, {%32, %33, %34, %35}, %36, p, 1, 1, %38;\n}\n"
               : F8(d, 0), F8(d, 8), F8(d, 16), F8(d, 24)
               : "r"(a0), "r"(a1), "r"(a2), "r"(a3), "l"(db), "r"(acc), "n"(TB));
}
__device__ __forceinline__ void mma_n8(float (&d)[4], uint64_t da, uint64_t db, int acc) {
  asm volatile("{\n.reg .pred p;\nsetp.ne.b32 p, %6, 0;\n"
               "wgmma.mma_async.sync.aligned.m64n8k16.f32.bf16.bf16 {%0, %1, %2, %3}, %4, %5, p, 1, 1, 1, 0;\n}\n"
               : "+f"(d[0]), "+f"(d[1]), "+f"(d[2]), "+f"(d[3])
               : "l"(da), "l"(db), "r"(acc));
}
__device__ __forceinline__ void hmma_k16(float (&d)[4], uint32_t a0, uint32_t a1, uint32_t a2, uint32_t a3, uint32_t b0, uint32_t b1) {
  asm volatile("mma.sync.aligned.m16n8k16.row.col.f32.bf16.bf16.f32 {%0, %1, %2, %3}, {%4, %5, %6, %7}, {%8, %9}, {%0, %1, %2, %3};"
               : "+f"(d[0]), "+f"(d[1]), "+f"(d[2]), "+f"(d[3]) : "r"(a0), "r"(a1), "r"(a2), "r"(a3), "r"(b0), "r"(b1));
}

__device__ __forceinline__ uint32_t pack2(float lo, float hi) {
  uint32_t r;
  asm("cvt.rn.bf16x2.f32 %0, %1, %2;" : "=r"(r) : "f"(hi), "f"(lo));
  return r;
}
__device__ __forceinline__ float bf_lo(uint32_t w) { return __uint_as_float(w << 16); }
__device__ __forceinline__ float bf_hi(uint32_t w) { return __uint_as_float(w & 0xFFFF0000u); }
__device__ __forceinline__ float bfr(float x) { return __uint_as_float(pack2(0.f, x)); }
__device__ __forceinline__ uint32_t sub2(uint32_t a, uint32_t b) {
  uint32_t r;
  asm("sub.rn.bf16x2 %0, %1, %2;" : "=r"(r) : "r"(a), "r"(b));
  return r;
}
__device__ __forceinline__ uint32_t add2(uint32_t a, uint32_t b) {
  uint32_t r;
  asm("add.rn.bf16x2 %0, %1, %2;" : "=r"(r) : "r"(a), "r"(b));
  return r;
}
__device__ __forceinline__ uint32_t mul2(uint32_t a, uint32_t b) {
  uint32_t r;
  asm("mul.rn.bf16x2 %0, %1, %2;" : "=r"(r) : "r"(a), "r"(b));
  return r;
}
__device__ __forceinline__ uint32_t fma2(uint32_t a, uint32_t b, uint32_t c) {
  uint32_t r;
  asm("fma.rn.bf16x2 %0, %1, %2, %3;" : "=r"(r) : "r"(a), "r"(b), "r"(c));
  return r;
}
__device__ __forceinline__ float ex2(float x) {
  float r;
  asm("ex2.approx.ftz.f32 %0, %1;" : "=f"(r) : "f"(x));
  return r;
}
__device__ __forceinline__ float rcp(float x) {
  float r;
  asm("rcp.approx.ftz.f32 %0, %1;" : "=f"(r) : "f"(x));
  return r;
}
__device__ __forceinline__ float silu_f(float t) { return t * rcp(1.0f + ex2(-1.4426950408889634f * t)); }
__device__ __forceinline__ void lds128(uint32_t a, uint32_t& x, uint32_t& y, uint32_t& z, uint32_t& w) {
  asm volatile("ld.shared.v4.u32 {%0, %1, %2, %3}, [%4];" : "=r"(x), "=r"(y), "=r"(z), "=r"(w) : "r"(a) : "memory");
}
__device__ __forceinline__ void ldsm4(uint32_t a, uint32_t& x, uint32_t& y, uint32_t& z, uint32_t& w) {
  asm volatile("ldmatrix.sync.aligned.m8n8.x4.shared.b16 {%0, %1, %2, %3}, [%4];" : "=r"(x), "=r"(y), "=r"(z), "=r"(w) : "r"(a) : "memory");
}
constexpr uint32_t TAG_BIT = 0x10000;
__device__ __forceinline__ void st_gran(uint4* p, uint32_t x, uint32_t y, uint32_t z, uint32_t w) {
  asm volatile("st.relaxed.gpu.global.v4.b32 [%0], {%1, %2, %3, %4};" ::"l"(p), "r"(x), "r"(y), "r"(z), "r"(w) : "memory");
}
__device__ __forceinline__ void ld_gran(const uint4* p, uint32_t& x, uint32_t& y, uint32_t& z, uint32_t& w) {
  asm volatile("ld.relaxed.gpu.global.v4.b32 {%0, %1, %2, %3}, [%4];" : "=r"(x), "=r"(y), "=r"(z), "=r"(w) : "l"(p) : "memory");
}
__device__ __forceinline__ void ldsm4t(uint32_t a, uint32_t& x, uint32_t& y, uint32_t& z, uint32_t& w) {
  asm volatile("ldmatrix.sync.aligned.m8n8.x4.trans.shared.b16 {%0, %1, %2, %3}, [%4];" : "=r"(x), "=r"(y), "=r"(z), "=r"(w) : "r"(a) : "memory");
}
__device__ __forceinline__ void stsm4t(uint32_t a, uint32_t x, uint32_t y, uint32_t z, uint32_t w) {
  asm volatile("stmatrix.sync.aligned.m8n8.x4.trans.shared.b16 [%0], {%1, %2, %3, %4};" ::"r"(a), "r"(x), "r"(y), "r"(z), "r"(w) : "memory");
}
__device__ __forceinline__ void stsm4(uint32_t a, uint32_t x, uint32_t y, uint32_t z, uint32_t w) {
  asm volatile("stmatrix.sync.aligned.m8n8.x4.shared.b16 [%0], {%1, %2, %3, %4};" ::"r"(a), "r"(x), "r"(y), "r"(z), "r"(w) : "memory");
}
template <class T>
__device__ __forceinline__ T* at(const void* base, uint32_t off) {
  uint64_t r;
  asm("{\n.reg .u32 lo, hi;\nmov.b64 {lo, hi}, %1;\nadd.cc.u32 lo, lo, %2;\naddc.u32 hi, hi, 0;\nmov.b64 %0, {lo, hi};\n}"
      : "=l"(r) : "l"(base), "r"(off));
  return (T*)__cvta_global_to_generic(r);
}
__device__ __forceinline__ void add_granules(float (&red)[32], const uint32_t (&g)[16]) {
#pragma unroll
  for (int i = 0; i < 16; i++) { red[2 * i] += bf_lo(g[i]); red[2 * i + 1] += bf_hi((i & 3) ? g[i] : g[i] & ~TAG_BIT); }
}
__device__ __forceinline__ bool granules_ok(const uint32_t (&g)[16], uint32_t tag) {
  uint32_t u, v;
  asm("lop3.b32 %0, %1, %2, %3, 0x7E;" : "=r"(u) : "r"(g[0]), "r"(g[4]), "r"(tag));
  asm("lop3.b32 %0, %1, %2, %3, 0x7E;" : "=r"(v) : "r"(g[8]), "r"(g[12]), "r"(tag));
  return __all_sync(0xffffffffu, ((u | v) & TAG_BIT) == 0);
}
__device__ __forceinline__ unsigned ld_acquire(const unsigned* p) {
  unsigned v;
  asm volatile("ld.acquire.gpu.global.u32 %0, [%1];" : "=r"(v) : "l"(p) : "memory");
  return v;
}
__device__ __forceinline__ void red_release(unsigned* p) {
  asm volatile("red.release.gpu.global.add.u32 [%0], 1;" ::"l"(p) : "memory");
}
__device__ __forceinline__ void st_release(unsigned* p, unsigned v) {
  asm volatile("st.release.gpu.global.u32 [%0], %1;" ::"l"(p), "r"(v) : "memory");
}

template <int K0, int K1>
__device__ __forceinline__ void ln_fetch(uint32_t (&xa)[144], uint32_t boxes, uint32_t lo) {
#pragma unroll
  for (int k = K0; k < K1; k++) ldsm4(((boxes + lo) ^ ((k & 3) << 5)) + (k >> 2) * 8192, xa[4 * k], xa[4 * k + 1], xa[4 * k + 2], xa[4 * k + 3]);
}
template <int K0, int K1>
__device__ __forceinline__ void ln_sums(const uint32_t (&xa)[144], float (&sm)[4][4]) {
#pragma unroll
  for (int k = K0; k < K1; k++) hmma_k16(sm[k & 3], xa[4 * k], xa[4 * k + 1], xa[4 * k + 2], xa[4 * k + 3], 0x3F803F80u, 0x3F803F80u);
}
__device__ __forceinline__ uint32_t sq8(const uint32_t* a) {
  uint32_t t, u;
  asm("mul.rn.bf16x2 %0, %1, %1;" : "=r"(t) : "r"(a[0]));
  asm("mul.rn.bf16x2 %0, %1, %1;" : "=r"(u) : "r"(a[2]));
#pragma unroll
  for (int i = 4; i < 16; i += 4) {
    asm("fma.rn.bf16x2 %0, %1, %1, %0;" : "+r"(t) : "r"(a[i]));
    asm("fma.rn.bf16x2 %0, %1, %1, %0;" : "+r"(u) : "r"(a[i + 2]));
  }
  return add2(t, u);
}
__device__ __forceinline__ void ln_centre(uint32_t (&xa)[144], int j0, int j1, uint32_t mm0, uint32_t mm1, float& sq0, float& sq1) {
#pragma unroll
  for (int j = 0; j < 72; j += 8)
    if (j >= j0 && j < j1) {
#pragma unroll
      for (int k = j; k < j + 8; k++) {
        xa[2 * k] = sub2(xa[2 * k], mm0);
        xa[2 * k + 1] = sub2(xa[2 * k + 1], mm1);
      }
      const uint32_t t0 = sq8(xa + 2 * j), t1 = sq8(xa + 2 * j + 1);
      sq0 += bf_lo(t0) + bf_hi(t0);
      sq1 += bf_lo(t1) + bf_hi(t1);
    }
}
__device__ __forceinline__ float ln_rstd(float var) {
  float sd;
  asm("sqrt.approx.ftz.f32 %0, %1;" : "=f"(sd) : "f"(bfr(bfr(fmaxf(var, 0.0f)) + 1e-5f)));
  return rcp(bfr(sd));
}
__device__ __forceinline__ uint32_t silu2(uint32_t t) { return pack2(silu_f(bf_lo(t)), silu_f(bf_hi(t))); }
__device__ __forceinline__ float sum8(float v) {
#pragma unroll
  for (int d = 4; d; d >>= 1) v += __shfl_xor_sync(0xffffffffu, v, d);
  return v;
}
__device__ __forceinline__ void await_count(const unsigned* p, unsigned target, unsigned sleep_ns) {
#pragma unroll 1
  for (int n = 0; n < (1 << 18) && __any_sync(0xffffffffu, (int)(ld_acquire(p) - target) < 0); n++) __nanosleep(sleep_ns);
}
__device__ __forceinline__ void bulk_load(uint32_t dst, const void* src, uint32_t bytes, uint32_t bar) {
  asm volatile("cp.async.bulk.shared::cluster.global.mbarrier::complete_tx::bytes [%0], [%1], %2, [%3];"
               ::"r"(dst), "l"(src), "r"(bytes), "r"(bar) : "memory");
}
__device__ __forceinline__ void proxy_fence() { asm volatile("fence.proxy.async;" ::: "memory"); }

template <int V> struct IC { static constexpr int value = V; };

struct Ctx {
  uint32_t sb;
  uint8_t* sp;
  uint32_t rank;
  Scratch* gs;
};

__device__ __forceinline__ void dly(const Ctx&, int) {}
__device__ __forceinline__ void load_box(uint32_t dst, const CUtensorMap* tm, int c0, int c1, uint32_t bar, uint64_t pol) {
  asm volatile("{\n.reg .pred p;\nelect.sync _|p, 0xffffffff;\n"
               "@p cp.async.bulk.tensor.2d.shared::cluster.global.mbarrier::complete_tx::bytes.multicast::cluster.L2::cache_hint"
               " [%0], [%1, {%2, %3}], [%4], %5, %6;\n}"
               ::"r"(dst), "l"(tm), "r"(c0), "r"(c1), "r"(bar), "h"((uint16_t)3), "l"(pol) : "memory");
}
template <int BOXES>
__device__ __forceinline__ void load_stage(uint32_t dst, const CUtensorMap* tm, int c0, int c1, uint32_t bar, uint32_t bytes, uint64_t pol) {
  asm volatile("{\n.reg .pred p;\nelect.sync _|p, 0xffffffff;\n"
               "@p mbarrier.arrive.expect_tx.shared::cta.b64 _, [%4], %7;\n"
               "@p cp.async.bulk.tensor.2d.shared::cluster.global.mbarrier::complete_tx::bytes.multicast::cluster.L2::cache_hint"
               " [%0], [%1, {%2, %3}], [%4], %5, %6;\n}"
               ::"r"(dst), "l"(tm), "r"(c0), "r"(c1), "r"(bar), "h"((uint16_t)3), "l"(pol), "r"(bytes) : "memory");
  if (BOXES == 2) load_box(dst + 8192, tm, c0, c1 + 64, bar, pol);
}
__device__ __forceinline__ void attn_producer(const Ctx& cx, int qb, int hs, const CUtensorMap* tmX, const CUtensorMap* tmK,
                                              const CUtensorMap* tmV, const CUtensorMap* tmWq, const CUtensorMap* tmWo) {
  const uint32_t full = cx.sb + SM_FULL, empty = cx.sb + SM_EMPTY, ring = cx.sb + SM_RING + cx.rank * 16384;
  const uint64_t keep = policy_evict_normal(), last_use = policy_evict_first();
  auto acquire = [&](int st) {
    mbar_wait(empty + 8 * (st & 3), ((st >> 2) ^ ((st & 3) >> 1) ^ 1) & 1);
    if (st > 3) dly(cx, st);
  };
  if (elect_one()) {
#pragma unroll
    for (int j = 0; j < 3; j++) {
      mbar_expect_tx(cx.sb + SM_XFULL + 96 + 8 * j, 24576);
      tma3d(cx.sb + SM_X + 73728 + j * 24576, tmX, qb * 128 + 64, j * 3, cx.sb + SM_XFULL + 96 + 8 * j);
    }
  }
  __syncwarp();
  const int c0 = cx.rank * 64;
#pragma unroll 1
  for (int st = 0; st < NST_Q - 1; st++) {
    const bool half = st >= 10 && st < 13;
    const int i = st - (st < 5 ? 0 : st < 10 ? 5 : half ? 10 : 13), sl = st & 3;
    const int n0 = (hs * 4 + (st < 5 ? 0 : st < 10 ? 2 : half ? 3 : 1)) * DH + (half ? 0 : c0);
    const int k0 = half ? (i < 2 ? 256 * i + 2 * c0 : 448 + c0) : (i < 3 ? 128 * i : 128 * i - 64);
    if (st == 1) mbar_wait(cx.sb + SM_XFULL + 16, 0);
    acquire(st);
    load_stage<1>(ring + sl * STAGE, tmWq, n0, k0, full + 8 * sl, i == 2 ? 16384 : (half && i) ? 24576 : 32768, last_use);
    if (i != 2 && !(half && i && c0)) load_box(ring + sl * STAGE + 8192, tmWq, n0, k0 + 64, full + 8 * sl, last_use);
    if ((st == 3 || st == 4 || st == 8) && elect_one()) {
      if (st != 4) tma2d_prefetch(tmWq, (hs * 4 + 2 - (st >> 3)) * DH + (qb & 1) * 64, (qb >> 1) * 64);
      else if (qb < 9) tma2d_prefetch(tmWq, (hs * 4 + 3) * DH, qb * 64);
    }
    __syncwarp();
  }
  int vrow = 0;
  uint64_t vpol = keep;
#pragma unroll 1
  for (int j = 0; j < 32; j++) {
    const int st = NST_Q - 1 + 4 * j, row = (hs * 2 + (j >> 4)) * SEQ + (j & 7) * 256;
    const uint64_t pol = (j & 8) ? last_use : keep;
    if (j < 7 && qb < 8 && elect_one()) tma2d_prefetch((qb & 4) ? tmV : tmK, (qb & 1) * 64, row + 256 + (qb & 2) * 64);
    __syncwarp();
    if (j == 24) mbar_wait(cx.sb + SM_BAR_Q3, 0);
    acquire(st);
    load_stage<1>(ring + SL_KE * STAGE, tmK, c0, row, full + 8 * SL_KE, 32768, pol);
    acquire(st + 1);
    if (j) load_stage<1>(ring + SL_VE * STAGE, tmV, c0, vrow, full + 8 * SL_VE, 32768, vpol);
    else load_stage<2>(ring + SL_VE * STAGE, tmWq, (hs * 4 + 1) * DH + c0, 448, full + 8 * SL_VE, 32768, last_use);
    vrow = row + 128;
    vpol = pol;
    acquire(st + 2);
    load_stage<1>(ring + SL_KO * STAGE, tmK, c0, vrow, full + 8 * SL_KO, 32768, pol);
    acquire(st + 3);
    load_stage<1>(ring + SL_VO * STAGE, tmV, c0, row, full + 8 * SL_VO, 32768, pol);
  }
  acquire(NST_Q + NST_KV - 1);
  load_stage<1>(ring + SL_KE * STAGE, tmV, c0, vrow, full + 8 * SL_KE, 32768, last_use);
#pragma unroll 1
  for (int u = 0; u < NST_O; u++) {
    const int st = NST_Q + NST_KV + u, sl = st & 3;
    const int blk = u < 4 && cx.rank ? 8 : ((hs + max(u >> 1, 1)) & 7);
    const int head = u < 4 ? u ^ (u >> 1) : ((u & 1) * 2 + cx.rank + 3) & 3;
    acquire(st);
    load_stage<1>(ring + sl * STAGE, tmWo, blk * 64, hs * 512 + head * 128, full + 8 * sl, 32768, last_use);
  }
}

__device__ __forceinline__ uint32_t xn_offset(uint32_t row, int lane) {
  return (row >> 6) * (9 * 8192) + (row & 63) * 128 + ((((lane >> 2) ^ row) & 7) << 4) + (lane & 3) * 4;
}

__device__ __forceinline__ void attn_rows(const Ctx& cx, int qb, int hs, int hw, int lane, const CUtensorMap* tmX16,
                                          const __nv_bfloat16* w_r) {
  extern __shared__ __align__(1024) uint8_t smem_rows[];
  auto box = [&](int blk) { return blk < 8 ? SM_SLOT + 2 * STAGE + 8192 + (blk >> 2) * 16384 + (blk & 3) * 2048 : SM_BOX8; };
  const uint32_t sb = smem_u32(smem_rows);
  if (hw == 0) {
    bar_sync(BAR_HELPER, 160);
    if (elect_one()) {
      mbar_expect_tx(sb + SM_BAR_ROWS, 9 * 2048);
#pragma unroll
      for (int i = 0; i < 9; i++) tma2d(sb + box(i), tmX16, i * 64, qb * 128 + hs * 16, sb + SM_BAR_ROWS);
    }
    __syncwarp();
  }
  uint32_t g = (lane >> 3) * 128 + (((lane ^ (lane >> 3)) & 7) << 4);
  auto next = [&]() {
    g = ((g + 512) & 2047) ^ 64;
    asm volatile("" : "+r"(g));
  };
  float* const part = (float*)(smem_rows + SM_ROWS);
  mbar_wait(sb + SM_BAR_ROWS, 0);
  if (hw == 0) dly(cx, 190);
#pragma unroll 1
  for (int i = 0; i < 4; i++) {
    float a = 0.f, b = 0.f;
#pragma unroll
    for (int j = 0; j < 3; j++) {
      const uint4 v = *(const uint4*)(smem_rows + box(hw * 3 + j) + g);
      const uint32_t w[4] = {v.x, v.y, v.z, v.w};
#pragma unroll
      for (int k = 0; k < 4; k++) {
        a += bf_lo(w[k]) + bf_hi(w[k]);
        b = fmaf(bf_lo(w[k]), bf_lo(w[k]), fmaf(bf_hi(w[k]), bf_hi(w[k]), b));
      }
    }
    a = sum8(a);
    b = sum8(b);
    float* p = part + hw * 16 + (g >> 7);
    p[0] = a;
    p[48] = b;
    next();
  }
  bar_sync(BAR_ROWS, 96);
  if (hw == 0) dly(cx, 191);
  {
    const float* p = part + (lane & 15);
    const float mean = (p[0] + p[16] + p[32]) * (1.0f / DM), rstd = ln_rstd((p[48] + p[64] + p[80]) * (1.0f / DM) - mean * mean);
    const uint32_t mm = pack2(mean, mean), rr = pack2(rstd - bfr(rstd), rstd);
#pragma unroll 1
    for (int u = hw * 12; u < hw * 12 + 12; u++) {
      const int blk = u >> 2;
      uint4* q = (uint4*)(smem_rows + box(blk) + g);
      uint4 v = *q;
      const uint32_t m = __shfl_sync(0xffffffffu, mm, g >> 7), r = __shfl_sync(0xffffffffu, rr, g >> 7);
      const uint32_t hi = __byte_perm(r, 0, 0x3232), lo = __byte_perm(r, 0, 0x1010);
      auto norm = [&](uint32_t w) {
        const uint32_t xc = sub2(w, m);
        return fma2(xc, hi, mul2(xc, lo));
      };
      v = make_uint4(norm(v.x), norm(v.y), norm(v.z), norm(v.w));
      *q = v;
      *at<uint4>(cx.gs->xn + ((qb * 2 + (hs >> 2)) * 9 + blk) * 512 + (hs & 3) * 128, g) = v;
      next();
    }
  }
  bar_sync(BAR_ROWS, 96);
  if (hw == 0) {
    dly(cx, 192);
    if (lane == 0) red_release(&cx.gs->rows[qb * 32]);
    dly(cx, 193);
  }
#pragma unroll 1
  for (int u = hw ? 13 * hw - 3 : 0; u < 13 * hw + 10; u++) {
    const int blk = u >> 2;
    const uint32_t o = (g + (u & 3) * 512) ^ ((u & 1) << 6);
    const uint4 v = *(const uint4*)(smem_rows + box(blk) + o);
    *at<uint4>(cx.gs->gate + (blk < 8 ? (qb * 8 + blk) * 144 + hs * 16 : (qb * 8 + hs) * 144 + 128) * 8, o) =
        make_uint4(silu2(v.x), silu2(v.y), silu2(v.z), silu2(v.w));
  }
  if (hw) dly(cx, 194 + hw);
  __nanosleep(8000);
#pragma unroll 1
  for (int blk = hw * 3; blk < hw * 3 + 3; blk++) {
    const uint4 c = __ldg(at<const uint4>(w_r, blk * 128 + ((g ^ (g >> 3)) & 0x70)));
#pragma unroll 1
    for (int i = 0; i < 4; i++) {
      const uint4 v = *(const uint4*)(smem_rows + box(blk) + g);
      part[blk * 16 + (g >> 7)] =
          sum8(fmaf(bf_lo(v.x), bf_lo(c.x), fmaf(bf_hi(v.x), bf_hi(c.x), fmaf(bf_lo(v.y), bf_lo(c.y), bf_hi(v.y) * bf_hi(c.y)))) +
               fmaf(bf_lo(v.z), bf_lo(c.z), fmaf(bf_hi(v.z), bf_hi(c.z), fmaf(bf_lo(v.w), bf_lo(c.w), bf_hi(v.w) * bf_hi(c.w)))));
      next();
      __nanosleep(700);
    }
  }
  bar_sync(BAR_ROWS, 96);
  if (hw == 0) {
    dly(cx, 194);
    float d = 0.f;
#pragma unroll
    for (int j = 0; j < 9; j++) d += part[j * 16 + (lane & 15)];
    const uint32_t row = qb * 128 + hs * 16 + (lane & 15), b = pack2(0.f, d);
    *at<uint32_t>(cx.gs->key, row * 4) = (b ^ ((int)b < 0 ? 0xFFFF0000u : 0x80000000u)) + 0xFFFF - row;
    __syncwarp();
    if (lane == 0) red_release(&cx.gs->rows[qb * 32 + 1]);
  }
}

constexpr uint32_t SM_XO = SM_SLOT, SM_GO = SM_SLOT + STAGE, SM_P8 = SM_SLOT + 2 * STAGE;
__device__ __forceinline__ void attn_helper(const Ctx& cx, int qb, int hs, int lane, const __nv_bfloat16* wo, const CUtensorMap* tmX16) {
  unsigned e = 0;
  if (lane == 0) {
    e = cx.gs->launch[blockIdx.x];
    cx.gs->launch[blockIdx.x] = e + 1;
  }
  e = __shfl_sync(0xffffffffu, e, 0);
  if (lane == 0) {
    *(uint32_t*)(cx.sp + SM_TAG) = (~e & 1) * TAG_BIT;
    mbar_arrive(cx.sb + SM_BAR_MISC);
  }
  bar_sync(BAR_HELPER, 64);
  await_count(&cx.gs->rows[qb * 32 + 1], 8 * (e + 1), 1000);
  await_count(&cx.gs->q3_flag[qb * 8 + hs], e + 1, 1000);
  proxy_fence();
  if (elect_one()) {
    mbar_expect_tx(cx.sb + SM_BAR_Q3, 16384);
#pragma unroll
    for (int i = 0; i < 2; i++) bulk_load(cx.sb + SM_SLOT + 2 * STAGE + i * 16384 + 8192, cx.gs->q3 + (qb * 16 + hs * 2 + i) * 512, 8192, cx.sb + SM_BAR_Q3);
  }
  __syncwarp();
  bar_sync(BAR_HELPER, 64);
  prefetch_l2(at<const void>(wo, (hs * 512 + qb * 32 + lane) * (DM * 2)), DM * 2);
  await_count(&cx.gs->ycnt, 4 * (e + 1), 500);
  const uint32_t mykey = __ldcg(at<const uint32_t>(cx.gs->top, (lane >> 1) * 4)), myrow = 0xFFFF - (mykey & 0xFFFF);
#pragma unroll 1
  for (uint32_t todo = __ballot_sync(0xffffffffu, lane < 16 && ((lane & 1) ? myrow >> 4 == qb * 8 + hs : myrow >> 7 == qb)); todo; todo &= todo - 1) {
    const int i = __ffs(todo) - 1, blk = (i & 1) ? 8 : hs;
    const uint32_t key = __shfl_sync(0xffffffffu, mykey, i), row = 0xFFFF - (key & 0xFFFF), o = xn_offset(row, lane);
    const uint32_t t = __ldcg(at<const uint32_t>(cx.gs->xn, o + blk * 8192));
    const float2* p = at<const float2>(cx.gs->ypart, ((i >> 1) * DM + blk * 64 + 2 * lane) * 4);
    const float2 y0 = __ldcg(p), y1 = __ldcg(p + TOPC * DM / 2), y2 = __ldcg(p + TOPC * DM), y3 = __ldcg(p + 3 * TOPC * DM / 2);
    const float rs = bfr(rcp(1.0f + ex2(-1.4426950408889634f * bf_hi(key ^ ((int)key < 0 ? 0x80000000u : 0xFFFF0000u)))));
    const uint32_t y = pack2((y0.x + y1.x) + (y2.x + y3.x), (y0.y + y1.y) + (y2.y + y3.y));
    const uint32_t u = pack2(bf_lo(y) * rs, bf_hi(y) * rs);
    *at<uint32_t>(cx.gs->gate, ((qb * 8 + hs) * 144 + ((i & 1) ? 128 + (row & 15) : row & 127)) * 128 + (o & 127)) = silu2(add2(t, u));
  }
  proxy_fence();
  bar_sync(BAR_OA, 352);
  if (elect_one()) {
    const uint32_t bar = cx.sb + SM_BAR_XG;
    mbar_expect_tx(bar, 2 * 144 * 128);
    bulk_load(cx.sb + SM_GO, cx.gs->gate + (qb * 8 + hs) * (144 * 8), 144 * 128, bar);
#pragma unroll 1
    for (int i = 0; i < 9; i++) tma2d_stream(cx.sb + SM_XO + i * 2048, tmX16, i < 8 ? hs * 64 : 512, qb * 128 + (i < 8 ? i : hs) * 16, bar);
  }
  __syncwarp();
  const uint4* src = cx.gs->part + (qb * 64 + 56 + hs) * 1024;
#pragma unroll 1
  for (int n = 0; n < (1 << 16); n++) {
    __nanosleep(n ? 400 : 700);
    uint32_t a, b, d, t;
    ld_gran(at<const uint4>(src, (lane & 7) * 2048 + 2032), a, b, d, t);
    if (__all_sync(0xffffffffu, ((a >> 16) ^ e) & 1)) break;
  }
  if (elect_one()) {
    mbar_expect_tx(cx.sb + SM_BAR_P8, 16384);
    bulk_load(cx.sb + SM_P8, src, 16384, cx.sb + SM_BAR_P8);
  }
  __syncwarp();
}
__device__ __forceinline__ void attn_finish8(const Ctx& cx, int qb, int hs, int hw, int lane, __nv_bfloat16* out) {
  const uint32_t tag = *(const uint32_t*)(cx.sp + SM_TAG);
  mbar_wait(cx.sb + SM_BAR_P8, 0);
  mbar_wait(cx.sb + SM_BAR_XG, 0);
#pragma unroll 1
  for (int g = 2 - hw; g < 4; g += 3) {
    float acc[8] = {0.f, 0.f, 0.f, 0.f, 0.f, 0.f, 0.f, 0.f};
    uint32_t a[4];
#pragma unroll 1
    for (uint32_t o = g * 512 + lane * 16; o < 16384; o += 2048) {
      lds128(cx.sb + SM_P8 + o, a[0], a[1], a[2], a[3]);
#pragma unroll 1
      for (int n = 0; n < (1 << 16) && __any_sync(0xffffffffu, (a[0] & TAG_BIT) != tag); n++)
        ld_gran(at<const uint4>(cx.gs->part, (qb * 64 + 56 + hs) * 16384 + o), a[0], a[1], a[2], a[3]);
      a[0] &= ~TAG_BIT;
#pragma unroll
      for (int j = 0; j < 4; j++) { acc[2 * j] += bf_lo(a[j]); acc[2 * j + 1] += bf_hi(a[j]); }
    }
    asm volatile("" : "+r"(lane));
    const uint32_t tile = cx.sb + SM_XO + (128 + (lane & 15)) * 128 + (((lane >> 4) ^ (lane & 7)) << 4);
    uint32_t b[4];
    ldsm4((tile ^ (g << 5)) + STAGE, a[0], a[1], a[2], a[3]);
    ldsm4(tile ^ (g << 5), b[0], b[1], b[2], b[3]);
    stsm4(tile ^ (g << 5), fma2(pack2(acc[0], acc[1]), a[0], b[0]), fma2(pack2(acc[2], acc[3]), a[1], b[1]),
          fma2(pack2(acc[4], acc[5]), a[2], b[2]), fma2(pack2(acc[6], acc[7]), a[3], b[3]));
  }
  bar_sync(BAR_ROWS, 96);
#pragma unroll 1
  for (int ch = threadIdx.x - 32; ch < 128; ch += 96)
    *at<uint4>(out, ((qb * 128 + hs * 16 + (ch >> 3)) * DM + 512 + (ch & 7) * 8) * 2) =
        *(const uint4*)(cx.sp + SM_XO + (128 + (ch >> 3)) * 128 + (((ch ^ (ch >> 3)) & 7) << 4));
}

constexpr float S_BIAS = 42.625f, S_SCALE = 6782714904576.f;
constexpr float O_BIAS = 53.333332f * 8796093022208.f;
constexpr float SUM_HI = 2.8147498e14f, SUM_LO = 9.0949470e-13f;

__device__ __forceinline__ float offset_for(const float* o, float f) {
  const float m = fmaxf(fmaxf(fmaxf(fabsf(o[0]), fabsf(o[9])), fmaxf(fabsf(o[16]), fabsf(o[25]))),
                        fmaxf(fmaxf(fabsf(o[32]), fabsf(o[41])), fmaxf(fabsf(o[48]), fabsf(o[57]))));
  return __uint_as_float(__float_as_uint(m) & 0x7F800000u) * f;
}
template <int LO, int HI>
__device__ __forceinline__ void softmax_exp(float (&s)[64]) {
#pragma unroll
  for (int i = LO; i < HI; i++) s[i] = ex2(s[i]);
}
__device__ __forceinline__ void row_sums(const uint32_t (&pf)[32], float& l0, float& l1) {
  uint32_t t[16];
#pragma unroll
  for (int i = 0; i < 16; i++) t[i] = add2(pf[(i >> 1) * 4 + (i & 1)], pf[(i >> 1) * 4 + 2 + (i & 1)]);
#pragma unroll
  for (int i = 0; i < 8; i++) t[i] = add2(t[(i >> 1) * 4 + (i & 1)], t[(i >> 1) * 4 + 2 + (i & 1)]);
#pragma unroll
  for (int i = 0; i < 4; i++) t[i] = add2(t[(i >> 1) * 4 + (i & 1)], t[(i >> 1) * 4 + 2 + (i & 1)]);
  t[0] = add2(t[0], t[2]);
  t[1] = add2(t[1], t[3]);
  l0 = (l0 + bf_lo(t[0])) + bf_hi(t[0]);
  l1 = (l1 + bf_lo(t[1])) + bf_hi(t[1]);
}
__device__ __forceinline__ void softmax_redo(uint32_t (&pf)[32], const uint32_t (&q)[32], const __nv_bfloat16* kblk, int lane, float& n0,
                                             float& n1, float& l0, float& l1, float& sc0, float& sc1, float bias) {
  float x0 = -3.0e38f, x1 = -3.0e38f;
#pragma unroll 1
  for (int u = 0; u < 16; u++) {
    const uint32_t* kp = (const uint32_t*)(kblk + ((u & 7) * 16 + (lane >> 2)) * DH) + (lane & 3);
    float d[2][4] = {};
#pragma unroll
    for (int k = 0; k < 16; k++)
      hmma_k16(d[k & 1], q[2 * (k & 14)], q[2 * (k & 14) + 1], q[2 * (k & 14) + 2], q[2 * (k & 14) + 3],
               kp[(k & 1) * 4 * DH + (k >> 1) * 8], kp[(k & 1) * 4 * DH + (k >> 1) * 8 + 4]);
    if (u < 8) {
      x0 = fmaxf(fmaxf(x0, fmaxf(d[0][0], d[0][1])), fmaxf(d[1][0], d[1][1]));
      x1 = fmaxf(fmaxf(x1, fmaxf(d[0][2], d[0][3])), fmaxf(d[1][2], d[1][3]));
      if (u == 7) {
#pragma unroll
        for (int m = 1; m < 4; m <<= 1) {
          x0 = fmaxf(x0, __shfl_xor_sync(0xffffffffu, x0, m));
          x1 = fmaxf(x1, __shfl_xor_sync(0xffffffffu, x1, m));
        }
        x0 = fminf(bias - x0, n0);
        x1 = fminf(bias - x1, n1);
        sc0 = ex2(x0 - n0);
        sc1 = ex2(x1 - n1);
        n0 = x0;
        n1 = x1;
        l0 *= sc0;
        l1 *= sc1;
      }
    } else {
#pragma unroll
      for (int i = 0; i < 28; i++) pf[i] = pf[i + 4];
#pragma unroll
      for (int i = 0; i < 4; i++) {
        const float n = (i & 1) ? n1 : n0;
        pf[28 + i] = pack2(ex2(d[i >> 1][(i & 1) * 2] + n), ex2(d[i >> 1][(i & 1) * 2 + 1] + n));
        ((i & 1) ? l1 : l0) += bf_lo(pf[28 + i]) + bf_hi(pf[28 + i]);
      }
    }
  }
}

#define TH(i)
__device__ __forceinline__ void attn_consumer(const Ctx& cx, int qb, int hs, int wg, int cw, int lane, const __nv_bfloat16* x,
                                              const __nv_bfloat16* kc, __nv_bfloat16* out) {
  const uint32_t full = cx.sb + SM_FULL;
  const uint32_t ring = cx.sb + SM_RING;
  uint32_t lo = ((cw & 3) * 16 + (lane & 15)) * 128 + (((lane >> 4) ^ (lane & 7)) << 4);
  const uint32_t slot = cx.sb + SM_SLOT + wg * 16384;
  auto frag = [&](int sl, int k) { return ((slot + sl * STAGE + lo) ^ ((k & 3) << 5)) + (k >> 2) * 8192; };
  auto park = [&](const float (&a)[64], int sl, int k0, int k1, float f0, float f1, float g0 = -0.f, float g1 = -0.f) {
#pragma unroll
    for (int k = 0; k < 8; k++)
      if (k >= k0 && k < k1)
        stsm4(frag(sl, k), pack2(fmaf(a[8 * k], f0, g0), fmaf(a[8 * k + 1], f0, g0)), pack2(fmaf(a[8 * k + 2], f1, g1), fmaf(a[8 * k + 3], f1, g1)),
              pack2(fmaf(a[8 * k + 4], f0, g0), fmaf(a[8 * k + 5], f0, g0)), pack2(fmaf(a[8 * k + 6], f1, g1), fmaf(a[8 * k + 7], f1, g1)));
  };
  const bool signaller = lane == 0 && (cw & 3) < 2;
  int my_turn = 1 + wg, other_turn = 2 - wg;

  uint32_t pf[32], q[32], empty_c;
#pragma nv_diag_suppress 549
  float o[64], l0, l1, c0 = 0.f, c1 = 0.f;
  {
    uint32_t xa[144];
    float rstd0, rstd1;
    {
      const uint32_t xb = cx.sb + SM_X + wg * 73728, xf = cx.sb + SM_XFULL + wg * 96;
      float sm[4][4] = {};
      prof(wg, 0);
      empty_c = mapa(cx.sb + SM_EMPTY, cw & 1);
      mbar_wait(xf, 0);
      TH(0)
      ln_fetch<0, 12>(xa, xb, lo);
      mbar_wait(xf + 8, 0);
      TH(1)
      ln_fetch<12, 24>(xa, xb, lo);
      ln_sums<0, 12>(xa, sm);
      mbar_wait(xf + 16, 0);
      TH(2)
      ln_fetch<24, 36>(xa, xb, lo);
      ln_sums<12, 36>(xa, sm);
      block_fence(36);
      if (wg) bar_arrive(other_turn, 256);
      block_fence(35);
      TH(3)
      rstd0 = ((sm[0][0] + sm[1][0]) + (sm[2][0] + sm[3][0])) * (1.0f / DM);
      rstd1 = ((sm[0][2] + sm[1][2]) + (sm[2][2] + sm[3][2])) * (1.0f / DM);
    }
    const uint32_t mm0 = pack2(rstd0, rstd0), mm1 = pack2(rstd1, rstd1);
    rstd0 -= bf_lo(mm0);
    rstd1 -= bf_lo(mm1);
    rstd0 *= rstd0 * (-0.25f * DM);
    rstd1 *= rstd1 * (-0.25f * DM);
    auto ln_finish = [&]() {
      rstd0 += __shfl_xor_sync(0xffffffffu, rstd0, 1); rstd1 += __shfl_xor_sync(0xffffffffu, rstd1, 1);
      rstd0 += __shfl_xor_sync(0xffffffffu, rstd0, 2); rstd1 += __shfl_xor_sync(0xffffffffu, rstd1, 2);
      rstd0 = ln_rstd(rstd0 * (1.0f / DM)) * SM_SCALE_LOG2;
      rstd1 = ln_rstd(rstd1 * (1.0f / DM)) * SM_SCALE_LOG2;
    };
    ln_centre(xa, 0, X_C0, mm0, mm1, rstd0, rstd1);
    if (wg == 0) {
      bar_sync(4, 128);
      if (signaller) {
        asm volatile("mbarrier.arrive.shared::cluster.b64 _, [%0], 2;" ::"r"(empty_c + 16) : "memory");
        asm volatile("mbarrier.arrive.shared::cluster.b64 _, [%0], 2;" ::"r"(empty_c + 24) : "memory");
      }
      block_fence(37);
      pin(xa);
      ln_centre(xa, X_C0, X_C1, mm0, mm1, rstd0, rstd1);
    }
    pin(xa);

    extern __shared__ __align__(1024) uint8_t smem_q[];
    const uint32_t ring = smem_u32(smem_q) + SM_RING;
    auto release = [&](int st) { if (signaller) mbar_arrive_cluster(empty_c + 8 * (st & 3)); };
    auto q_stage = [&](float (&acc)[64], int st, int i, int last) {
      mbar_wait(full + 8 * (st & 3), (st >> 2) & 1);
      if (i != (wg ? last : 1)) bar_sync(my_turn, 256);
      wg_fence();
      const uint64_t db = mkdesc(ring + (st & 3) * STAGE, 16384);
#pragma unroll
      for (int k = 0; k < 8; k++) {
        const int kb = (i < 3 ? 8 * i : 8 * i - 4) + k;
        if (i != 2 || k < 4) mma_n128<1>(acc, xa[4 * kb], xa[4 * kb + 1], xa[4 * kb + 2], xa[4 * kb + 3], db + k * 128, kb > 0);
      }
      wg_commit();
      if (i != (wg ? last - 1 : 0)) bar_arrive(other_turn, 256);
    };
    auto q_release = [&](int st, int i, int last) {
      if (i == 1 || i == last) {
        wg_wait<1>();
        if (i == last || !wg) release(st - 1);
      }
      if (i != last - 1 && (i || wg)) {
        wg_wait<0>();
        release(st);
      }
    };
    {
      float (&acc)[64] = o;
#pragma unroll 1
      for (int p = 0; p < 2; p++) {
#pragma unroll
        for (int i = 0; i < 5; i++) {
          q_stage(acc, 5 * p + i, i, 4);
          if (p == 0 && i != 3) {
            if (i == 0 && wg) bar_arrive(BAR_HELPER, 160);
            if ((wg || i) && i < 3) ln_centre(xa, i == 0 ? X_C0 : i == 1 ? X_C1 : X_C2, i == 0 ? X_C1 : i == 1 ? X_C2 : 72, mm0, mm1, rstd0, rstd1);
            if (i == 4) ln_finish();
            pin(xa);
          }
          q_release(5 * p + i, i, 4);
        }
        pin(acc);
#pragma unroll
        for (int k = 0; k < 8; k += 2) {
          park(acc, p, k, k + 2, rstd0, rstd1);
          if (k < 6) block_fence(40 + k);
        }
      }
    }
    {
      float (&h)[32] = *(float (*)[32])&o[0];
#pragma unroll
      for (int i = 0; i < 3; i++) {
        const uint32_t sl = (10 + i) & 3;
        mbar_wait(full + 8 * sl, ((10 + i) >> 2) & 1);
        if (i != (wg ? 2 : 1)) bar_sync(my_turn, 256);
        wg_fence();
#pragma unroll
        for (int k = 0; k < 16 - 4 * i; k++) {
          const int kb = (i == 2 ? 28 : 16 * i) + k;
          const uint64_t db = mkdesc(ring + sl * STAGE, 16) + (i == 2 && k >= 4 ? k + 4 : k) * 128;
          mma_n64<1>(h, xa[4 * kb], xa[4 * kb + 1], xa[4 * kb + 2], xa[4 * kb + 3], db, kb > 0);
        }
        wg_commit();
        if (i != (wg ? 1 : 0)) bar_arrive(other_turn, 256);
        q_release(10 + i, i, 2);
      }
      pin(h);
      park(o, 2, 0, 2, rstd0, rstd1);
      block_fence(49);
      park(o, 2, 2, 4, rstd0, rstd1);
    }
#pragma unroll
    for (int i = 0; i < 4; i++) {
      q_stage(o, 13 + i, i, 3);
      q_release(13 + i, i, 3);
    }
    prof(wg, 6);
#pragma unroll
    for (int i = 0; i < 32; i++) pf[i] = xa[112 + i];
    l0 = 0.25f * rcp(rstd0);
    l1 = 0.25f * rcp(rstd1);
  }

  uint32_t oa[96];
  const uint32_t zero = __shfl_sync(0xffffffffu, blockIdx.y, lane);
  my_turn = __shfl_sync(0xffffffffu, my_turn, lane);
  other_turn = __shfl_sync(0xffffffffu, other_turn, lane);
  lo = __shfl_sync(0xffffffffu, lo, lane);
  {
    float s[64], n0 = 0.f, n1 = 0.f;
    float lp0, lp1;
    float i0 = 0.f, i1 = 0.f;
    float hi = 0.f;
    bool redo;
    auto turn = [&](int it, auto kc_) -> bool {
      constexpr int KIND = decltype(kc_)::value;
      constexpr uint32_t slk = KIND == 1 ? SL_KO : SL_KE, slv = KIND == 1 ? SL_VO : SL_VE, slkn = KIND == 1 ? SL_KE : SL_KO;
      constexpr int SPLIT = KIND == 3 ? X_SPLIT3 : X_SPLIT, PARK1 = X_PARK;
      const uint32_t par = ((it + NST_Q / 2) >> 1) & 1;
      const int hsl = max((it >> 4) - 1, 0);
      const bool second = KIND == 1 && (it & 15) == 1;
      const uint64_t dk = mkdesc(ring + slk * STAGE, 16), dv = mkdesc(ring + slv * STAGE, 16384);
      auto qk = [&](int k, int acc) {
        if (KIND == 3) mma_n128_ss<0>(s, mkdesc(slot + hsl * STAGE, 16) + (k >> 2) * 512 + (k & 3) * 2, dk + (k >> 2) * 1024 + (k & 3) * 2, acc);
        else mma_n128<0>(s, q[4 * k], q[4 * k + 1], q[4 * k + 2], q[4 * k + 3], dk + (k >> 2) * 1024 + (k & 3) * 2, acc);
      };
      auto pv = [&]() {
#pragma unroll
        for (int k = 0; k < 8; k++)
          mma_n128<1>(o, pf[4 * k], pf[4 * k + 1], pf[4 * k + 2], pf[4 * k + 3], dv + k * 128, k > 0 || !second);
        wg_commit();
      };
      if (KIND == 2 && (it & 15) == 2) {
        n0 += S_BIAS;
        n1 += S_BIAS;
        l0 *= S_SCALE;
        l1 *= S_SCALE;
        hi = SUM_HI * S_SCALE;
        asm volatile("" : "+f"(n0), "+f"(n1), "+f"(l0), "+f"(l1), "+f"(hi)::"memory");
      }
      lp0 = l0; lp1 = l1;
#define TS(i)
      {
        TS(0)
        if (KIND == 3) {
          asm volatile("fence.proxy.async.shared::cta;" ::: "memory");
          const float t0 = lp0 + __shfl_xor_sync(0xffffffffu, lp0, 1), t1 = lp1 + __shfl_xor_sync(0xffffffffu, lp1, 1);
          i0 = rcp(t0 + __shfl_xor_sync(0xffffffffu, t0, 2));
          i1 = rcp(t1 + __shfl_xor_sync(0xffffffffu, t1, 2));
          asm volatile("" : "+f"(i0), "+f"(i1)::"memory");
          block_fence(31, zero);
#pragma unroll
          for (int k = 0; k < X_N1; k++) ldsm4(frag(hsl, k), q[4 * k], q[4 * k + 1], q[4 * k + 2], q[4 * k + 3]);
        }
        if (KIND != 3) pin(q);
        pin(pf); pin(o);
        if (KIND != 3 && !second) {
#pragma unroll
          for (int i = 0; i < 64; i++) s[i] = ((i & 2) ? n1 : n0) + (i + 1) * 1e-30f;
        }
        if (KIND != 3) pin(s);
        bar_sync(my_turn, 256);
        wg_fence();
#pragma unroll
        for (int k = 0; k < 8; k++) qk(k, k > 0 || (KIND != 3 && !second));
        wg_commit();
        TS(2)
        mbar_wait(full + 8 * slv, par);
        if (KIND == 2 && (it & 15) == 2) {
          c0 = offset_for(o, O_BIAS);
          c1 = offset_for(o + 2, O_BIAS);
          asm volatile("" : "+f"(c0), "+f"(c1)::"memory");
          wg_fence();
        }
        if (KIND == 1 && (it & 13) == 1) {
          if (second) {
            park(o, hsl, PARK1, 8, i0, i1, c0, c1);
          } else {
#pragma unroll
            for (int i = 0; i < 64; i++) o[i] = fmaf(o[i], S_SCALE, (i & 2) ? c1 : c0);
            pin(o);
          }
          wg_fence();
        }
        if (KIND == 3) {
#pragma unroll
          for (int k = X_N1; k < 8; k++) ldsm4(frag(hsl, k), q[4 * k], q[4 * k + 1], q[4 * k + 2], q[4 * k + 3]);
          block_fence(32, zero);
        }
        TS(3)
        pv();
        bar_arrive(other_turn, 256);
        TS(4)
        wg_wait<1>();
      }
      pin(s);
      mbar_arrive_cluster_now<10 * KIND + 3>(empty_c + 8 * slk, signaller, zero);
      TS(5)
      if (KIND == 3) {
        n0 = n1 = l0 = l1 = 0.f;
        hi = SUM_HI;
        c0 *= -i0;
        c1 *= -i1;
      }
      softmax_exp<0, SPLIT>(s);
      pin(s);
      block_fence(10 * KIND + 4, zero);
      TS(6)
      wg_wait<0>();
      pin(o); pin(pf);
      mbar_arrive_cluster_now<10 * KIND + 5>(empty_c + 8 * slv, signaller, zero);
      TS(7)
      const bool kready = mbar_test(full + 8 * slkn, par);
      softmax_exp<SPLIT, 64>(s);
#pragma unroll
      for (int i = 0; i < 32; i++) pf[i] = pack2(s[2 * i], s[2 * i + 1]);
      row_sums(pf, l0, l1);
      if (KIND == 3) {
        park(o, hsl, 0, PARK1, i0, i1, c0, c1);
        if (it) prof(wg, 6 + (it >> 4));
        if (it >= 32 && cw == 0) bar_arrive(BAR_HELPER, 64);
      }
      redo = !(l0 + l1 <= hi) || (KIND == 3 && fminf(l0, l1) < SUM_LO);
      const bool leave = __any_sync(0xffffffffu, redo || !kready);
      return leave;
    };
    int it = -1;
#pragma unroll 1
    while (true) {
      mbar_wait(full + 8 * ((it & 1) ? SL_KE : SL_KO), ((it + NST_Q / 2) >> 1) & 1);
      it++;
#pragma unroll 1
      while (true) {
        if (it & 1) {
          if (turn(it, IC<1>()) || it == 63) break;
          it++;
        }
        if (it & 15) {
          if (turn(it, IC<2>())) break;
        } else {
          if (turn(it, IC<3>())) break;
        }
        it++;
      }
      if (__any_sync(0xffffffffu, redo)) {
        const int j = it & 15;
        float sc0 = 1.f, sc1 = 1.f;
        if (j == 0) n0 = n1 = 3.0e38f;
        l0 = j ? lp0 : 0.f;
        l1 = j ? lp1 : 0.f;
        softmax_redo(pf, q, kc + (size_t)((hs * 2 + (it >> 5)) * SEQ + j * 128) * DH, lane, n0, n1, l0, l1, sc0, sc1, j > 1 ? S_BIAS : 0.f);
        if (j == 0) {
          sc0 = sc1 = 1.f;
          hi = -1.f;
        }
        c0 *= sc0;
        c1 *= sc1;
#pragma unroll
        for (int i = 0; i < 16; i++) { o[4 * i] *= sc0; o[4 * i + 1] *= sc0; o[4 * i + 2] *= sc1; o[4 * i + 3] *= sc1; }
      }
      if (it == 63) break;
    }
  }

#define TE(i) {}
  {
    constexpr int ST0 = NST_Q + NST_KV;
    float acc[32], red[32], first[32];
    uint32_t tag;
    uint4* xch;
    auto await = [&](int st) { mbar_wait(full + 8 * (st & 3), (st >> 2) & 1); };
    auto release = [&](int st) { if (signaller) mbar_arrive_cluster(empty_c + 8 * (st & 3)); };
    auto unpark = [&](int h, int k0, int k1) {
#pragma unroll
      for (int k = 0; k < 8; k++)
        if (k >= k0 && k < k1) ldsm4(frag(h, k), oa[32 * h + 4 * k], oa[32 * h + 4 * k + 1], oa[32 * h + 4 * k + 2], oa[32 * h + 4 * k + 3]);
    };
    {
      float ar[64];
      asm volatile("fence.proxy.async.shared::cta;" ::: "memory");
      await(ST0 - 1);
      unpark(1, 0, 4);
      bar_sync(my_turn, 256);
      pin(pf); pin(o);
      wg_fence();
#pragma unroll
      for (int k = 0; k < 8; k++)
        mma_n128<1>(o, pf[4 * k], pf[4 * k + 1], pf[4 * k + 2], pf[4 * k + 3], mkdesc(ring + SL_KE * STAGE, 16384) + k * 128, 1);
      wg_commit();
      block_fence(66, zero);
      l0 += __shfl_xor_sync(0xffffffffu, l0, 1); l1 += __shfl_xor_sync(0xffffffffu, l1, 1);
      l0 += __shfl_xor_sync(0xffffffffu, l0, 2); l1 += __shfl_xor_sync(0xffffffffu, l1, 2);
      float f0 = rcp(l0), f1 = rcp(l1);
      asm volatile("" : "+f"(f0), "+f"(f1)::"memory");
      await(ST0);
      unpark(1, 4, 8);
      block_fence(61, zero);
#pragma unroll
      for (int k = 0; k < 8; k++) mma_n128_ss<1>(ar, mkdesc(slot, 16) + (k >> 2) * 512 + (k & 3) * 2, mkdesc(ring + (ST0 & 3) * STAGE, 16384) + k * 128, k > 0);
      wg_commit();
      bar_arrive(other_turn, 256);
      wg_wait<1>();
      pin(o); pin(pf);
      mbar_arrive_cluster_now<62>(empty_c + 8 * SL_KE, signaller, zero);
      c0 *= -f0;
      c1 *= -f1;
#pragma unroll
      for (int i = 0; i < 16; i++) {
        pf[2 * i] = pack2(fmaf(o[4 * i], f0, c0), fmaf(o[4 * i + 1], f0, c0));
        pf[2 * i + 1] = pack2(fmaf(o[4 * i + 2], f1, c1), fmaf(o[4 * i + 3], f1, c1));
      }
      pin(pf);
      prof(wg, 10);
#pragma unroll
      for (int u = 1; u < 4; u++) {
        await(ST0 + u);
        wg_wait<0>();
        release(ST0 + u - 1);
        bar_sync(my_turn, 256);
        wg_fence();
#pragma unroll
        for (int k = 0; k < 8; k++) {
          const uint32_t* a = (u == 1 ? oa + 32 : u == 2 ? pf : oa + 64) + 4 * k;
          mma_n128<1>(ar, a[0], a[1], a[2], a[3], mkdesc(ring + ((ST0 + u) & 3) * STAGE, 16384) + k * 128, 1);
        }
        wg_commit();
        bar_arrive(other_turn, 256);
        if (u < 3) {
          block_fence(62 + u, zero);
          unpark(u == 1 ? 2 : 0, 0, 8);
        }
      }
      mbar_wait(cx.sb + SM_BAR_MISC, 0);
      tag = *(const volatile uint32_t*)(cx.sp + SM_TAG);
      xch = at<uint4>(cx.gs->part, (qb << 20) + lane * 16 + zero);
      tag = __shfl_sync(0xffffffffu, tag, lane);
      await(ST0 + 4);
      wg_wait<0>();
      release(ST0 + 3);
      pin(ar);
#pragma unroll
      for (int i = 0; i < 32; i++) { first[i] = ar[i]; red[i] = ar[32 + i]; }
    }
    auto send = [&](const float (&v)[32], int dst, int idx) {
      uint4* p = at<uint4>(xch, (dst * 8 + idx) * 2048);
#pragma unroll
      for (int i = 0; i < 4; i++)
        st_gran(p + i * 32, (pack2(v[8 * i], v[8 * i + 1]) & ~TAG_BIT) | tag, pack2(v[8 * i + 2], v[8 * i + 3]),
                pack2(v[8 * i + 4], v[8 * i + 5]), pack2(v[8 * i + 6], v[8 * i + 7]));
    };
    send(first, ((hs + 1) & 7) * 7, cw);
    int nrx = 1;
    auto half_step = [&](int s, auto hc, bool arrive) {
      constexpr int h = decltype(hc)::value;
      const int st = ST0 + 2 * s + h;
      const uint64_t db = mkdesc(ring + (st & 3) * STAGE, 16);
      bar_sync(my_turn, 256);
      if (h == 0) pin(pf);
#pragma unroll
      for (int i = 32 * h; i < 32 + 64 * h; i++) asm volatile("" : "+r"(oa[i])::"memory");
      wg_fence();
#pragma unroll
      for (int k = 0; k < 16; k++) {
        const int kb = h * 16 + k - 8;
        if (kb >= 0) mma_n64<1>(acc, oa[4 * kb], oa[4 * kb + 1], oa[4 * kb + 2], oa[4 * kb + 3], db + k * 128, 1);
        else mma_n64<1>(acc, pf[4 * k], pf[4 * k + 1], pf[4 * k + 2], pf[4 * k + 3], db + k * 128, k > 0);
      }
      wg_commit();
      if (arrive) bar_arrive(other_turn, 256);
    };
    auto source = [&](int n) { return at<const uint4>(xch, ((hs * 7 + n - 1) * 8 + cw) * 2048); };
    auto fetch = [&](uint32_t (&g)[16], const uint4* p) {
#pragma unroll
      for (int i = 0; i < 4; i++) ld_gran(p + i * 32, g[4 * i], g[4 * i + 1], g[4 * i + 2], g[4 * i + 3]);
    };
    uint32_t g[16];
#pragma unroll 1
    for (int s = 2; s < 8; s++) {
      const int st = ST0 + 2 * s;
      half_step(s, IC<0>(), true);
      if (s == 2) {
        bar_arrive(BAR_OA, 352);
        send(red, 56 + cw, hs);
#pragma unroll
        for (int i = 0; i < 32; i++) red[i] = 0.f;
      }
      await(st + 1);
      if (s > 3 && granules_ok(g, tag)) { add_granules(red, g); nrx++; }
      wg_wait<0>();
      if (s < 7) release(st);
      if (s > 2) fetch(g, source(nrx));
      half_step(s, IC<1>(), true);
      await(st + 2);
      wg_wait<0>();
      if (s < 7) release(st + 1);
      pin(acc);
      if (s == 7) prof(wg, 19);
      send(acc, ((hs + s) & 7) * 7 + s - 1, cw);
    }
    TE(1)
    uint32_t xv[16], gt[16];
    {
      const int s = 8;
      uint32_t g2[16];
      half_step(s, IC<0>(), true);
      TE(2)
      await(NST_Q + NST_KV + NST_O - 1);
      cluster_arrive();
      mbar_wait(cx.sb + SM_BAR_XG, 0);
      const uint32_t tile = cx.sb + SM_XO + wg * 8192 + lo;
      if (granules_ok(g, tag)) { add_granules(red, g); nrx++; }
      fetch(g, source(nrx));
      block_fence(58, zero);
      wg_wait<0>();
      TE(3)
#pragma unroll
      for (int k = 0; k < 4; k++) ldsm4((tile ^ (k << 5)) + STAGE, gt[4 * k], gt[4 * k + 1], gt[4 * k + 2], gt[4 * k + 3]);
      half_step(s, IC<1>(), wg == 0);
      TE(4)
      block_fence(56, zero);
      const bool ok = granules_ok(g, tag);
      block_fence(57, zero + ok * 1000);
      const uint4* src = source(7);
      fetch(g2, src);
#pragma unroll
      for (int k = 0; k < 4; k++) ldsm4(tile ^ (k << 5), xv[4 * k], xv[4 * k + 1], xv[4 * k + 2], xv[4 * k + 3]);
      if (ok) { add_granules(red, g); nrx++; }
      TE(5)
      block_fence(59, zero);
      wg_wait<0>();
      pin(acc);
      TE(6)
#pragma unroll
      for (int i = 0; i < 32; i++) red[i] += acc[i];
      pin(red);
      TE(7)
      int n = 7;
#pragma unroll 1
      for (int spins = 0; spins < (1 << 16); spins++) {
        if (granules_ok(g2, tag)) {
          add_granules(red, g2);
          if (--n < nrx) {
            break;
          }
          src -= 1024;
        }
        fetch(g2, src);
      }
      TE(8)
    }
    prof(wg, 20);
    TE(9)
    const uint32_t ot = ring + ((ST0 + NST_O) & 3) * STAGE + cw * (16 * 144);
    uint32_t ow[16];
#pragma unroll
    for (int i = 0; i < 16; i++) ow[i] = fma2(pack2(red[2 * i], red[2 * i + 1]), gt[i], xv[i]);
#pragma unroll
    for (int i = 0; i < 4; i++)
      stsm4(ot + (lane & 15) * 144 + (2 * i + (lane >> 4)) * 16, ow[4 * i], ow[4 * i + 1], ow[4 * i + 2], ow[4 * i + 3]);
    __syncwarp();
#pragma unroll
    for (int i = 0; i < 4; i++) {
      uint4 v;
      lds128(ot + (i * 4 + (lane >> 3)) * 144 + (lane & 7) * 16, v.x, v.y, v.z, v.w);
      at<uint4>(out, ((qb * 128 + cw * 16 + (lane >> 3)) * DM + hs * 64 + (lane & 7) * 8) * 2)[i * (4 * DM / 8)] = v;
    }
    TE(10)
    prof(wg, 22);
  }
}

constexpr int AST_X = 6, AST_F = AST_X + 96;
__device__ __forceinline__ void aux_producer(const Ctx& cx, int f, const CUtensorMap* tmWq, const CUtensorMap* tmG) {
  const uint32_t full = cx.sb + SM_FULL, empty = cx.sb + SM_EMPTY;
  __nanosleep(3000);
  if (elect_one()) {
#pragma unroll 1
    for (int st = 0; st < AST_X; st++) {
      mbar_expect_tx(full + 8 * st, FSTAGE);
#pragma unroll
      for (int i = 0; i < 3; i++)
        tma2d_stream(cx.sb + st * FSTAGE + i * 8192, tmWq, (2 * f + (st & 1)) * 512 + 448, (st >> 1) * 192 + i * 64, full + 8 * st);
    }
  }
  __syncwarp();
  mbar_wait(cx.sb + SM_BAR_MISC, 0);
  proxy_fence();
  int st = AST_X;
#pragma unroll 1
  for (; st < AST_F; st++) {
    const uint32_t sl = st & 7;
    mbar_wait(empty + 8 * sl, ((st >> 3) & 1) ^ 1);
    if (elect_one()) {
      mbar_expect_tx(full + 8 * sl, FSTAGE);
      bulk_load(cx.sb + sl * FSTAGE, cx.gs->xn + (st - AST_X) * (FSTAGE / 16), FSTAGE, full + 8 * sl);
    }
    __syncwarp();
  }
#pragma unroll 1
  for (int pair = 0; pair < 14; pair++) {
#pragma unroll 1
    for (int u = 0; u < 12; u++, st++) {
      const uint32_t sl = st & 7;
      const int unit = pair * 2 + (u & 1), k = u >> 1;
      if (unit == 27) continue;
      const bool gu = pair < 9;
      mbar_wait(empty + 8 * sl, ((st >> 3) & 1) ^ 1);
      if (elect_one()) {
        mbar_expect_tx(full + 8 * sl, FSTAGE);
        tma2d_stream(cx.sb + sl * FSTAGE, tmG + (gu ? k >= 3 : 2), gu ? f * 1152 + unit * 64 : (unit - 18) * 64,
                     gu ? (k >= 3 ? k - 3 : k) * 192 : f * 1152 + k * 192, full + 8 * sl);
      }
      __syncwarp();
    }
  }
}

constexpr int BAR_FREE = 4, BAR_TILE = 6;
__device__ __forceinline__ void aux_helper(const Ctx& cx, int f, int warp, int lane) {
  unsigned epoch = 0;
  if (lane == 0) epoch = cx.gs->launch[blockIdx.x] + 1;
  epoch = __shfl_sync(0xffffffffu, epoch, 0);
  bar_sync(BAR_OA, 96);
  if (warp == 3) {
    if (lane == 0) cx.gs->launch[blockIdx.x] = epoch;
    await_count(at<const unsigned>(cx.gs->rows, (lane & 15) * 128), 8 * epoch, 200);
    if (lane == 0) mbar_arrive(cx.sb + SM_BAR_MISC);
    prof(0, 1, 31);
    await_count(at<const unsigned>(cx.gs->rows, (lane & 15) * 128 + 4), 8 * epoch, 500);
    proxy_fence();
    if (elect_one()) {
      mbar_expect_tx(cx.sb + SM_BAR_ROWS, SEQ * 4);
      bulk_load(cx.sb + SM_XSEL, cx.gs->key, SEQ * 4, cx.sb + SM_BAR_ROWS);
    }
    __syncwarp();
    mbar_wait(cx.sb + SM_BAR_ROWS, 0);
    uint32_t bound = 0xFFFFFFFFu, mine = 0;
#pragma unroll 1
    for (int k = 0; k < TOPC; k++) {
      uint32_t m = 0;
#pragma unroll 2
      for (int i = 0; i < 16; i++) {
        const uint4 v = *(const uint4*)(cx.sp + SM_XSEL + lane * 16 + i * 512);
        m = max(max(m, v.x <= bound ? v.x : 0), max(v.y <= bound ? v.y : 0, max(v.z <= bound ? v.z : 0, v.w <= bound ? v.w : 0)));
      }
      m = __reduce_max_sync(0xffffffffu, m);
      bound = m - 1;
      if (lane == k) mine = m;
    }
    if (f == 0 && lane < TOPC) *at<uint32_t>(cx.gs->top, lane * 4) = mine;
#pragma unroll 1
    for (int u = 0; u < 6; u++) {
      const int k = (u & 1) * 4 + (lane >> 3);
      const uint32_t row = 0xFFFF - (__shfl_sync(0xffffffffu, mine, k) & 0xFFFF);
#pragma unroll
      for (int j = 0; j < 3; j++)
        *(uint4*)(cx.sp + SM_XSEL + ((u >> 1) * 3 + j) * 1024 + k * 128 + (((lane ^ k) & 7) << 4)) =
            __ldcg(at<const uint4>(cx.gs->xn, xn_offset(row, (lane & 7) * 4) + (u >> 1) * (3 * 8192)) + j * 512);
    }
    asm volatile("fence.proxy.async.shared::cta;" ::: "memory");
    prof(0, 2, 31);
  } else {
    const int wg = warp - 1;
#pragma unroll 1
    for (int u = 0; u < 32; u++) {
      bar_arrive(BAR_FREE + wg, 160);
      bar_sync(BAR_TILE + wg, 160);
      if (elect_one()) {
        const int n = (u >> 1) * 8 + 2 * f + wg;
        asm volatile("cp.async.bulk.global.shared::cta.bulk_group [%0], [%1], 8192;\ncp.async.bulk.commit_group;\ncp.async.bulk.wait_group 0;"
                     ::"l"(cx.gs->q3 + (n * 2 + (u & 1)) * 512), "r"(cx.sb + SM_H + wg * 8192) : "memory");
        if (u & 1) st_release(&cx.gs->q3_flag[n], epoch);
      }
      __syncwarp();
    }
  }
  bar_arrive(3, 352);
}

__device__ __forceinline__ void aux_consumer(const Ctx& cx, int f, int wg, int cw, int lane) {
  const int r = lane >> 2, c = lane & 3, tid = cw * 32 + lane;
  const uint32_t full = cx.sb + SM_FULL, empty = cx.sb + SM_EMPTY;
  const bool signaller = (tid & 127) == 0;
  auto await = [&](int st) { mbar_wait(full + 8 * (st & 7), (st >> 3) & 1); };
  auto release = [&](int st, int cnt) {
    asm volatile("{\n.reg .pred p;\nsetp.ne.u32 p, %2, 0;\n@p mbarrier.arrive.shared::cta.b64 _, [%0], %1;\n}"
                 ::"r"(empty + 8 * (st & 7)), "r"(cnt), "r"((uint32_t)signaller) : "memory");
  };
  prof(wg, 0);
  {
    const uint32_t lt = ((lane & 7) + (lane >> 4) * 8) * 128 + ((((cw & 3) * 2 + ((lane >> 3) & 1)) ^ (lane & 7)) << 4);
    uint32_t wa[144];
#pragma unroll
    for (int i = 0; i < 3; i++) {
      await(2 * i + wg);
#pragma unroll
      for (int k = 0; k < 12; k++) {
        const int kb = 12 * i + k;
        ldsm4t(cx.sb + (2 * i + wg) * FSTAGE + k * 2048 + lt, wa[4 * kb], wa[4 * kb + 1], wa[4 * kb + 2], wa[4 * kb + 3]);
      }
    }
    bar_sync(1, 256);
#pragma unroll
    for (int i = 0; i < 3; i++) release(2 * i + wg, 2);
    if (wg) bar_arrive(1, 256);
#pragma unroll 1
    for (int st = AST_X; st < AST_F; st += 3) {
      float acc[32];
      await(st);
      await(st + 1);
      await(st + 2);
      bar_sync(1 + wg, 256);
      wg_fence();
#pragma unroll
      for (int kb = 0; kb < 36; kb++) {
        const int i = kb / 12, k = kb % 12;
        mma_n64<0>(acc, wa[4 * kb], wa[4 * kb + 1], wa[4 * kb + 2], wa[4 * kb + 3],
                   mkdesc(cx.sb + ((st + i) & 7) * FSTAGE, 16) + (k >> 2) * 512 + (k & 3) * 2, kb > 0);
        if (k == 11) wg_commit();
      }
      if (st < AST_F - 3 || !wg) bar_arrive(2 - wg, 256);
      wg_wait<1>();
      release(st, 1);
      release(st + 1, 1);
      bar_sync(BAR_FREE + wg, 160);
      wg_wait<0>();
      pin(acc);
      release(st + 2, 1);
#pragma unroll
      for (int k = 0; k < 4; k++)
        stsm4t(cx.sb + SM_H + wg * 8192 + k * 2048 + lt, pack2(acc[8 * k] * SM_SCALE_LOG2, acc[8 * k + 1] * SM_SCALE_LOG2),
               pack2(acc[8 * k + 2] * SM_SCALE_LOG2, acc[8 * k + 3] * SM_SCALE_LOG2),
               pack2(acc[8 * k + 4] * SM_SCALE_LOG2, acc[8 * k + 5] * SM_SCALE_LOG2),
               pack2(acc[8 * k + 6] * SM_SCALE_LOG2, acc[8 * k + 7] * SM_SCALE_LOG2));
      asm volatile("fence.proxy.async.shared::cta;" ::: "memory");
      bar_arrive(BAR_TILE + wg, 160);
    }
    bar_sync(3, 352);
  }
  prof(wg, 3);
#pragma unroll 1
  for (int unit = wg; unit < 27; unit += 2) {
    if (unit >> 1 == 9) {
      asm volatile("fence.proxy.async.shared::cta;" ::: "memory");
      bar_sync(3, 256);
      prof(wg, 4);
    }
    const bool gu = unit < 18;
    float a0[4], a1[4];
#pragma unroll 1
    for (int m = 0; m < 2; m++) {
      float p0[4], p1[4];
      int st = AST_F + (unit >> 1) * 12 + m * 6 + wg;
      uint32_t b = cx.sb + (gu ? SM_XSEL : SM_H + m * 9216);
#pragma unroll 1
      for (int u = 0; u < 3; u++, st += 2, b += 3072) {
        await(st);
        wg_fence();
        const uint64_t da = mkdesc(cx.sb + (st & 7) * FSTAGE, 16), db = mkdesc(b, 16);
#pragma unroll
        for (int k = 0; k < 12; k++) mma_n8((k & 1) ? p1 : p0, da + k * 128, db + (k >> 2) * 64 + (k & 3) * 2, u > 0 || k > 1);
        wg_commit();
        wg_wait<0>();
        release(st, 2);
      }
      pin(p0); pin(p1);
#pragma unroll
      for (int i = 0; i < 4; i++) { a0[i] = a1[i]; a1[i] = p0[i] + p1[i]; }
    }
#pragma unroll
    for (int i = 0; i < 4; i++) {
      const int fl = (cw & 3) * 16 + r + (i >> 1) * 8, tok = 2 * c + (i & 1);
      if (gu) {
        const float h = bfr(silu_f(bfr(a0[i]))) * bfr(a1[i]);
        *(__nv_bfloat16*)(cx.sp + SM_H + unit * 1024 + tok * 128 + (((fl >> 3) ^ tok) << 4) + (fl & 7) * 2) = __float2bfloat16_rn(h);
      } else {
        *at<float>(cx.gs->ypart, ((f * TOPC + tok) * DM + (unit - 18) * 64 + fl) * 4) = a0[i] + a1[i];
      }
    }
  }
  prof(wg, 5);
  bar_sync(3, 256);
  if (tid == 0) red_release(&cx.gs->ycnt);
  prof(wg, 6);
}

struct Maps { CUtensorMap m[9]; };
__global__ void __cluster_dims__(2, 1, 1) __launch_bounds__(THREADS, 1)
fused_kernel(const __nv_bfloat16* __restrict__ x, const __nv_bfloat16* __restrict__ w_r, const __nv_bfloat16* __restrict__ kc,
             const __nv_bfloat16* __restrict__ wo, __nv_bfloat16* __restrict__ out, Scratch* gs,
             const __grid_constant__ Maps maps) {
  const CUtensorMap &tmX = maps.m[0], &tmWq = maps.m[1], &tmK = maps.m[2], &tmV = maps.m[3], &tmWo = maps.m[4];
  extern __shared__ __align__(1024) uint8_t smem_raw[];
  prof(0, 23, 511);
  if (threadIdx.x < 72 && blockIdx.x < N_ATT_CTA)
    asm volatile("prefetch.global.L2 [%0];" ::"l"(at<const void>(x, ((blockIdx.x >> 3) * 128 + (blockIdx.x & 7) * 8) * (DM * 2) + threadIdx.x * 128)));
  Ctx cx;
  cx.sb = smem_u32(smem_raw);
  cx.sp = smem_raw;
  cx.gs = gs;
  cx.rank = blockIdx.x & 1;
  const int warp = __shfl_sync(0xffffffffu, threadIdx.x >> 5, 0);
  const int cluster = blockIdx.x >> 1;
  const bool is_aux = blockIdx.x >= N_ATT_CTA;
  const int c7 = ((cluster - 36) * 37) >> 8;
  const int hs = cluster < 4 ? 4 + cluster : cluster < 36 ? (cluster - 4) >> 3 : 4 + c7;
  const int qb = (cluster < 4 ? 0 : cluster < 36 ? (cluster - 4) & 7 : cluster - 35 - 7 * c7) * 2 + cx.rank;

  extern __shared__ __align__(1024) uint8_t smem_alias[];
  const uint32_t xf = smem_u32(smem_alias) + SM_MISC + warp * 24;
  if (warp == 4 && elect_one()) prefetch_tmap(&tmX);
  if (elect_one()) {
    const uint32_t cnt = (warp > 4 && warp < 8) ? (is_aux ? 2 : 4) : 1;
#pragma unroll
    for (int i = 0; i < 3; i++) mbar_init(xf + 8 * i, cnt);
    asm volatile("fence.proxy.async.shared::cta;" ::: "memory");
    asm volatile("fence.mbarrier_init.release.cluster;" ::: "memory");
  }
  __syncwarp();
  cluster_arrive();
  if (warp == 4 && !is_aux) {
    if (elect_one()) {
#pragma unroll
      for (int i = 0; i < 3; i++) {
        mbar_expect_tx(xf + 8 * i, 24576);
        tma3d(xf - SM_XFULL + SM_X + i * 24576, &tmX, qb * 128, i * 3, xf + 8 * i);
      }
    }
  } else if (warp > 7 && elect_one()) {
    prefetch_tmap(&tmX + (is_aux ? warp - 4 : warp == 8 ? 8 : warp - 8));
  }
  __syncwarp();

  if (warp < 4) {
    asm volatile("setmaxnreg.dec.sync.aligned.u32 24;");
    cluster_wait();
    prof(0, 24, 511);
    if (warp == 0) {
      if (!is_aux) attn_producer(cx, qb, hs, &tmX, &tmK, &tmV, &tmWq, &tmWo);
      else aux_producer(cx, blockIdx.x - N_ATT_CTA, &tmWq, &maps.m[5]);
      prof(0, 25, 511);
    } else if (!is_aux) {
      attn_rows(cx, qb, hs, 3 - warp, read_lane(), &maps.m[8], w_r);
      if (warp == 1) attn_helper(cx, qb, hs, read_lane(), wo, &maps.m[8]);
      else bar_sync(BAR_OA, 352);
      attn_finish8(cx, qb, hs, warp - 1, read_lane(), out);
    } else {
      aux_helper(cx, blockIdx.x - N_ATT_CTA, warp, read_lane());
    }
    __syncwarp();
    cluster_arrive();
    cluster_wait();
    if (threadIdx.x == 32) { dly(cx, 201); dly(cx, 251); }
  } else {
    asm volatile("setmaxnreg.inc.sync.aligned.u32 240;");
    cluster_wait();
    const int cw = warp - 4, wg = cw >> 2;
    if (is_aux) aux_consumer(cx, blockIdx.x - N_ATT_CTA, wg, cw, read_lane());
    else attn_consumer(cx, qb, hs, wg, cw, read_lane(), x, kc, out);
  }
}

typedef CUresult (*EncodeFn)(CUtensorMap*, CUtensorMapDataType, cuuint32_t, void*, const cuuint64_t*, const cuuint64_t*,
                             const cuuint32_t*, const cuuint32_t*, CUtensorMapInterleave, CUtensorMapSwizzle,
                             CUtensorMapL2promotion, CUtensorMapFloatOOBfill);

void encode(EncodeFn fn, CUtensorMap* m, const void* p, int rank, const cuuint64_t* dims, const cuuint64_t* strides,
            const cuuint32_t* box) {
  const cuuint32_t es[5] = {1, 1, 1, 1, 1};
  fn(m, CU_TENSOR_MAP_DATA_TYPE_BFLOAT16, rank, const_cast<void*>(p), dims, strides, box, es, CU_TENSOR_MAP_INTERLEAVE_NONE,
     CU_TENSOR_MAP_SWIZZLE_128B, CU_TENSOR_MAP_L2_PROMOTION_L2_128B, CU_TENSOR_MAP_FLOAT_OOB_FILL_NONE);
}
void encode2d(EncodeFn fn, CUtensorMap* m, const void* p, uint64_t rows, uint64_t cols, uint32_t box_rows) {
  const cuuint64_t dims[2] = {cols, rows}, strides[1] = {cols * 2};
  const cuuint32_t box[2] = {64, box_rows};
  encode(fn, m, p, 2, dims, strides, box);
}

}

extern "C" void kernel_launch(void* const* d_in, const int* in_sizes, int n_in, void* d_out, int out_size) {
  (void)in_sizes; (void)n_in; (void)out_size;
  void* fnp = nullptr;
  cudaDriverEntryPointQueryResult qr;
  cudaGetDriverEntryPoint("cuTensorMapEncodeTiled", &fnp, cudaEnableDefault, &qr);
  EncodeFn fn = (EncodeFn)fnp;
  void* gs = nullptr;
  cudaGetSymbolAddress(&gs, g_scratch);
  Maps maps;
  CUtensorMap &tmX = maps.m[0], &tmWq = maps.m[1], &tmK = maps.m[2], &tmV = maps.m[3], &tmWo = maps.m[4], &tmG = maps.m[5],
              &tmU = maps.m[6], &tmD = maps.m[7];
  encode2d(fn, &tmK, d_in[1], 16 * SEQ, DH, 128);
  encode2d(fn, &tmV, d_in[2], 16 * SEQ, DH, 128);
  encode2d(fn, &tmWq, d_in[3], DM, 4096, 64);
  {
    const cuuint64_t dims[3] = {64, SEQ, 9}, strides[2] = {DM * 2, 128};
    const cuuint32_t box[3] = {64, 64, 3};
    encode(fn, &tmX, d_in[0], 3, dims, strides, box);
  }
  encode2d(fn, &maps.m[8], d_in[0], SEQ, DM, 16);
  encode2d(fn, &tmWo, d_in[4], 4096, DM, 128);
  encode2d(fn, &tmG, d_in[7], DM, FF, 192);
  encode2d(fn, &tmU, d_in[8], DM, FF, 192);
  encode2d(fn, &tmD, d_in[9], FF, DM, 192);
  cudaFuncSetAttribute(fused_kernel, cudaFuncAttributeMaxDynamicSharedMemorySize, SM_TOTAL);
  fused_kernel<<<N_CTA, THREADS, SM_TOTAL>>>((const __nv_bfloat16*)d_in[0], (const __nv_bfloat16*)d_in[6], (const __nv_bfloat16*)d_in[1],
                                            (const __nv_bfloat16*)d_in[4], (__nv_bfloat16*)d_out, (Scratch*)gs, maps);
}
```

```cpp
#include <cuda_runtime.h>
#include <cuda_bf16.h>
#include <cuda.h>
#include <stdint.h>

namespace {

constexpr int SEQ = 2048, DM = 576, DH = 128, FF = 4608, TOPC = 8;
constexpr int N_ATT_CTA = 128, N_CTA = 132;
constexpr int THREADS = 384;

constexpr uint32_t SM_RING = 0;
constexpr uint32_t STAGE = 32768;
constexpr uint32_t SM_SLOT = 131072;
constexpr uint32_t FSTAGE = 24576;
constexpr uint32_t SM_XSEL = 196608;
constexpr uint32_t SM_H = 205824;
constexpr uint32_t SM_MISC = 229376;
constexpr uint32_t SM_FULL = SM_MISC, SM_BAR_MISC = SM_MISC + 64, SM_BAR_XG = SM_MISC + 72, SM_BAR_P8 = SM_MISC + 80, SM_BAR_Q3 = SM_MISC + 88, SM_XFULL = SM_MISC + 96,
                   SM_EMPTY = SM_MISC + 120, SM_BAR_ROWS = SM_MISC + 216, SM_TAG = SM_MISC + 288,
                   SM_ROWS = SM_MISC + 304, SM_BOX8 = SM_MISC + 1024;
constexpr uint32_t SM_TOTAL = SM_MISC + 3072;
constexpr uint32_t SM_X = SM_MISC - 147456;

constexpr int BAR_ROWS = 6, BAR_HELPER = 7, BAR_OA = 8;
constexpr int NST_Q = 18, NST_KV = 128, NST_O = 18;
constexpr uint32_t SL_KE = (NST_Q - 1) & 3, SL_VE = NST_Q & 3, SL_KO = (NST_Q + 1) & 3, SL_VO = (NST_Q + 2) & 3;
#define X_N1 6
#define X_SPLIT 44
#define X_SPLIT3 36
#define X_PARK 5
#define X_C0 24
#define X_C1 32
#define X_C2 56
constexpr float SM_SCALE_LOG2 = 0.08838834764831845f * 1.4426950408889634f;

struct Scratch {
  uint4 part[16 * 64 * 2 * 4 * 128];
  uint4 gate[N_ATT_CTA * 144 * 8];
  uint4 q3[N_ATT_CTA * 1024];
  uint4 xn[SEQ * DM / 8];
  uint32_t key[SEQ];
  float ypart[4 * TOPC * DM];
  uint32_t top[32];
  unsigned launch[160];
  unsigned rows[16 * 32];
  unsigned q3_flag[N_ATT_CTA];
  unsigned ycnt;
};
__device__ __align__(1024) Scratch g_scratch;

__device__ __forceinline__ void prof(int, int, int = 0) {}

__device__ __forceinline__ uint32_t smem_u32(const void* p) { return (uint32_t)__cvta_generic_to_shared(p); }
__device__ __forceinline__ void mbar_init(uint32_t bar, uint32_t cnt) {
  asm volatile("mbarrier.init.shared::cta.b64 [%0], %1;" ::"r"(bar), "r"(cnt) : "memory");
}
__device__ __forceinline__ void mbar_expect_tx(uint32_t bar, uint32_t bytes) {
  asm volatile("mbarrier.arrive.expect_tx.shared::cta.b64 _, [%0], %1;" ::"r"(bar), "r"(bytes) : "memory");
}
__device__ __forceinline__ void mbar_arrive(uint32_t bar) {
  asm volatile("mbarrier.arrive.shared::cta.b64 _, [%0];" ::"r"(bar) : "memory");
}
__device__ __forceinline__ void mbar_arrive_cluster(uint32_t bar_cluster_addr) {
  asm volatile("mbarrier.arrive.shared::cluster.b64 _, [%0];" ::"r"(bar_cluster_addr) : "memory");
}
template <int ID>
__device__ __forceinline__ void mbar_arrive_cluster_now(uint32_t bar_cluster_addr, bool pred, uint32_t zero) {
  asm volatile("{\n.reg .pred p, q;\nsetp.ne.u32 p, %1, 0;\nsetp.eq.u32 q, %2, %3;\n"
               "ARR_LOOP:\n@p mbarrier.arrive.shared::cluster.b64 _, [%0];\n@q bra.uni ARR_LOOP;\n}"
               ::"r"(bar_cluster_addr), "r"((uint32_t)pred), "r"(zero), "n"(ID) : "memory");
}
__device__ __forceinline__ void block_fence(int id, uint32_t zero = blockIdx.y) {
  asm volatile("{\n.reg .pred q;\nsetp.eq.u32 q, %0, %1;\nBF_LOOP:\n@q st.volatile.shared.u32 [%0], %0;\n@q bra.uni BF_LOOP;\n}"
               ::"r"(zero), "r"(id) : "memory");
}
__device__ __forceinline__ bool mbar_test(uint32_t bar, uint32_t parity) {
  uint32_t ok;
  asm volatile("{\n.reg .pred p;\nmbarrier.test_wait.parity.shared::cta.b64 p, [%1], %2;\nselp.u32 %0, 1, 0, p;\n}"
               : "=r"(ok) : "r"(bar), "r"(parity) : "memory");
  return ok;
}
__device__ __forceinline__ void mbar_wait(uint32_t bar, uint32_t parity) {
  asm volatile("{\n.reg .pred p, q;\n.reg .u32 n;\nmov.u32 n, 0;\n"
               "WAIT_LOOP:\nmbarrier.try_wait.parity.shared::cta.b64 p, [%0], %1;\n"
               "add.u32 n, n, 1;\nsetp.lt.u32 q, n, 4194304;\nand.pred q, q, !p;\n@q bra WAIT_LOOP;\n}"
               ::"r"(bar), "r"(parity) : "memory");
}
__device__ __forceinline__ uint32_t mapa(uint32_t addr, uint32_t rank) {
  uint32_t r;
  asm volatile("mapa.shared::cluster.u32 %0, %1, %2;" : "=r"(r) : "r"(addr), "r"(rank));
  return r;
}
__device__ __forceinline__ void cluster_arrive() { asm volatile("barrier.cluster.arrive.relaxed.aligned;" ::: "memory"); }
__device__ __forceinline__ bool elect_one() {
  uint32_t p;
  asm volatile("{\n.reg .pred p;\nelect.sync _|p, 0xffffffff;\nselp.u32 %0, 1, 0, p;\n}" : "=r"(p));
  return p;
}
__device__ __forceinline__ int read_lane() { return threadIdx.x & 31; }
__device__ __forceinline__ void cluster_wait() { asm volatile("barrier.cluster.wait.acquire.aligned;" ::: "memory"); }
__device__ __forceinline__ void bar_sync(int id, int n) { asm volatile("barrier.cta.sync %0, %1;" ::"r"(id), "r"(n) : "memory"); }
__device__ __forceinline__ void bar_arrive(int id, int n) { asm volatile("barrier.cta.arrive %0, %1;" ::"r"(id), "r"(n) : "memory"); }

__device__ __forceinline__ uint64_t policy_evict_first() {
  uint64_t p;
  asm("createpolicy.fractional.L2::evict_first.b64 %0, 1.0;" : "=l"(p));
  return p;
}
__device__ __forceinline__ uint64_t policy_evict_normal() {
  uint64_t p;
  asm("createpolicy.fractional.L2::evict_normal.b64 %0, 1.0;" : "=l"(p));
  return p;
}
__device__ __forceinline__ void tma3d(uint32_t dst, const CUtensorMap* tm, int c1, int c2, uint32_t bar) {
  asm volatile("cp.async.bulk.tensor.3d.shared::cluster.global.mbarrier::complete_tx::bytes [%0], [%1, {%2, %3, %4}], [%5];"
               ::"r"(dst), "l"(tm), "r"(0), "r"(c1), "r"(c2), "r"(bar) : "memory");
}
__device__ __forceinline__ void tma2d(uint32_t dst, const CUtensorMap* tm, int c0, int c1, uint32_t bar) {
  asm volatile("cp.async.bulk.tensor.2d.shared::cluster.global.mbarrier::complete_tx::bytes [%0], [%1, {%2, %3}], [%4];"
               ::"r"(dst), "l"(tm), "r"(c0), "r"(c1), "r"(bar) : "memory");
}
__device__ __forceinline__ void tma2d_stream(uint32_t dst, const CUtensorMap* tm, int c0, int c1, uint32_t bar) {
  asm volatile("{\n.reg .b64 pol;\ncreatepolicy.fractional.L2::evict_first.b64 pol, 1.0;\n"
               "cp.async.bulk.tensor.2d.shared::cluster.global.mbarrier::complete_tx::bytes.L2::cache_hint [%0], [%1, {%2, %3}], [%4], pol;\n}"
               ::"r"(dst), "l"(tm), "r"(c0), "r"(c1), "r"(bar) : "memory");
}
__device__ __forceinline__ void tma2d_prefetch(const CUtensorMap* tm, int c0, int c1) {
  asm volatile("cp.async.bulk.prefetch.tensor.2d.L2.global [%0, {%1, %2}];" ::"l"(tm), "r"(c0), "r"(c1) : "memory");
}
__device__ __forceinline__ void prefetch_l2(const void* p, uint32_t bytes) {
  asm volatile("cp.async.bulk.prefetch.L2.global [%0], %1;" ::"l"(p), "r"(bytes) : "memory");
}
__device__ __forceinline__ void prefetch_tmap(const CUtensorMap* tm) {
  asm volatile("prefetch.tensormap [%0];" ::"l"(tm) : "memory");
}

__device__ __forceinline__ void wg_fence() { asm volatile("wgmma.fence.sync.aligned;" ::: "memory"); }
__device__ __forceinline__ void wg_commit() { asm volatile("wgmma.commit_group.sync.aligned;" ::: "memory"); }
template <int N> __device__ __forceinline__ void wg_wait() { asm volatile("wgmma.wait_group.sync.aligned %0;" ::"n"(N) : "memory"); }

__device__ __forceinline__ uint64_t mkdesc(uint32_t addr, uint32_t lbo_bytes) {
  return (uint64_t)(((addr & 0x3FFFF) >> 4) | ((lbo_bytes >> 4) << 16)) | ((uint64_t)0x40000040u << 32);
}
template <int N> __device__ __forceinline__ void pin(float (&a)[N]) {
#pragma unroll
  for (int i = 0; i < N; i++) asm volatile("" : "+f"(a[i])::"memory");
}
template <int N> __device__ __forceinline__ void pin(uint32_t (&a)[N]) {
#pragma unroll
  for (int i = 0; i < N; i++) asm volatile("" : "+r"(a[i])::"memory");
}

#define F8(d, o) "+f"(d[o]), "+f"(d[o + 1]), "+f"(d[o + 2]), "+f"(d[o + 3]), "+f"(d[o + 4]), "+f"(d[o + 5]), "+f"(d[o + 6]), "+f"(d[o + 7])
#define R32A "%0, %1, %2, %3, %4, %5, %6, %7, %8, %9, %10, %11, %12, %13, %14, %15, %16, %17, %18, %19, %20, %21, %22, %23, %24, %25, %26, %27, %28, %29, %30, %31"
#define R32B "%32, %33, %34, %35, %36, %37, %38, %39, %40, %41, %42, %43, %44, %45, %46, %47, %48, %49, %50, %51, %52, %53, %54, %55, %56, %57, %58, %59, %60, %61, %62, %63"

template <int TB>
__device__ __forceinline__ void mma_n128(float (&d)[64], uint32_t a0, uint32_t a1, uint32_t a2, uint32_t a3, uint64_t db, int acc) {
  asm volatile("{\n.reg .pred p;\nsetp.ne.b32 p, %69, 0;\n"
               "wgmma.mma_async.sync.aligned.m64n128k16.f32.bf16.bf16 {" R32A ", " R32B "}, {%64, %65, %66, %67}, %68, p, 1, 1, %70;\n}\n"
               : F8(d, 0), F8(d, 8), F8(d, 16), F8(d, 24), F8(d, 32), F8(d, 40), F8(d, 48), F8(d, 56)
               : "r"(a0), "r"(a1), "r"(a2), "r"(a3), "l"(db), "r"(acc), "n"(TB));
}
template <int TB>
__device__ __forceinline__ void mma_n128_ss(float (&d)[64], uint64_t da, uint64_t db, int acc) {
  asm volatile("{\n.reg .pred p;\nsetp.ne.b32 p, %66, 0;\n"
               "wgmma.mma_async.sync.aligned.m64n128k16.f32.bf16.bf16 {" R32A ", " R32B "}, %64, %65, p, 1, 1, 0, %67;\n}\n"
               : F8(d, 0), F8(d, 8), F8(d, 16), F8(d, 24), F8(d, 32), F8(d, 40), F8(d, 48), F8(d, 56)
               : "l"(da), "l"(db), "r"(acc), "n"(TB));
}
template <int TB>
__device__ __forceinline__ void mma_n64(float (&d)[32], uint32_t a0, uint32_t a1, uint32_t a2, uint32_t a3, uint64_t db, int acc) {
  asm volatile("{\n.reg .pred p;\nsetp.ne.b32 p, %37, 0;\n"
               "wgmma.mma_async.sync.aligned.m64n64k16.f32.bf16.bf16 {" R32A "}, {%32, %33, %34, %35}, %36, p, 1, 1, %38;\n}\n"
               : F8(d, 0), F8(d, 8), F8(d, 16), F8(d, 24)
               : "r"(a0), "r"(a1), "r"(a2), "r"(a3), "l"(db), "r"(acc), "n"(TB));
}
__device__ __forceinline__ void mma_n8(float (&d)[4], uint64_t da, uint64_t db, int acc) {
  asm volatile("{\n.reg .pred p;\nsetp.ne.b32 p, %6, 0;\n"
               "wgmma.mma_async.sync.aligned.m64n8k16.f32.bf16.bf16 {%0, %1, %2, %3}, %4, %5, p, 1, 1, 1, 0;\n}\n"
               : "+f"(d[0]), "+f"(d[1]), "+f"(d[2]), "+f"(d[3])
               : "l"(da), "l"(db), "r"(acc));
}
__device__ __forceinline__ void hmma_k16(float (&d)[4], uint32_t a0, uint32_t a1, uint32_t a2, uint32_t a3, uint32_t b0, uint32_t b1) {
  asm volatile("mma.sync.aligned.m16n8k16.row.col.f32.bf16.bf16.f32 {%0, %1, %2, %3}, {%4, %5, %6, %7}, {%8, %9}, {%0, %1, %2, %3};"
               : "+f"(d[0]), "+f"(d[1]), "+f"(d[2]), "+f"(d[3]) : "r"(a0), "r"(a1), "r"(a2), "r"(a3), "r"(b0), "r"(b1));
}

__device__ __forceinline__ uint32_t pack2(float lo, float hi) {
  uint32_t r;
  asm("cvt.rn.bf16x2.f32 %0, %1, %2;" : "=r"(r) : "f"(hi), "f"(lo));
  return r;
}
__device__ __forceinline__ float bf_lo(uint32_t w) { return __uint_as_float(w << 16); }
__device__ __forceinline__ float bf_hi(uint32_t w) { return __uint_as_float(w & 0xFFFF0000u); }
__device__ __forceinline__ float bfr(float x) { return __uint_as_float(pack2(0.f, x)); }
__device__ __forceinline__ uint32_t sub2(uint32_t a, uint32_t b) {
  uint32_t r;
  asm("sub.rn.bf16x2 %0, %1, %2;" : "=r"(r) : "r"(a), "r"(b));
  return r;
}
__device__ __forceinline__ uint32_t add2(uint32_t a, uint32_t b) {
  uint32_t r;
  asm("add.rn.bf16x2 %0, %1, %2;" : "=r"(r) : "r"(a), "r"(b));
  return r;
}
__device__ __forceinline__ uint32_t mul2(uint32_t a, uint32_t b) {
  uint32_t r;
  asm("mul.rn.bf16x2 %0, %1, %2;" : "=r"(r) : "r"(a), "r"(b));
  return r;
}
__device__ __forceinline__ uint32_t fma2(uint32_t a, uint32_t b, uint32_t c) {
  uint32_t r;
  asm("fma.rn.bf16x2 %0, %1, %2, %3;" : "=r"(r) : "r"(a), "r"(b), "r"(c));
  return r;
}
__device__ __forceinline__ float ex2(float x) {
  float r;
  asm("ex2.approx.ftz.f32 %0, %1;" : "=f"(r) : "f"(x));
  return r;
}
__device__ __forceinline__ float rcp(float x) {
  float r;
  asm("rcp.approx.ftz.f32 %0, %1;" : "=f"(r) : "f"(x));
  return r;
}
__device__ __forceinline__ float silu_f(float t) { return t * rcp(1.0f + ex2(-1.4426950408889634f * t)); }
__device__ __forceinline__ void lds128(uint32_t a, uint32_t& x, uint32_t& y, uint32_t& z, uint32_t& w) {
  asm volatile("ld.shared.v4.u32 {%0, %1, %2, %3}, [%4];" : "=r"(x), "=r"(y), "=r"(z), "=r"(w) : "r"(a) : "memory");
}
__device__ __forceinline__ void ldsm4(uint32_t a, uint32_t& x, uint32_t& y, uint32_t& z, uint32_t& w) {
  asm volatile("ldmatrix.sync.aligned.m8n8.x4.shared.b16 {%0, %1, %2, %3}, [%4];" : "=r"(x), "=r"(y), "=r"(z), "=r"(w) : "r"(a) : "memory");
}
constexpr uint32_t TAG_BIT = 0x10000;
__device__ __forceinline__ void st_gran(uint4* p, uint32_t x, uint32_t y, uint32_t z, uint32_t w) {
  asm volatile("st.relaxed.gpu.global.v4.b32 [%0], {%1, %2, %3, %4};" ::"l"(p), "r"(x), "r"(y), "r"(z), "r"(w) : "memory");
}
__device__ __forceinline__ void ld_gran(const uint4* p, uint32_t& x, uint32_t& y, uint32_t& z, uint32_t& w) {
  asm volatile("ld.relaxed.gpu.global.v4.b32 {%0, %1, %2, %3}, [%4];" : "=r"(x), "=r"(y), "=r"(z), "=r"(w) : "l"(p) : "memory");
}
__device__ __forceinline__ void ldsm4t(uint32_t a, uint32_t& x, uint32_t& y, uint32_t& z, uint32_t& w) {
  asm volatile("ldmatrix.sync.aligned.m8n8.x4.trans.shared.b16 {%0, %1, %2, %3}, [%4];" : "=r"(x), "=r"(y), "=r"(z), "=r"(w) : "r"(a) : "memory");
}
__device__ __forceinline__ void stsm4t(uint32_t a, uint32_t x, uint32_t y, uint32_t z, uint32_t w) {
  asm volatile("stmatrix.sync.aligned.m8n8.x4.trans.shared.b16 [%0], {%1, %2, %3, %4};" ::"r"(a), "r"(x), "r"(y), "r"(z), "r"(w) : "memory");
}
__device__ __forceinline__ void stsm4(uint32_t a, uint32_t x, uint32_t y, uint32_t z, uint32_t w) {
  asm volatile("stmatrix.sync.aligned.m8n8.x4.shared.b16 [%0], {%1, %2, %3, %4};" ::"r"(a), "r"(x), "r"(y), "r"(z), "r"(w) : "memory");
}
template <class T>
__device__ __forceinline__ T* at(const void* base, uint32_t off) {
  uint64_t r;
  asm("{\n.reg .u32 lo, hi;\nmov.b64 {lo, hi}, %1;\nadd.cc.u32 lo, lo, %2;\naddc.u32 hi, hi, 0;\nmov.b64 %0, {lo, hi};\n}"
      : "=l"(r) : "l"(base), "r"(off));
  return (T*)__cvta_global_to_generic(r);
}
__device__ __forceinline__ void add_granules(float (&red)[32], const uint32_t (&g)[16]) {
#pragma unroll
  for (int i = 0; i < 16; i++) { red[2 * i] += bf_lo(g[i]); red[2 * i + 1] += bf_hi((i & 3) ? g[i] : g[i] & ~TAG_BIT); }
}
__device__ __forceinline__ bool granules_ok(const uint32_t (&g)[16], uint32_t tag) {
  uint32_t u, v;
  asm("lop3.b32 %0, %1, %2, %3, 0x7E;" : "=r"(u) : "r"(g[0]), "r"(g[4]), "r"(tag));
  asm("lop3.b32 %0, %1, %2, %3, 0x7E;" : "=r"(v) : "r"(g[8]), "r"(g[12]), "r"(tag));
  return __all_sync(0xffffffffu, ((u | v) & TAG_BIT) == 0);
}
__device__ __forceinline__ unsigned ld_acquire(const unsigned* p) {
  unsigned v;
  asm volatile("ld.acquire.gpu.global.u32 %0, [%1];" : "=r"(v) : "l"(p) : "memory");
  return v;
}
__device__ __forceinline__ void red_release(unsigned* p) {
  asm volatile("red.release.gpu.global.add.u32 [%0], 1;" ::"l"(p) : "memory");
}
__device__ __forceinline__ void st_release(unsigned* p, unsigned v) {
  asm volatile("st.release.gpu.global.u32 [%0], %1;" ::"l"(p), "r"(v) : "memory");
}

template <int K0, int K1>
__device__ __forceinline__ void ln_fetch(uint32_t (&xa)[144], uint32_t boxes, uint32_t lo) {
#pragma unroll
  for (int k = K0; k < K1; k++) ldsm4(((boxes + lo) ^ ((k & 3) << 5)) + (k >> 2) * 8192, xa[4 * k], xa[4 * k + 1], xa[4 * k + 2], xa[4 * k + 3]);
}
template <int K0, int K1>
__device__ __forceinline__ void ln_sums(const uint32_t (&xa)[144], float (&sm)[4][4]) {
#pragma unroll
  for (int k = K0; k < K1; k++) hmma_k16(sm[k & 3], xa[4 * k], xa[4 * k + 1], xa[4 * k + 2], xa[4 * k + 3], 0x3F803F80u, 0x3F803F80u);
}
__device__ __forceinline__ uint32_t sq8(const uint32_t* a) {
  uint32_t t, u;
  asm("mul.rn.bf16x2 %0, %1, %1;" : "=r"(t) : "r"(a[0]));
  asm("mul.rn.bf16x2 %0, %1, %1;" : "=r"(u) : "r"(a[2]));
#pragma unroll
  for (int i = 4; i < 16; i += 4) {
    asm("fma.rn.bf16x2 %0, %1, %1, %0;" : "+r"(t) : "r"(a[i]));
    asm("fma.rn.bf16x2 %0, %1, %1, %0;" : "+r"(u) : "r"(a[i + 2]));
  }
  return add2(t, u);
}
__device__ __forceinline__ void ln_centre(uint32_t (&xa)[144], int j0, int j1, uint32_t mm0, uint32_t mm1, float& sq0, float& sq1) {
#pragma unroll
  for (int j = 0; j < 72; j += 8)
    if (j >= j0 && j < j1) {
#pragma unroll
      for (int k = j; k < j + 8; k++) {
        xa[2 * k] = sub2(xa[2 * k], mm0);
        xa[2 * k + 1] = sub2(xa[2 * k + 1], mm1);
      }
      const uint32_t t0 = sq8(xa + 2 * j), t1 = sq8(xa + 2 * j + 1);
      sq0 += bf_lo(t0) + bf_hi(t0);
      sq1 += bf_lo(t1) + bf_hi(t1);
    }
}
__device__ __forceinline__ float ln_rstd(float var) {
  float sd;
  asm("sqrt.approx.ftz.f32 %0, %1;" : "=f"(sd) : "f"(bfr(bfr(fmaxf(var, 0.0f)) + 1e-5f)));
  return rcp(bfr(sd));
}
__device__ __forceinline__ uint32_t silu2(uint32_t t) { return pack2(silu_f(bf_lo(t)), silu_f(bf_hi(t))); }
__device__ __forceinline__ float sum8(float v) {
#pragma unroll
  for (int d = 4; d; d >>= 1) v += __shfl_xor_sync(0xffffffffu, v, d);
  return v;
}
__device__ __forceinline__ void await_count(const unsigned* p, unsigned target, unsigned sleep_ns) {
#pragma unroll 1
  for (int n = 0; n < (1 << 18) && __any_sync(0xffffffffu, (int)(ld_acquire(p) - target) < 0); n++) __nanosleep(sleep_ns);
}
__device__ __forceinline__ void bulk_load(uint32_t dst, const void* src, uint32_t bytes, uint32_t bar) {
  asm volatile("cp.async.bulk.shared::cluster.global.mbarrier::complete_tx::bytes [%0], [%1], %2, [%3];"
               ::"r"(dst), "l"(src), "r"(bytes), "r"(bar) : "memory");
}
__device__ __forceinline__ void proxy_fence() { asm volatile("fence.proxy.async;" ::: "memory"); }

template <int V> struct IC { static constexpr int value = V; };

struct Ctx {
  uint32_t sb;
  uint8_t* sp;
  uint32_t rank;
  Scratch* gs;
};

__device__ __forceinline__ void dly(const Ctx&, int) {}
__device__ __forceinline__ void load_box(uint32_t dst, const CUtensorMap* tm, int c0, int c1, uint32_t bar, uint64_t pol) {
  asm volatile("{\n.reg .pred p;\nelect.sync _|p, 0xffffffff;\n"
               "@p cp.async.bulk.tensor.2d.shared::cluster.global.mbarrier::complete_tx::bytes.multicast::cluster.L2::cache_hint"
               " [%0], [%1, {%2, %3}], [%4], %5, %6;\n}"
               ::"r"(dst), "l"(tm), "r"(c0), "r"(c1), "r"(bar), "h"((uint16_t)3), "l"(pol) : "memory");
}
template <int BOXES>
__device__ __forceinline__ void load_stage(uint32_t dst, const CUtensorMap* tm, int c0, int c1, uint32_t bar, uint32_t bytes, uint64_t pol) {
  asm volatile("{\n.reg .pred p;\nelect.sync _|p, 0xffffffff;\n"
               "@p mbarrier.arrive.expect_tx.shared::cta.b64 _, [%4], %7;\n"
               "@p cp.async.bulk.tensor.2d.shared::cluster.global.mbarrier::complete_tx::bytes.multicast::cluster.L2::cache_hint"
               " [%0], [%1, {%2, %3}], [%4], %5, %6;\n}"
               ::"r"(dst), "l"(tm), "r"(c0), "r"(c1), "r"(bar), "h"((uint16_t)3), "l"(pol), "r"(bytes) : "memory");
  if (BOXES == 2) load_box(dst + 8192, tm, c0, c1 + 64, bar, pol);
}
__device__ __forceinline__ void attn_producer(const Ctx& cx, int qb, int hs, const CUtensorMap* tmX, const CUtensorMap* tmK,
                                              const CUtensorMap* tmV, const CUtensorMap* tmWq, const CUtensorMap* tmWo) {
  const uint32_t full = cx.sb + SM_FULL, empty = cx.sb + SM_EMPTY, ring = cx.sb + SM_RING + cx.rank * 16384;
  const uint64_t keep = policy_evict_normal(), last_use = policy_evict_first();
  auto acquire = [&](int st) {
    mbar_wait(empty + 8 * (st & 3), ((st >> 2) ^ ((st & 3) >> 1) ^ 1) & 1);
    if (st > 3) dly(cx, st);
  };
  if (elect_one()) {
#pragma unroll
    for (int j = 0; j < 3; j++) {
      mbar_expect_tx(cx.sb + SM_XFULL + 96 + 8 * j, 24576);
      tma3d(cx.sb + SM_X + 73728 + j * 24576, tmX, qb * 128 + 64, j * 3, cx.sb + SM_XFULL + 96 + 8 * j);
    }
  }
  __syncwarp();
  const int c0 = cx.rank * 64;
#pragma unroll 1
  for (int st = 0; st < NST_Q - 1; st++) {
    const bool half = st >= 10 && st < 13;
    const int i = st - (st < 5 ? 0 : st < 10 ? 5 : half ? 10 : 13), sl = st & 3;
    const int n0 = (hs * 4 + (st < 5 ? 0 : st < 10 ? 2 : half ? 3 : 1)) * DH + (half ? 0 : c0);
    const int k0 = half ? (i < 2 ? 256 * i + 2 * c0 : 448 + c0) : (i < 3 ? 128 * i : 128 * i - 64);
    if (st == 1) mbar_wait(cx.sb + SM_XFULL + 16, 0);
    acquire(st);
    load_stage<1>(ring + sl * STAGE, tmWq, n0, k0, full + 8 * sl, i == 2 ? 16384 : (half && i) ? 24576 : 32768, last_use);
    if (i != 2 && !(half && i && c0)) load_box(ring + sl * STAGE + 8192, tmWq, n0, k0 + 64, full + 8 * sl, last_use);
    if ((st == 3 || st == 4 || st == 8) && elect_one()) {
      if (st != 4) tma2d_prefetch(tmWq, (hs * 4 + 2 - (st >> 3)) * DH + (qb & 1) * 64, (qb >> 1) * 64);
      else if (qb < 9) tma2d_prefetch(tmWq, (hs * 4 + 3) * DH, qb * 64);
    }
    __syncwarp();
  }
  int vrow = 0;
  uint64_t vpol = keep;
#pragma unroll 1
  for (int j = 0; j < 32; j++) {
    const int st = NST_Q - 1 + 4 * j, row = (hs * 2 + (j >> 4)) * SEQ + (j & 7) * 256;
    const uint64_t pol = (j & 8) ? last_use : keep;
    if (j < 7 && qb < 8 && elect_one()) tma2d_prefetch((qb & 4) ? tmV : tmK, (qb & 1) * 64, row + 256 + (qb & 2) * 64);
    __syncwarp();
    if (j == 24) mbar_wait(cx.sb + SM_BAR_Q3, 0);
    acquire(st);
    load_stage<1>(ring + SL_KE * STAGE, tmK, c0, row, full + 8 * SL_KE, 32768, pol);
    acquire(st + 1);
    if (j) load_stage<1>(ring + SL_VE * STAGE, tmV, c0, vrow, full + 8 * SL_VE, 32768, vpol);
    else load_stage<2>(ring + SL_VE * STAGE, tmWq, (hs * 4 + 1) * DH + c0, 448, full + 8 * SL_VE, 32768, last_use);
    vrow = row + 128;
    vpol = pol;
    acquire(st + 2);
    load_stage<1>(ring + SL_KO * STAGE, tmK, c0, vrow, full + 8 * SL_KO, 32768, pol);
    acquire(st + 3);
    load_stage<1>(ring + SL_VO * STAGE, tmV, c0, row, full + 8 * SL_VO, 32768, pol);
  }
  acquire(NST_Q + NST_KV - 1);
  load_stage<1>(ring + SL_KE * STAGE, tmV, c0, vrow, full + 8 * SL_KE, 32768, last_use);
#pragma unroll 1
  for (int u = 0; u < NST_O; u++) {
    const int st = NST_Q + NST_KV + u, sl = st & 3;
    const int blk = u < 4 && cx.rank ? 8 : ((hs + max(u >> 1, 1)) & 7);
    const int head = u < 4 ? u ^ (u >> 1) : ((u & 1) * 2 + cx.rank + 3) & 3;
    acquire(st);
    load_stage<1>(ring + sl * STAGE, tmWo, blk * 64, hs * 512 + head * 128, full + 8 * sl, 32768, last_use);
  }
}

__device__ __forceinline__ uint32_t xn_offset(uint32_t row, int lane) {
  return (row >> 6) * (9 * 8192) + (row & 63) * 128 + ((((lane >> 2) ^ row) & 7) << 4) + (lane & 3) * 4;
}

__device__ __forceinline__ void attn_rows(const Ctx& cx, int qb, int hs, int hw, int lane, const CUtensorMap* tmX16,
                                          const __nv_bfloat16* w_r) {
  extern __shared__ __align__(1024) uint8_t smem_rows[];
  auto box = [&](int blk) { return blk < 8 ? SM_SLOT + 2 * STAGE + 8192 + (blk >> 2) * 16384 + (blk & 3) * 2048 : SM_BOX8; };
  const uint32_t sb = smem_u32(smem_rows);
  if (hw == 0) {
    bar_sync(BAR_HELPER, 160);
    if (elect_one()) {
      mbar_expect_tx(sb + SM_BAR_ROWS, 9 * 2048);
#pragma unroll
      for (int i = 0; i < 9; i++) tma2d(sb + box(i), tmX16, i * 64, qb * 128 + hs * 16, sb + SM_BAR_ROWS);
    }
    __syncwarp();
  }
  uint32_t g = (lane >> 3) * 128 + (((lane ^ (lane >> 3)) & 7) << 4);
  auto next = [&]() {
    g = ((g + 512) & 2047) ^ 64;
    asm volatile("" : "+r"(g));
  };
  float* const part = (float*)(smem_rows + SM_ROWS);
  mbar_wait(sb + SM_BAR_ROWS, 0);
  if (hw == 0) dly(cx, 190);
#pragma unroll 1
  for (int i = 0; i < 4; i++) {
    float a = 0.f, b = 0.f;
#pragma unroll
    for (int j = 0; j < 3; j++) {
      const uint4 v = *(const uint4*)(smem_rows + box(hw * 3 + j) + g);
      const uint32_t w[4] = {v.x, v.y, v.z, v.w};
#pragma unroll
      for (int k = 0; k < 4; k++) {
        a += bf_lo(w[k]) + bf_hi(w[k]);
        b = fmaf(bf_lo(w[k]), bf_lo(w[k]), fmaf(bf_hi(w[k]), bf_hi(w[k]), b));
      }
    }
    a = sum8(a);
    b = sum8(b);
    float* p = part + hw * 16 + (g >> 7);
    p[0] = a;
    p[48] = b;
    next();
  }
  bar_sync(BAR_ROWS, 96);
  if (hw == 0) dly(cx, 191);
  {
    const float* p = part + (lane & 15);
    const float mean = (p[0] + p[16] + p[32]) * (1.0f / DM), rstd = ln_rstd((p[48] + p[64] + p[80]) * (1.0f / DM) - mean * mean);
    const uint32_t mm = pack2(mean, mean), rr = pack2(rstd - bfr(rstd), rstd);
#pragma unroll 1
    for (int u = hw * 12; u < hw * 12 + 12; u++) {
      const int blk = u >> 2;
      uint4* q = (uint4*)(smem_rows + box(blk) + g);
      uint4 v = *q;
      const uint32_t m = __shfl_sync(0xffffffffu, mm, g >> 7), r = __shfl_sync(0xffffffffu, rr, g >> 7);
      const uint32_t hi = __byte_perm(r, 0, 0x3232), lo = __byte_perm(r, 0, 0x1010);
      auto norm = [&](uint32_t w) {
        const uint32_t xc = sub2(w, m);
        return fma2(xc, hi, mul2(xc, lo));
      };
      v = make_uint4(norm(v.x), norm(v.y), norm(v.z), norm(v.w));
      *q = v;
      *at<uint4>(cx.gs->xn + ((qb * 2 + (hs >> 2)) * 9 + blk) * 512 + (hs & 3) * 128, g) = v;
      next();
    }
  }
  bar_sync(BAR_ROWS, 96);
  if (hw == 0) {
    dly(cx, 192);
    if (lane == 0) red_release(&cx.gs->rows[qb * 32]);
    dly(cx, 193);
  }
#pragma unroll 1
  for (int u = hw ? 13 * hw - 3 : 0; u < 13 * hw + 10; u++) {
    const int blk = u >> 2;
    const uint32_t o = (g + (u & 3) * 512) ^ ((u & 1) << 6);
    const uint4 v = *(const uint4*)(smem_rows + box(blk) + o);
    *at<uint4>(cx.gs->gate + (blk < 8 ? (qb * 8 + blk) * 144 + hs * 16 : (qb * 8 + hs) * 144 + 128) * 8, o) =
        make_uint4(silu2(v.x), silu2(v.y), silu2(v.z), silu2(v.w));
  }
  if (hw) dly(cx, 194 + hw);
  __nanosleep(8000);
#pragma unroll 1
  for (int blk = hw * 3; blk < hw * 3 + 3; blk++) {
    const uint4 c = __ldg(at<const uint4>(w_r, blk * 128 + ((g ^ (g >> 3)) & 0x70)));
#pragma unroll 1
    for (int i = 0; i < 4; i++) {
      const uint4 v = *(const uint4*)(smem_rows + box(blk) + g);
      part[blk * 16 + (g >> 7)] =
          sum8(fmaf(bf_lo(v.x), bf_lo(c.x), fmaf(bf_hi(v.x), bf_hi(c.x), fmaf(bf_lo(v.y), bf_lo(c.y), bf_hi(v.y) * bf_hi(c.y)))) +
               fmaf(bf_lo(v.z), bf_lo(c.z), fmaf(bf_hi(v.z), bf_hi(c.z), fmaf(bf_lo(v.w), bf_lo(c.w), bf_hi(v.w) * bf_hi(c.w)))));
      next();
      __nanosleep(700);
    }
  }
  bar_sync(BAR_ROWS, 96);
  if (hw == 0) {
    dly(cx, 194);
    float d = 0.f;
#pragma unroll
    for (int j = 0; j < 9; j++) d += part[j * 16 + (lane & 15)];
    const uint32_t row = qb * 128 + hs * 16 + (lane & 15), b = pack2(0.f, d);
    *at<uint32_t>(cx.gs->key, row * 4) = (b ^ ((int)b < 0 ? 0xFFFF0000u : 0x80000000u)) + 0xFFFF - row;
    __syncwarp();
    if (lane == 0) red_release(&cx.gs->rows[qb * 32 + 1]);
  }
}

constexpr uint32_t SM_XO = SM_SLOT, SM_GO = SM_SLOT + STAGE, SM_P8 = SM_SLOT + 2 * STAGE;
__device__ __forceinline__ void attn_helper(const Ctx& cx, int qb, int hs, int lane, const __nv_bfloat16* wo, const CUtensorMap* tmX16) {
  unsigned e = 0;
  if (lane == 0) {
    e = cx.gs->launch[blockIdx.x];
    cx.gs->launch[blockIdx.x] = e + 1;
  }
  e = __shfl_sync(0xffffffffu, e, 0);
  if (lane == 0) {
    *(uint32_t*)(cx.sp + SM_TAG) = (~e & 1) * TAG_BIT;
    mbar_arrive(cx.sb + SM_BAR_MISC);
  }
  bar_sync(BAR_HELPER, 64);
  await_count(&cx.gs->rows[qb * 32 + 1], 8 * (e + 1), 1000);
  await_count(&cx.gs->q3_flag[qb * 8 + hs], e + 1, 1000);
  proxy_fence();
  if (elect_one()) {
    mbar_expect_tx(cx.sb + SM_BAR_Q3, 16384);
#pragma unroll
    for (int i = 0; i < 2; i++) bulk_load(cx.sb + SM_SLOT + 2 * STAGE + i * 16384 + 8192, cx.gs->q3 + (qb * 16 + hs * 2 + i) * 512, 8192, cx.sb + SM_BAR_Q3);
  }
  __syncwarp();
  bar_sync(BAR_HELPER, 64);
  prefetch_l2(at<const void>(wo, (hs * 512 + qb * 32 + lane) * (DM * 2)), DM * 2);
  await_count(&cx.gs->ycnt, 4 * (e + 1), 500);
  const uint32_t mykey = __ldcg(at<const uint32_t>(cx.gs->top, (lane >> 1) * 4)), myrow = 0xFFFF - (mykey & 0xFFFF);
#pragma unroll 1
  for (uint32_t todo = __ballot_sync(0xffffffffu, lane < 16 && ((lane & 1) ? myrow >> 4 == qb * 8 + hs : myrow >> 7 == qb)); todo; todo &= todo - 1) {
    const int i = __ffs(todo) - 1, blk = (i & 1) ? 8 : hs;
    const uint32_t key = __shfl_sync(0xffffffffu, mykey, i), row = 0xFFFF - (key & 0xFFFF), o = xn_offset(row, lane);
    const uint32_t t = __ldcg(at<const uint32_t>(cx.gs->xn, o + blk * 8192));
    const float2* p = at<const float2>(cx.gs->ypart, ((i >> 1) * DM + blk * 64 + 2 * lane) * 4);
    const float2 y0 = __ldcg(p), y1 = __ldcg(p + TOPC * DM / 2), y2 = __ldcg(p + TOPC * DM), y3 = __ldcg(p + 3 * TOPC * DM / 2);
    const float rs = bfr(rcp(1.0f + ex2(-1.4426950408889634f * bf_hi(key ^ ((int)key < 0 ? 0x80000000u : 0xFFFF0000u)))));
    const uint32_t y = pack2((y0.x + y1.x) + (y2.x + y3.x), (y0.y + y1.y) + (y2.y + y3.y));
    const uint32_t u = pack2(bf_lo(y) * rs, bf_hi(y) * rs);
    *at<uint32_t>(cx.gs->gate, ((qb * 8 + hs) * 144 + ((i & 1) ? 128 + (row & 15) : row & 127)) * 128 + (o & 127)) = silu2(add2(t, u));
  }
  proxy_fence();
  bar_sync(BAR_OA, 352);
  if (elect_one()) {
    const uint32_t bar = cx.sb + SM_BAR_XG;
    mbar_expect_tx(bar, 2 * 144 * 128);
    bulk_load(cx.sb + SM_GO, cx.gs->gate + (qb * 8 + hs) * (144 * 8), 144 * 128, bar);
#pragma unroll 1
    for (int i = 0; i < 9; i++) tma2d_stream(cx.sb + SM_XO + i * 2048, tmX16, i < 8 ? hs * 64 : 512, qb * 128 + (i < 8 ? i : hs) * 16, bar);
  }
  __syncwarp();
  const uint4* src = cx.gs->part + (qb * 64 + 56 + hs) * 1024;
#pragma unroll 1
  for (int n = 0; n < (1 << 16); n++) {
    __nanosleep(n ? 400 : 700);
    uint32_t a, b, d, t;
    ld_gran(at<const uint4>(src, (lane & 7) * 2048 + 2032), a, b, d, t);
    if (__all_sync(0xffffffffu, ((a >> 16) ^ e) & 1)) break;
  }
  if (elect_one()) {
    mbar_expect_tx(cx.sb + SM_BAR_P8, 16384);
    bulk_load(cx.sb + SM_P8, src, 16384, cx.sb + SM_BAR_P8);
  }
  __syncwarp();
}
__device__ __forceinline__ void attn_finish8(const Ctx& cx, int qb, int hs, int hw, int lane, __nv_bfloat16* out) {
  const uint32_t tag = *(const uint32_t*)(cx.sp + SM_TAG);
  mbar_wait(cx.sb + SM_BAR_P8, 0);
  mbar_wait(cx.sb + SM_BAR_XG, 0);
#pragma unroll 1
  for (int g = 2 - hw; g < 4; g += 3) {
    float acc[8] = {0.f, 0.f, 0.f, 0.f, 0.f, 0.f, 0.f, 0.f};
    uint32_t a[4];
#pragma unroll 1
    for (uint32_t o = g * 512 + lane * 16; o < 16384; o += 2048) {
      lds128(cx.sb + SM_P8 + o, a[0], a[1], a[2], a[3]);
#pragma unroll 1
      for (int n = 0; n < (1 << 16) && __any_sync(0xffffffffu, (a[0] & TAG_BIT) != tag); n++)
        ld_gran(at<const uint4>(cx.gs->part, (qb * 64 + 56 + hs) * 16384 + o), a[0], a[1], a[2], a[3]);
      a[0] &= ~TAG_BIT;
#pragma unroll
      for (int j = 0; j < 4; j++) { acc[2 * j] += bf_lo(a[j]); acc[2 * j + 1] += bf_hi(a[j]); }
    }
    asm volatile("" : "+r"(lane));
    const uint32_t tile = cx.sb + SM_XO + (128 + (lane & 15)) * 128 + (((lane >> 4) ^ (lane & 7)) << 4);
    uint32_t b[4];
    ldsm4((tile ^ (g << 5)) + STAGE, a[0], a[1], a[2], a[3]);
    ldsm4(tile ^ (g << 5), b[0], b[1], b[2], b[3]);
    stsm4(tile ^ (g << 5), fma2(pack2(acc[0], acc[1]), a[0], b[0]), fma2(pack2(acc[2], acc[3]), a[1], b[1]),
          fma2(pack2(acc[4], acc[5]), a[2], b[2]), fma2(pack2(acc[6], acc[7]), a[3], b[3]));
  }
  bar_sync(BAR_ROWS, 96);
#pragma unroll 1
  for (int ch = threadIdx.x - 32; ch < 128; ch += 96)
    *at<uint4>(out, ((qb * 128 + hs * 16 + (ch >> 3)) * DM + 512 + (ch & 7) * 8) * 2) =
        *(const uint4*)(cx.sp + SM_XO + (128 + (ch >> 3)) * 128 + (((ch ^ (ch >> 3)) & 7) << 4));
}

constexpr float S_BIAS = 42.625f, S_SCALE = 6782714904576.f;
constexpr float O_BIAS = 53.333332f * 8796093022208.f;
constexpr float SUM_HI = 2.8147498e14f, SUM_LO = 9.0949470e-13f;

__device__ __forceinline__ float offset_for(const float* o, float f) {
  const float m = fmaxf(fmaxf(fmaxf(fabsf(o[0]), fabsf(o[9])), fmaxf(fabsf(o[16]), fabsf(o[25]))),
                        fmaxf(fmaxf(fabsf(o[32]), fabsf(o[41])), fmaxf(fabsf(o[48]), fabsf(o[57]))));
  return __uint_as_float(__float_as_uint(m) & 0x7F800000u) * f;
}
template <int LO, int HI>
__device__ __forceinline__ void softmax_exp(float (&s)[64]) {
#pragma unroll
  for (int i = LO; i < HI; i++) s[i] = ex2(s[i]);
}
__device__ __forceinline__ void row_sums(const uint32_t (&pf)[32], float& l0, float& l1) {
  uint32_t t[16];
#pragma unroll
  for (int i = 0; i < 16; i++) t[i] = add2(pf[(i >> 1) * 4 + (i & 1)], pf[(i >> 1) * 4 + 2 + (i & 1)]);
#pragma unroll
  for (int i = 0; i < 8; i++) t[i] = add2(t[(i >> 1) * 4 + (i & 1)], t[(i >> 1) * 4 + 2 + (i & 1)]);
#pragma unroll
  for (int i = 0; i < 4; i++) t[i] = add2(t[(i >> 1) * 4 + (i & 1)], t[(i >> 1) * 4 + 2 + (i & 1)]);
  t[0] = add2(t[0], t[2]);
  t[1] = add2(t[1], t[3]);
  l0 = (l0 + bf_lo(t[0])) + bf_hi(t[0]);
  l1 = (l1 + bf_lo(t[1])) + bf_hi(t[1]);
}
__device__ __forceinline__ void softmax_redo(uint32_t (&pf)[32], const uint32_t (&q)[32], const __nv_bfloat16* kblk, int lane, float& n0,
                                             float& n1, float& l0, float& l1, float& sc0, float& sc1, float bias) {
  float x0 = -3.0e38f, x1 = -3.0e38f;
#pragma unroll 1
  for (int u = 0; u < 16; u++) {
    const uint32_t* kp = (const uint32_t*)(kblk + ((u & 7) * 16 + (lane >> 2)) * DH) + (lane & 3);
    float d[2][4] = {};
#pragma unroll
    for (int k = 0; k < 16; k++)
      hmma_k16(d[k & 1], q[2 * (k & 14)], q[2 * (k & 14) + 1], q[2 * (k & 14) + 2], q[2 * (k & 14) + 3],
               kp[(k & 1) * 4 * DH + (k >> 1) * 8], kp[(k & 1) * 4 * DH + (k >> 1) * 8 + 4]);
    if (u < 8) {
      x0 = fmaxf(fmaxf(x0, fmaxf(d[0][0], d[0][1])), fmaxf(d[1][0], d[1][1]));
      x1 = fmaxf(fmaxf(x1, fmaxf(d[0][2], d[0][3])), fmaxf(d[1][2], d[1][3]));
      if (u == 7) {
#pragma unroll
        for (int m = 1; m < 4; m <<= 1) {
          x0 = fmaxf(x0, __shfl_xor_sync(0xffffffffu, x0, m));
          x1 = fmaxf(x1, __shfl_xor_sync(0xffffffffu, x1, m));
        }
        x0 = fminf(bias - x0, n0);
        x1 = fminf(bias - x1, n1);
        sc0 = ex2(x0 - n0);
        sc1 = ex2(x1 - n1);
        n0 = x0;
        n1 = x1;
        l0 *= sc0;
        l1 *= sc1;
      }
    } else {
#pragma unroll
      for (int i = 0; i < 28; i++) pf[i] = pf[i + 4];
#pragma unroll
      for (int i = 0; i < 4; i++) {
        const float n = (i & 1) ? n1 : n0;
        pf[28 + i] = pack2(ex2(d[i >> 1][(i & 1) * 2] + n), ex2(d[i >> 1][(i & 1) * 2 + 1] + n));
        ((i & 1) ? l1 : l0) += bf_lo(pf[28 + i]) + bf_hi(pf[28 + i]);
      }
    }
  }
}

#define TH(i)
__device__ __forceinline__ void attn_consumer(const Ctx& cx, int qb, int hs, int wg, int cw, int lane, const __nv_bfloat16* x,
                                              const __nv_bfloat16* kc, __nv_bfloat16* out) {
  const uint32_t full = cx.sb + SM_FULL;
  const uint32_t ring = cx.sb + SM_RING;
  uint32_t lo = ((cw & 3) * 16 + (lane & 15)) * 128 + (((lane >> 4) ^ (lane & 7)) << 4);
  const uint32_t slot = cx.sb + SM_SLOT + wg * 16384;
  auto frag = [&](int sl, int k) { return ((slot + sl * STAGE + lo) ^ ((k & 3) << 5)) + (k >> 2) * 8192; };
  auto park = [&](const float (&a)[64], int sl, int k0, int k1, float f0, float f1, float g0 = -0.f, float g1 = -0.f) {
#pragma unroll
    for (int k = 0; k < 8; k++)
      if (k >= k0 && k < k1)
        stsm4(frag(sl, k), pack2(fmaf(a[8 * k], f0, g0), fmaf(a[8 * k + 1], f0, g0)), pack2(fmaf(a[8 * k + 2], f1, g1), fmaf(a[8 * k + 3], f1, g1)),
              pack2(fmaf(a[8 * k + 4], f0, g0), fmaf(a[8 * k + 5], f0, g0)), pack2(fmaf(a[8 * k + 6], f1, g1), fmaf(a[8 * k + 7], f1, g1)));
  };
  const bool signaller = lane == 0 && (cw & 3) < 2;
  int my_turn = 1 + wg, other_turn = 2 - wg;

  uint32_t pf[32], q[32], empty_c;
#pragma nv_diag_suppress 549
  float o[64], l0, l1, c0 = 0.f, c1 = 0.f;
  {
    uint32_t xa[144];
    float rstd0, rstd1;
    {
      const uint32_t xb = cx.sb + SM_X + wg * 73728, xf = cx.sb + SM_XFULL + wg * 96;
      float sm[4][4] = {};
      prof(wg, 0);
      empty_c = mapa(cx.sb + SM_EMPTY, cw & 1);
      mbar_wait(xf, 0);
      TH(0)
      ln_fetch<0, 12>(xa, xb, lo);
      mbar_wait(xf + 8, 0);
      TH(1)
      ln_fetch<12, 24>(xa, xb, lo);
      ln_sums<0, 12>(xa, sm);
      mbar_wait(xf + 16, 0);
      TH(2)
      ln_fetch<24, 36>(xa, xb, lo);
      ln_sums<12, 36>(xa, sm);
      block_fence(36);
      if (wg) bar_arrive(other_turn, 256);
      block_fence(35);
      TH(3)
      rstd0 = ((sm[0][0] + sm[1][0]) + (sm[2][0] + sm[3][0])) * (1.0f / DM);
      rstd1 = ((sm[0][2] + sm[1][2]) + (sm[2][2] + sm[3][2])) * (1.0f / DM);
    }
    const uint32_t mm0 = pack2(rstd0, rstd0), mm1 = pack2(rstd1, rstd1);
    rstd0 -= bf_lo(mm0);
    rstd1 -= bf_lo(mm1);
    rstd0 *= rstd0 * (-0.25f * DM);
    rstd1 *= rstd1 * (-0.25f * DM);
    auto ln_finish = [&]() {
      rstd0 += __shfl_xor_sync(0xffffffffu, rstd0, 1); rstd1 += __shfl_xor_sync(0xffffffffu, rstd1, 1);
      rstd0 += __shfl_xor_sync(0xffffffffu, rstd0, 2); rstd1 += __shfl_xor_sync(0xffffffffu, rstd1, 2);
      rstd0 = ln_rstd(rstd0 * (1.0f / DM)) * SM_SCALE_LOG2;
      rstd1 = ln_rstd(rstd1 * (1.0f / DM)) * SM_SCALE_LOG2;
    };
    ln_centre(xa, 0, X_C0, mm0, mm1, rstd0, rstd1);
    if (wg == 0) {
      bar_sync(4, 128);
      if (signaller) {
        asm volatile("mbarrier.arrive.shared::cluster.b64 _, [%0], 2;" ::"r"(empty_c + 16) : "memory");
        asm volatile("mbarrier.arrive.shared::cluster.b64 _, [%0], 2;" ::"r"(empty_c + 24) : "memory");
      }
      block_fence(37);
      pin(xa);
      ln_centre(xa, X_C0, X_C1, mm0, mm1, rstd0, rstd1);
    }
    pin(xa);

    extern __shared__ __align__(1024) uint8_t smem_q[];
    const uint32_t ring = smem_u32(smem_q) + SM_RING;
    auto release = [&](int st) { if (signaller) mbar_arrive_cluster(empty_c + 8 * (st & 3)); };
    auto q_stage = [&](float (&acc)[64], int st, int i, int last) {
      mbar_wait(full + 8 * (st & 3), (st >> 2) & 1);
      if (i != (wg ? last : 1)) bar_sync(my_turn, 256);
      wg_fence();
      const uint64_t db = mkdesc(ring + (st & 3) * STAGE, 16384);
#pragma unroll
      for (int k = 0; k < 8; k++) {
        const int kb = (i < 3 ? 8 * i : 8 * i - 4) + k;
        if (i != 2 || k < 4) mma_n128<1>(acc, xa[4 * kb], xa[4 * kb + 1], xa[4 * kb + 2], xa[4 * kb + 3], db + k * 128, kb > 0);
      }
      wg_commit();
      if (i != (wg ? last - 1 : 0)) bar_arrive(other_turn, 256);
    };
    auto q_release = [&](int st, int i, int last) {
      if (i == 1 || i == last) {
        wg_wait<1>();
        if (i == last || !wg) release(st - 1);
      }
      if (i != last - 1 && (i || wg)) {
        wg_wait<0>();
        release(st);
      }
    };
    {
      float (&acc)[64] = o;
#pragma unroll 1
      for (int p = 0; p < 2; p++) {
#pragma unroll
        for (int i = 0; i < 5; i++) {
          q_stage(acc, 5 * p + i, i, 4);
          if (p == 0 && i != 3) {
            if (i == 0 && wg) bar_arrive(BAR_HELPER, 160);
            if ((wg || i) && i < 3) ln_centre(xa, i == 0 ? X_C0 : i == 1 ? X_C1 : X_C2, i == 0 ? X_C1 : i == 1 ? X_C2 : 72, mm0, mm1, rstd0, rstd1);
            if (i == 4) ln_finish();
            pin(xa);
          }
          q_release(5 * p + i, i, 4);
        }
        pin(acc);
#pragma unroll
        for (int k = 0; k < 8; k += 2) {
          park(acc, p, k, k + 2, rstd0, rstd1);
          if (k < 6) block_fence(40 + k);
        }
      }
    }
    {
      float (&h)[32] = *(float (*)[32])&o[0];
#pragma unroll
      for (int i = 0; i < 3; i++) {
        const uint32_t sl = (10 + i) & 3;
        mbar_wait(full + 8 * sl, ((10 + i) >> 2) & 1);
        if (i != (wg ? 2 : 1)) bar_sync(my_turn, 256);
        wg_fence();
#pragma unroll
        for (int k = 0; k < 16 - 4 * i; k++) {
          const int kb = (i == 2 ? 28 : 16 * i) + k;
          const uint64_t db = mkdesc(ring + sl * STAGE, 16) + (i == 2 && k >= 4 ? k + 4 : k) * 128;
          mma_n64<1>(h, xa[4 * kb], xa[4 * kb + 1], xa[4 * kb + 2], xa[4 * kb + 3], db, kb > 0);
        }
        wg_commit();
        if (i != (wg ? 1 : 0)) bar_arrive(other_turn, 256);
        q_release(10 + i, i, 2);
      }
      pin(h);
      park(o, 2, 0, 2, rstd0, rstd1);
      block_fence(49);
      park(o, 2, 2, 4, rstd0, rstd1);
    }
#pragma unroll
    for (int i = 0; i < 4; i++) {
      q_stage(o, 13 + i, i, 3);
      q_release(13 + i, i, 3);
    }
    prof(wg, 6);
#pragma unroll
    for (int i = 0; i < 32; i++) pf[i] = xa[112 + i];
    l0 = 0.25f * rcp(rstd0);
    l1 = 0.25f * rcp(rstd1);
  }

  uint32_t oa[96];
  const uint32_t zero = __shfl_sync(0xffffffffu, blockIdx.y, lane);
  my_turn = __shfl_sync(0xffffffffu, my_turn, lane);
  other_turn = __shfl_sync(0xffffffffu, other_turn, lane);
  lo = __shfl_sync(0xffffffffu, lo, lane);
  {
    float s[64], n0 = 0.f, n1 = 0.f;
    float lp0, lp1;
    float i0 = 0.f, i1 = 0.f;
    float hi = 0.f;
    bool redo;
    auto turn = [&](int it, auto kc_) -> bool {
      constexpr int KIND = decltype(kc_)::value;
      constexpr uint32_t slk = KIND == 1 ? SL_KO : SL_KE, slv = KIND == 1 ? SL_VO : SL_VE, slkn = KIND == 1 ? SL_KE : SL_KO;
      constexpr int SPLIT = KIND == 3 ? X_SPLIT3 : X_SPLIT, PARK1 = X_PARK;
      const uint32_t par = ((it + NST_Q / 2) >> 1) & 1;
      const int hsl = max((it >> 4) - 1, 0);
      const bool second = KIND == 1 && (it & 15) == 1;
      const uint64_t dk = mkdesc(ring + slk * STAGE, 16), dv = mkdesc(ring + slv * STAGE, 16384);
      auto qk = [&](int k, int acc) {
        if (KIND == 3) mma_n128_ss<0>(s, mkdesc(slot + hsl * STAGE, 16) + (k >> 2) * 512 + (k & 3) * 2, dk + (k >> 2) * 1024 + (k & 3) * 2, acc);
        else mma_n128<0>(s, q[4 * k], q[4 * k + 1], q[4 * k + 2], q[4 * k + 3], dk + (k >> 2) * 1024 + (k & 3) * 2, acc);
      };
      auto pv = [&]() {
#pragma unroll
        for (int k = 0; k < 8; k++)
          mma_n128<1>(o, pf[4 * k], pf[4 * k + 1], pf[4 * k + 2], pf[4 * k + 3], dv + k * 128, k > 0 || !second);
        wg_commit();
      };
      if (KIND == 2 && (it & 15) == 2) {
        n0 += S_BIAS;
        n1 += S_BIAS;
        l0 *= S_SCALE;
        l1 *= S_SCALE;
        hi = SUM_HI * S_SCALE;
        asm volatile("" : "+f"(n0), "+f"(n1), "+f"(l0), "+f"(l1), "+f"(hi)::"memory");
      }
      lp0 = l0; lp1 = l1;
#define TS(i)
      {
        TS(0)
        if (KIND == 3) {
          asm volatile("fence.proxy.async.shared::cta;" ::: "memory");
          const float t0 = lp0 + __shfl_xor_sync(0xffffffffu, lp0, 1), t1 = lp1 + __shfl_xor_sync(0xffffffffu, lp1, 1);
          i0 = rcp(t0 + __shfl_xor_sync(0xffffffffu, t0, 2));
          i1 = rcp(t1 + __shfl_xor_sync(0xffffffffu, t1, 2));
          asm volatile("" : "+f"(i0), "+f"(i1)::"memory");
          block_fence(31, zero);
#pragma unroll
          for (int k = 0; k < X_N1; k++) ldsm4(frag(hsl, k), q[4 * k], q[4 * k + 1], q[4 * k + 2], q[4 * k + 3]);
        }
        if (KIND != 3) pin(q);
        pin(pf); pin(o);
        if (KIND != 3 && !second) {
#pragma unroll
          for (int i = 0; i < 64; i++) s[i] = ((i & 2) ? n1 : n0) + (i + 1) * 1e-30f;
        }
        if (KIND != 3) pin(s);
        bar_sync(my_turn, 256);
        wg_fence();
#pragma unroll
        for (int k = 0; k < 8; k++) qk(k, k > 0 || (KIND != 3 && !second));
        wg_commit();
        TS(2)
        mbar_wait(full + 8 * slv, par);
        if (KIND == 2 && (it & 15) == 2) {
          c0 = offset_for(o, O_BIAS);
          c1 = offset_for(o + 2, O_BIAS);
          asm volatile("" : "+f"(c0), "+f"(c1)::"memory");
          wg_fence();
        }
        if (KIND == 1 && (it & 13) == 1) {
          if (second) {
            park(o, hsl, PARK1, 8, i0, i1, c0, c1);
          } else {
#pragma unroll
            for (int i = 0; i < 64; i++) o[i] = fmaf(o[i], S_SCALE, (i & 2) ? c1 : c0);
            pin(o);
          }
          wg_fence();
        }
        if (KIND == 3) {
#pragma unroll
          for (int k = X_N1; k < 8; k++) ldsm4(frag(hsl, k), q[4 * k], q[4 * k + 1], q[4 * k + 2], q[4 * k + 3]);
          block_fence(32, zero);
        }
        TS(3)
        pv();
        bar_arrive(other_turn, 256);
        TS(4)
        wg_wait<1>();
      }
      pin(s);
      mbar_arrive_cluster_now<10 * KIND + 3>(empty_c + 8 * slk, signaller, zero);
      TS(5)
      if (KIND == 3) {
        n0 = n1 = l0 = l1 = 0.f;
        hi = SUM_HI;
        c0 *= -i0;
        c1 *= -i1;
      }
      softmax_exp<0, SPLIT>(s);
      pin(s);
      block_fence(10 * KIND + 4, zero);
      TS(6)
      wg_wait<0>();
      pin(o); pin(pf);
      mbar_arrive_cluster_now<10 * KIND + 5>(empty_c + 8 * slv, signaller, zero);
      TS(7)
      const bool kready = mbar_test(KIND == 1 && it == 63 ? cx.sb + SM_BAR_XG : full + 8 * slkn, KIND == 1 && it == 63 ? 0 : par);
      softmax_exp<SPLIT, 64>(s);
#pragma unroll
      for (int i = 0; i < 32; i++) pf[i] = pack2(s[2 * i], s[2 * i + 1]);
      row_sums(pf, l0, l1);
      if (KIND == 3) {
        park(o, hsl, 0, PARK1, i0, i1, c0, c1);
        if (it) prof(wg, 6 + (it >> 4));
        if (it >= 32 && cw == 0) bar_arrive(BAR_HELPER, 64);
      }
      redo = !(l0 + l1 <= hi) || (KIND == 3 && fminf(l0, l1) < SUM_LO);
      const bool leave = __any_sync(0xffffffffu, redo || !kready);
      return leave;
    };
    int it = -1;
#pragma unroll 1
    while (true) {
      mbar_wait(full + 8 * ((it & 1) ? SL_KE : SL_KO), ((it + NST_Q / 2) >> 1) & 1);
      it++;
      bool odd = it & 1;
#pragma unroll 1
      while (true) {
        if (odd) {
          if (turn(it, IC<1>())) break;
          it++;
        }
        odd = true;
        if (it & 15) {
          if (turn(it, IC<2>())) break;
        } else {
          if (turn(it, IC<3>())) break;
        }
        it++;
      }
      if (__any_sync(0xffffffffu, redo)) {
        const int j = it & 15;
        float sc0 = 1.f, sc1 = 1.f;
        if (j == 0) n0 = n1 = 3.0e38f;
        l0 = j ? lp0 : 0.f;
        l1 = j ? lp1 : 0.f;
        softmax_redo(pf, q, kc + (size_t)((hs * 2 + (it >> 5)) * SEQ + j * 128) * DH, lane, n0, n1, l0, l1, sc0, sc1, j > 1 ? S_BIAS : 0.f);
        if (j == 0) {
          sc0 = sc1 = 1.f;
          hi = -1.f;
        }
        c0 *= sc0;
        c1 *= sc1;
#pragma unroll
        for (int i = 0; i < 16; i++) { o[4 * i] *= sc0; o[4 * i + 1] *= sc0; o[4 * i + 2] *= sc1; o[4 * i + 3] *= sc1; }
      }
      if (it == 63) break;
    }
  }

#define TE(i) {}
  {
    constexpr int ST0 = NST_Q + NST_KV;
    float acc[32], red[32], first[32];
    uint32_t tag;
    uint4* xch;
    auto await = [&](int st) { mbar_wait(full + 8 * (st & 3), (st >> 2) & 1); };
    auto release = [&](int st) { if (signaller) mbar_arrive_cluster(empty_c + 8 * (st & 3)); };
    auto unpark = [&](int h, int k0, int k1) {
#pragma unroll
      for (int k = 0; k < 8; k++)
        if (k >= k0 && k < k1) ldsm4(frag(h, k), oa[32 * h + 4 * k], oa[32 * h + 4 * k + 1], oa[32 * h + 4 * k + 2], oa[32 * h + 4 * k + 3]);
    };
    {
      float ar[64];
      asm volatile("fence.proxy.async.shared::cta;" ::: "memory");
      await(ST0 - 1);
      unpark(1, 0, 4);
      bar_sync(my_turn, 256);
      pin(pf); pin(o);
      wg_fence();
#pragma unroll
      for (int k = 0; k < 8; k++)
        mma_n128<1>(o, pf[4 * k], pf[4 * k + 1], pf[4 * k + 2], pf[4 * k + 3], mkdesc(ring + SL_KE * STAGE, 16384) + k * 128, 1);
      wg_commit();
      block_fence(66, zero);
      l0 += __shfl_xor_sync(0xffffffffu, l0, 1); l1 += __shfl_xor_sync(0xffffffffu, l1, 1);
      l0 += __shfl_xor_sync(0xffffffffu, l0, 2); l1 += __shfl_xor_sync(0xffffffffu, l1, 2);
      float f0 = rcp(l0), f1 = rcp(l1);
      asm volatile("" : "+f"(f0), "+f"(f1)::"memory");
      await(ST0);
      unpark(1, 4, 8);
      block_fence(61, zero);
#pragma unroll
      for (int k = 0; k < 8; k++) mma_n128_ss<1>(ar, mkdesc(slot, 16) + (k >> 2) * 512 + (k & 3) * 2, mkdesc(ring + (ST0 & 3) * STAGE, 16384) + k * 128, k > 0);
      wg_commit();
      bar_arrive(other_turn, 256);
      wg_wait<1>();
      pin(o); pin(pf);
      mbar_arrive_cluster_now<62>(empty_c + 8 * SL_KE, signaller, zero);
      c0 *= -f0;
      c1 *= -f1;
#pragma unroll
      for (int i = 0; i < 16; i++) {
        pf[2 * i] = pack2(fmaf(o[4 * i], f0, c0), fmaf(o[4 * i + 1], f0, c0));
        pf[2 * i + 1] = pack2(fmaf(o[4 * i + 2], f1, c1), fmaf(o[4 * i + 3], f1, c1));
      }
      pin(pf);
      prof(wg, 10);
#pragma unroll
      for (int u = 1; u < 4; u++) {
        await(ST0 + u);
        wg_wait<0>();
        release(ST0 + u - 1);
        bar_sync(my_turn, 256);
        wg_fence();
#pragma unroll
        for (int k = 0; k < 8; k++) {
          const uint32_t* a = (u == 1 ? oa + 32 : u == 2 ? pf : oa + 64) + 4 * k;
          mma_n128<1>(ar, a[0], a[1], a[2], a[3], mkdesc(ring + ((ST0 + u) & 3) * STAGE, 16384) + k * 128, 1);
        }
        wg_commit();
        bar_arrive(other_turn, 256);
        if (u < 3) {
          block_fence(62 + u, zero);
          unpark(u == 1 ? 2 : 0, 0, 8);
        }
      }
      mbar_wait(cx.sb + SM_BAR_MISC, 0);
      tag = *(const volatile uint32_t*)(cx.sp + SM_TAG);
      xch = at<uint4>(cx.gs->part, (qb << 20) + lane * 16 + zero);
      tag = __shfl_sync(0xffffffffu, tag, lane);
      await(ST0 + 4);
      wg_wait<0>();
      release(ST0 + 3);
      pin(ar);
#pragma unroll
      for (int i = 0; i < 32; i++) { first[i] = ar[i]; red[i] = ar[32 + i]; }
    }
    auto send = [&](const float (&v)[32], int dst, int idx) {
      uint4* p = at<uint4>(xch, (dst * 8 + idx) * 2048);
#pragma unroll
      for (int i = 0; i < 4; i++)
        st_gran(p + i * 32, (pack2(v[8 * i], v[8 * i + 1]) & ~TAG_BIT) | tag, pack2(v[8 * i + 2], v[8 * i + 3]),
                pack2(v[8 * i + 4], v[8 * i + 5]), pack2(v[8 * i + 6], v[8 * i + 7]));
    };
    send(first, ((hs + 1) & 7) * 7, cw);
    int nrx = 1;
    auto half_step = [&](int s, auto hc, bool arrive) {
      constexpr int h = decltype(hc)::value;
      const int st = ST0 + 2 * s + h;
      const uint64_t db = mkdesc(ring + (st & 3) * STAGE, 16);
      bar_sync(my_turn, 256);
      if (h == 0) pin(pf);
#pragma unroll
      for (int i = 32 * h; i < 32 + 64 * h; i++) asm volatile("" : "+r"(oa[i])::"memory");
      wg_fence();
#pragma unroll
      for (int k = 0; k < 16; k++) {
        const int kb = h * 16 + k - 8;
        if (kb >= 0) mma_n64<1>(acc, oa[4 * kb], oa[4 * kb + 1], oa[4 * kb + 2], oa[4 * kb + 3], db + k * 128, 1);
        else mma_n64<1>(acc, pf[4 * k], pf[4 * k + 1], pf[4 * k + 2], pf[4 * k + 3], db + k * 128, k > 0);
      }
      wg_commit();
      if (arrive) bar_arrive(other_turn, 256);
    };
    auto source = [&](int n) { return at<const uint4>(xch, ((hs * 7 + n - 1) * 8 + cw) * 2048); };
    auto fetch = [&](uint32_t (&g)[16], const uint4* p) {
#pragma unroll
      for (int i = 0; i < 4; i++) ld_gran(p + i * 32, g[4 * i], g[4 * i + 1], g[4 * i + 2], g[4 * i + 3]);
    };
    uint32_t g[16];
#pragma unroll 1
    for (int s = 2; s < 8; s++) {
      const int st = ST0 + 2 * s;
      half_step(s, IC<0>(), true);
      if (s == 2) {
        bar_arrive(BAR_OA, 352);
        send(red, 56 + cw, hs);
#pragma unroll
        for (int i = 0; i < 32; i++) red[i] = 0.f;
      }
      await(st + 1);
      if (s > 3 && granules_ok(g, tag)) { add_granules(red, g); nrx++; }
      wg_wait<0>();
      if (s < 7) release(st);
      if (s > 2) fetch(g, source(nrx));
      half_step(s, IC<1>(), true);
      await(st + 2);
      wg_wait<0>();
      if (s < 7) release(st + 1);
      pin(acc);
      if (s == 7) prof(wg, 19);
      send(acc, ((hs + s) & 7) * 7 + s - 1, cw);
    }
    TE(1)
    uint32_t xv[16], gt[16];
    {
      const int s = 8;
      uint32_t g2[16];
      half_step(s, IC<0>(), true);
      TE(2)
      await(NST_Q + NST_KV + NST_O - 1);
      cluster_arrive();
      mbar_wait(cx.sb + SM_BAR_XG, 0);
      const uint32_t tile = cx.sb + SM_XO + wg * 8192 + lo;
      if (granules_ok(g, tag)) { add_granules(red, g); nrx++; }
      fetch(g, source(nrx));
      block_fence(58, zero);
      wg_wait<0>();
      TE(3)
#pragma unroll
      for (int k = 0; k < 4; k++) ldsm4((tile ^ (k << 5)) + STAGE, gt[4 * k], gt[4 * k + 1], gt[4 * k + 2], gt[4 * k + 3]);
      half_step(s, IC<1>(), wg == 0);
      TE(4)
      block_fence(56, zero);
      const bool ok = granules_ok(g, tag);
      block_fence(57, zero + ok * 1000);
      const uint4* src = source(7);
      fetch(g2, src);
#pragma unroll
      for (int k = 0; k < 4; k++) ldsm4(tile ^ (k << 5), xv[4 * k], xv[4 * k + 1], xv[4 * k + 2], xv[4 * k + 3]);
      if (ok) { add_granules(red, g); nrx++; }
      TE(5)
      block_fence(59, zero);
      wg_wait<0>();
      pin(acc);
      TE(6)
#pragma unroll
      for (int i = 0; i < 32; i++) red[i] += acc[i];
      pin(red);
      TE(7)
      int n = 7;
#pragma unroll 1
      for (int spins = 0; spins < (1 << 16); spins++) {
        if (granules_ok(g2, tag)) {
          add_granules(red, g2);
          if (--n < nrx) {
            break;
          }
          src -= 1024;
        }
        fetch(g2, src);
      }
      TE(8)
    }
    prof(wg, 20);
    TE(9)
    const uint32_t ot = ring + ((ST0 + NST_O) & 3) * STAGE + cw * (16 * 144);
    uint32_t ow[16];
#pragma unroll
    for (int i = 0; i < 16; i++) ow[i] = fma2(pack2(red[2 * i], red[2 * i + 1]), gt[i], xv[i]);
#pragma unroll
    for (int i = 0; i < 4; i++)
      stsm4(ot + (lane & 15) * 144 + (2 * i + (lane >> 4)) * 16, ow[4 * i], ow[4 * i + 1], ow[4 * i + 2], ow[4 * i + 3]);
    __syncwarp();
#pragma unroll
    for (int i = 0; i < 4; i++) {
      uint4 v;
      lds128(ot + (i * 4 + (lane >> 3)) * 144 + (lane & 7) * 16, v.x, v.y, v.z, v.w);
      at<uint4>(out, ((qb * 128 + cw * 16 + (lane >> 3)) * DM + hs * 64 + (lane & 7) * 8) * 2)[i * (4 * DM / 8)] = v;
    }
    TE(10)
    prof(wg, 22);
  }
}

constexpr int AST_X = 6, AST_F = AST_X + 96;
__device__ __forceinline__ void aux_producer(const Ctx& cx, int f, const CUtensorMap* tmWq, const CUtensorMap* tmG) {
  const uint32_t full = cx.sb + SM_FULL, empty = cx.sb + SM_EMPTY;
  __nanosleep(3000);
  if (elect_one()) {
#pragma unroll 1
    for (int st = 0; st < AST_X; st++) {
      mbar_expect_tx(full + 8 * st, FSTAGE);
#pragma unroll
      for (int i = 0; i < 3; i++)
        tma2d_stream(cx.sb + st * FSTAGE + i * 8192, tmWq, (2 * f + (st & 1)) * 512 + 448, (st >> 1) * 192 + i * 64, full + 8 * st);
    }
  }
  __syncwarp();
  mbar_wait(cx.sb + SM_BAR_MISC, 0);
  proxy_fence();
  int st = AST_X;
#pragma unroll 1
  for (; st < AST_F; st++) {
    const uint32_t sl = st & 7;
    mbar_wait(empty + 8 * sl, ((st >> 3) & 1) ^ 1);
    if (elect_one()) {
      mbar_expect_tx(full + 8 * sl, FSTAGE);
      bulk_load(cx.sb + sl * FSTAGE, cx.gs->xn + (st - AST_X) * (FSTAGE / 16), FSTAGE, full + 8 * sl);
    }
    __syncwarp();
  }
#pragma unroll 1
  for (int pair = 0; pair < 14; pair++) {
#pragma unroll 1
    for (int u = 0; u < 12; u++, st++) {
      const uint32_t sl = st & 7;
      const int unit = pair * 2 + (u & 1), k = u >> 1;
      if (unit == 27) continue;
      const bool gu = pair < 9;
      mbar_wait(empty + 8 * sl, ((st >> 3) & 1) ^ 1);
      if (elect_one()) {
        mbar_expect_tx(full + 8 * sl, FSTAGE);
        tma2d_stream(cx.sb + sl * FSTAGE, tmG + (gu ? k >= 3 : 2), gu ? f * 1152 + unit * 64 : (unit - 18) * 64,
                     gu ? (k >= 3 ? k - 3 : k) * 192 : f * 1152 + k * 192, full + 8 * sl);
      }
      __syncwarp();
    }
  }
}

constexpr int BAR_FREE = 4, BAR_TILE = 6;
__device__ __forceinline__ void aux_helper(const Ctx& cx, int f, int warp, int lane) {
  unsigned epoch = 0;
  if (lane == 0) epoch = cx.gs->launch[blockIdx.x] + 1;
  epoch = __shfl_sync(0xffffffffu, epoch, 0);
  bar_sync(BAR_OA, 96);
  if (warp == 3) {
    if (lane == 0) cx.gs->launch[blockIdx.x] = epoch;
    await_count(at<const unsigned>(cx.gs->rows, (lane & 15) * 128), 8 * epoch, 200);
    if (lane == 0) mbar_arrive(cx.sb + SM_BAR_MISC);
    prof(0, 1, 31);
    await_count(at<const unsigned>(cx.gs->rows, (lane & 15) * 128 + 4), 8 * epoch, 500);
    proxy_fence();
    if (elect_one()) {
      mbar_expect_tx(cx.sb + SM_BAR_ROWS, SEQ * 4);
      bulk_load(cx.sb + SM_XSEL, cx.gs->key, SEQ * 4, cx.sb + SM_BAR_ROWS);
    }
    __syncwarp();
    mbar_wait(cx.sb + SM_BAR_ROWS, 0);
    uint32_t bound = 0xFFFFFFFFu, mine = 0;
#pragma unroll 1
    for (int k = 0; k < TOPC; k++) {
      uint32_t m = 0;
#pragma unroll 2
      for (int i = 0; i < 16; i++) {
        const uint4 v = *(const uint4*)(cx.sp + SM_XSEL + lane * 16 + i * 512);
        m = max(max(m, v.x <= bound ? v.x : 0), max(v.y <= bound ? v.y : 0, max(v.z <= bound ? v.z : 0, v.w <= bound ? v.w : 0)));
      }
      m = __reduce_max_sync(0xffffffffu, m);
      bound = m - 1;
      if (lane == k) mine = m;
    }
    if (f == 0 && lane < TOPC) *at<uint32_t>(cx.gs->top, lane * 4) = mine;
#pragma unroll 1
    for (int u = 0; u < 6; u++) {
      const int k = (u & 1) * 4 + (lane >> 3);
      const uint32_t row = ~__shfl_sync(0xffffffffu, mine, k) & (SEQ - 1);
#pragma unroll
      for (int j = 0; j < 3; j++)
        *(uint4*)(cx.sp + SM_XSEL + ((u >> 1) * 3 + j) * 1024 + k * 128 + (((lane ^ k) & 7) << 4)) =
            __ldcg(at<const uint4>(cx.gs->xn, xn_offset(row, (lane & 7) * 4) + (u >> 1) * (3 * 8192)) + j * 512);
    }
    asm volatile("fence.proxy.async.shared::cta;" ::: "memory");
    prof(0, 2, 31);
  } else {
    const int wg = warp - 1;
#pragma unroll 1
    for (int u = 0; u < 32; u++) {
      bar_arrive(BAR_FREE + wg, 160);
      bar_sync(BAR_TILE + wg, 160);
      if (elect_one()) {
        const int n = (u >> 1) * 8 + 2 * f + wg;
        asm volatile("cp.async.bulk.global.shared::cta.bulk_group [%0], [%1], 8192;\ncp.async.bulk.commit_group;\ncp.async.bulk.wait_group 0;"
                     ::"l"(cx.gs->q3 + (n * 2 + (u & 1)) * 512), "r"(cx.sb + SM_H + wg * 8192) : "memory");
        if (u & 1) st_release(&cx.gs->q3_flag[n], epoch);
      }
      __syncwarp();
    }
  }
  bar_arrive(3, 352);
}

__device__ __forceinline__ void aux_consumer(const Ctx& cx, int f, int wg, int cw, int lane) {
  const int r = lane >> 2, c = lane & 3, tid = cw * 32 + lane;
  const uint32_t full = cx.sb + SM_FULL, empty = cx.sb + SM_EMPTY;
  const bool signaller = (tid & 127) == 0;
  auto await = [&](int st) { mbar_wait(full + 8 * (st & 7), (st >> 3) & 1); };
  auto release = [&](int st, int cnt) {
    asm volatile("{\n.reg .pred p;\nsetp.ne.u32 p, %2, 0;\n@p mbarrier.arrive.shared::cta.b64 _, [%0], %1;\n}"
                 ::"r"(empty + 8 * (st & 7)), "r"(cnt), "r"((uint32_t)signaller) : "memory");
  };
  prof(wg, 0);
  {
    const uint32_t lt = ((lane & 7) + (lane >> 4) * 8) * 128 + ((((cw & 3) * 2 + ((lane >> 3) & 1)) ^ (lane & 7)) << 4);
    uint32_t wa[144];
#pragma unroll
    for (int i = 0; i < 3; i++) {
      await(2 * i + wg);
#pragma unroll
      for (int k = 0; k < 12; k++) {
        const int kb = 12 * i + k;
        ldsm4t(cx.sb + (2 * i + wg) * FSTAGE + k * 2048 + lt, wa[4 * kb], wa[4 * kb + 1], wa[4 * kb + 2], wa[4 * kb + 3]);
      }
    }
    bar_sync(1, 256);
#pragma unroll
    for (int i = 0; i < 3; i++) release(2 * i + wg, 2);
    if (wg) bar_arrive(1, 256);
#pragma unroll 1
    for (int st = AST_X; st < AST_F; st += 3) {
      float acc[32];
      await(st);
      await(st + 1);
      await(st + 2);
      bar_sync(1 + wg, 256);
      wg_fence();
#pragma unroll
      for (int kb = 0; kb < 36; kb++) {
        const int i = kb / 12, k = kb % 12;
        mma_n64<0>(acc, wa[4 * kb], wa[4 * kb + 1], wa[4 * kb + 2], wa[4 * kb + 3],
                   mkdesc(cx.sb + ((st + i) & 7) * FSTAGE, 16) + (k >> 2) * 512 + (k & 3) * 2, kb > 0);
        if (k == 11) wg_commit();
      }
      if (st < AST_F - 3 || !wg) bar_arrive(2 - wg, 256);
      wg_wait<1>();
      release(st, 1);
      release(st + 1, 1);
      bar_sync(BAR_FREE + wg, 160);
      wg_wait<0>();
      pin(acc);
      release(st + 2, 1);
#pragma unroll
      for (int k = 0; k < 4; k++)
        stsm4t(cx.sb + SM_H + wg * 8192 + k * 2048 + lt, pack2(acc[8 * k] * SM_SCALE_LOG2, acc[8 * k + 1] * SM_SCALE_LOG2),
               pack2(acc[8 * k + 2] * SM_SCALE_LOG2, acc[8 * k + 3] * SM_SCALE_LOG2),
               pack2(acc[8 * k + 4] * SM_SCALE_LOG2, acc[8 * k + 5] * SM_SCALE_LOG2),
               pack2(acc[8 * k + 6] * SM_SCALE_LOG2, acc[8 * k + 7] * SM_SCALE_LOG2));
      asm volatile("fence.proxy.async.shared::cta;" ::: "memory");
      bar_arrive(BAR_TILE + wg, 160);
    }
    bar_sync(3, 352);
  }
  prof(wg, 3);
#pragma unroll 1
  for (int unit = wg; unit < 27; unit += 2) {
    if (unit >> 1 == 9) {
      asm volatile("fence.proxy.async.shared::cta;" ::: "memory");
      bar_sync(3, 256);
      prof(wg, 4);
    }
    const bool gu = unit < 18;
    float a0[4], a1[4];
#pragma unroll 1
    for (int m = 0; m < 2; m++) {
      float p0[4], p1[4];
      int st = AST_F + (unit >> 1) * 12 + m * 6 + wg;
      uint32_t b = cx.sb + (gu ? SM_XSEL : SM_H + m * 9216);
#pragma unroll 1
      for (int u = 0; u < 3; u++, st += 2, b += 3072) {
        await(st);
        wg_fence();
        const uint64_t da = mkdesc(cx.sb + (st & 7) * FSTAGE, 16), db = mkdesc(b, 16);
#pragma unroll
        for (int k = 0; k < 12; k++) mma_n8((k & 1) ? p1 : p0, da + k * 128, db + (k >> 2) * 64 + (k & 3) * 2, u > 0 || k > 1);
        wg_commit();
        wg_wait<0>();
        release(st, 2);
      }
      pin(p0); pin(p1);
#pragma unroll
      for (int i = 0; i < 4; i++) { a0[i] = a1[i]; a1[i] = p0[i] + p1[i]; }
    }
#pragma unroll
    for (int i = 0; i < 4; i++) {
      const int fl = (cw & 3) * 16 + r + (i >> 1) * 8, tok = 2 * c + (i & 1);
      if (gu) {
        const float h = bfr(silu_f(bfr(a0[i]))) * bfr(a1[i]);
        *(__nv_bfloat16*)(cx.sp + SM_H + unit * 1024 + tok * 128 + (((fl >> 3) ^ tok) << 4) + (fl & 7) * 2) = __float2bfloat16_rn(h);
      } else {
        *at<float>(cx.gs->ypart, ((f * TOPC + tok) * DM + (unit - 18) * 64 + fl) * 4) = a0[i] + a1[i];
      }
    }
  }
  prof(wg, 5);
  bar_sync(3, 256);
  if (tid == 0) red_release(&cx.gs->ycnt);
  prof(wg, 6);
}

struct Maps { CUtensorMap m[9]; };
__global__ void __cluster_dims__(2, 1, 1) __launch_bounds__(THREADS, 1)
fused_kernel(const __nv_bfloat16* __restrict__ x, const __nv_bfloat16* __restrict__ w_r, const __nv_bfloat16* __restrict__ kc,
             const __nv_bfloat16* __restrict__ wo, __nv_bfloat16* __restrict__ out, Scratch* gs,
             const __grid_constant__ Maps maps) {
  const CUtensorMap &tmX = maps.m[0], &tmWq = maps.m[1], &tmK = maps.m[2], &tmV = maps.m[3], &tmWo = maps.m[4];
  extern __shared__ __align__(1024) uint8_t smem_raw[];
  prof(0, 23, 511);
  if (threadIdx.x < 72 && blockIdx.x < N_ATT_CTA)
    asm volatile("prefetch.global.L2 [%0];" ::"l"(at<const void>(x, ((blockIdx.x >> 3) * 128 + (blockIdx.x & 7) * 8) * (DM * 2) + threadIdx.x * 128)));
  Ctx cx;
  cx.sb = smem_u32(smem_raw);
  cx.sp = smem_raw;
  cx.gs = gs;
  cx.rank = blockIdx.x & 1;
  const int warp = __shfl_sync(0xffffffffu, threadIdx.x >> 5, 0);
  const int cluster = blockIdx.x >> 1;
  const bool is_aux = blockIdx.x >= N_ATT_CTA;
  const int c7 = ((cluster - 36) * 37) >> 8;
  const int hs = cluster < 4 ? 4 + cluster : cluster < 36 ? (cluster - 4) >> 3 : 4 + c7;
  const int qb = (cluster < 4 ? 0 : cluster < 36 ? (cluster - 4) & 7 : cluster - 35 - 7 * c7) * 2 + cx.rank;

  extern __shared__ __align__(1024) uint8_t smem_alias[];
  const uint32_t xf = smem_u32(smem_alias) + SM_MISC + warp * 24;
  if (warp == 4 && elect_one()) prefetch_tmap(&tmX);
  if (elect_one()) {
    const uint32_t cnt = (warp > 4 && warp < 8) ? (is_aux ? 2 : 4) : 1;
#pragma unroll
    for (int i = 0; i < 3; i++) mbar_init(xf + 8 * i, cnt);
    asm volatile("fence.proxy.async.shared::cta;" ::: "memory");
    asm volatile("fence.mbarrier_init.release.cluster;" ::: "memory");
  }
  __syncwarp();
  cluster_arrive();
  if (warp == 4 && !is_aux) {
    if (elect_one()) {
#pragma unroll
      for (int i = 0; i < 3; i++) {
        mbar_expect_tx(xf + 8 * i, 24576);
        tma3d(xf - SM_XFULL + SM_X + i * 24576, &tmX, qb * 128, i * 3, xf + 8 * i);
      }
    }
  } else if (warp > 7 && elect_one()) {
    prefetch_tmap(&tmX + (is_aux ? warp - 4 : warp == 8 ? 8 : warp - 8));
  }
  __syncwarp();

  if (warp < 4) {
    asm volatile("setmaxnreg.dec.sync.aligned.u32 24;");
    cluster_wait();
    prof(0, 24, 511);
    if (warp == 0) {
      if (!is_aux) attn_producer(cx, qb, hs, &tmX, &tmK, &tmV, &tmWq, &tmWo);
      else aux_producer(cx, blockIdx.x - N_ATT_CTA, &tmWq, &maps.m[5]);
      prof(0, 25, 511);
    } else if (!is_aux) {
      attn_rows(cx, qb, hs, 3 - warp, read_lane(), &maps.m[8], w_r);
      if (warp == 1) attn_helper(cx, qb, hs, read_lane(), wo, &maps.m[8]);
      else bar_sync(BAR_OA, 352);
      attn_finish8(cx, qb, hs, warp - 1, read_lane(), out);
    } else {
      aux_helper(cx, blockIdx.x - N_ATT_CTA, warp, read_lane());
    }
    __syncwarp();
    cluster_arrive();
    cluster_wait();
    if (threadIdx.x == 32) { dly(cx, 201); dly(cx, 251); }
  } else {
    asm volatile("setmaxnreg.inc.sync.aligned.u32 240;");
    cluster_wait();
    const int cw = warp - 4, wg = cw >> 2;
    if (is_aux) aux_consumer(cx, blockIdx.x - N_ATT_CTA, wg, cw, read_lane());
    else attn_consumer(cx, qb, hs, wg, cw, read_lane(), x, kc, out);
  }
}

typedef CUresult (*EncodeFn)(CUtensorMap*, CUtensorMapDataType, cuuint32_t, void*, const cuuint64_t*, const cuuint64_t*,
                             const cuuint32_t*, const cuuint32_t*, CUtensorMapInterleave, CUtensorMapSwizzle,
                             CUtensorMapL2promotion, CUtensorMapFloatOOBfill);

void encode(EncodeFn fn, CUtensorMap* m, const void* p, int rank, const cuuint64_t* dims, const cuuint64_t* strides,
            const cuuint32_t* box) {
  const cuuint32_t es[5] = {1, 1, 1, 1, 1};
  fn(m, CU_TENSOR_MAP_DATA_TYPE_BFLOAT16, rank, const_cast<void*>(p), dims, strides, box, es, CU_TENSOR_MAP_INTERLEAVE_NONE,
     CU_TENSOR_MAP_SWIZZLE_128B, CU_TENSOR_MAP_L2_PROMOTION_L2_128B, CU_TENSOR_MAP_FLOAT_OOB_FILL_NONE);
}
void encode2d(EncodeFn fn, CUtensorMap* m, const void* p, uint64_t rows, uint64_t cols, uint32_t box_rows) {
  const cuuint64_t dims[2] = {cols, rows}, strides[1] = {cols * 2};
  const cuuint32_t box[2] = {64, box_rows};
  encode(fn, m, p, 2, dims, strides, box);
}

}

extern "C" void kernel_launch(void* const* d_in, const int* in_sizes, int n_in, void* d_out, int out_size) {
  (void)in_sizes; (void)n_in; (void)out_size;
  void* fnp = nullptr;
  cudaDriverEntryPointQueryResult qr;
  cudaGetDriverEntryPoint("cuTensorMapEncodeTiled", &fnp, cudaEnableDefault, &qr);
  EncodeFn fn = (EncodeFn)fnp;
  void* gs = nullptr;
  cudaGetSymbolAddress(&gs, g_scratch);
  Maps maps;
  CUtensorMap &tmX = maps.m[0], &tmWq = maps.m[1], &tmK = maps.m[2], &tmV = maps.m[3], &tmWo = maps.m[4], &tmG = maps.m[5],
              &tmU = maps.m[6], &tmD = maps.m[7];
  encode2d(fn, &tmK, d_in[1], 16 * SEQ, DH, 128);
  encode2d(fn, &tmV, d_in[2], 16 * SEQ, DH, 128);
  encode2d(fn, &tmWq, d_in[3], DM, 4096, 64);
  {
    const cuuint64_t dims[3] = {64, SEQ, 9}, strides[2] = {DM * 2, 128};
    const cuuint32_t box[3] = {64, 64, 3};
    encode(fn, &tmX, d_in[0], 3, dims, strides, box);
  }
  encode2d(fn, &maps.m[8], d_in[0], SEQ, DM, 16);
  encode2d(fn, &tmWo, d_in[4], 4096, DM, 128);
  encode2d(fn, &tmG, d_in[7], DM, FF, 192);
  encode2d(fn, &tmU, d_in[8], DM, FF, 192);
  encode2d(fn, &tmD, d_in[9], FF, DM, 192);
  cudaFuncSetAttribute(fused_kernel, cudaFuncAttributeMaxDynamicSharedMemorySize, SM_TOTAL);
  fused_kernel<<<N_CTA, THREADS, SM_TOTAL>>>((const __nv_bfloat16*)d_in[0], (const __nv_bfloat16*)d_in[6], (const __nv_bfloat16*)d_in[1],
                                            (const __nv_bfloat16*)d_in[4], (__nv_bfloat16*)d_out, (Scratch*)gs, maps);
}
```
